```python
import torch

def _softmax(x, axis=-1):
    return torch.softmax(x, dim=axis)
def _gelu(x):
    return torch.nn.functional.gelu(x, approximate="tanh")
def _silu(x):
    return torch.nn.functional.silu(x)
def _sigmoid(x):
    return torch.sigmoid(x)
def _layernorm(x, axis=-1, eps=1e-5):
    m = x.mean(dim=axis, keepdim=True)
    v = x.var(dim=axis, keepdim=True, unbiased=False)
    return (x - m) / torch.sqrt(v + eps)
def _scatter_add(tgt, idx, src, axis=0):
    return tgt.clone().index_add_(axis, idx, src)
def _segment_sum(src, seg, n):
    out = torch.zeros((n,) + src.shape[1:], dtype=src.dtype)
    return out.index_add_(0, seg, src)
def _pad(x, pw):
    flat = tuple(v for pair in reversed(pw) for v in pair)
    return torch.nn.functional.pad(x, flat)

kernel_name = 'parallel_sum__linear_attn_block__glu_gated_swiglu__prompt'

def setup_inputs():

    _w = (lambda a: (lambda t: t.to(torch.bfloat16) if t.is_floating_point() else t)(torch.as_tensor(a)))
    def _A_setup():
        B, S, D = 1, 2048, 512
        return {
            "x": _w((lambda *s: torch.randn(*s, dtype=torch.bfloat16) * 0.05)(B, S, D)),
            "wqkv": _w((lambda *s: torch.randn(*s, dtype=torch.bfloat16) * 0.05)(D, 3 * D)),
            "wo": _w((lambda *s: torch.randn(*s, dtype=torch.bfloat16) * 0.05)(D, D)),
        }
    _A_in = _A_setup()

    def _B_setup():
        B, S, D, F = 1, 2048, 512, 1792
        return {
            "x": _w((lambda *s: torch.randn(*s, dtype=torch.bfloat16) * 0.05)(B, S, D)),
            "w1": _w((lambda *s: torch.randn(*s, dtype=torch.bfloat16) * 0.2)(D, F) * (2.0 / D) ** 0.5),
            "w3": _w((lambda *s: torch.randn(*s, dtype=torch.bfloat16) * 0.2)(D, F) * (2.0 / D) ** 0.5),
            "w2": _w((lambda *s: torch.randn(*s, dtype=torch.bfloat16) * 0.2)(F, D) * (2.0 / F) ** 0.5),
        }
    _B_in = _B_setup()

    return {
        "A_x": _A_in["x"],
        "A_wqkv": _A_in["wqkv"],
        "A_wo": _A_in["wo"],
        "B_x": _B_in["x"],
        "B_w1": _B_in["w1"],
        "B_w3": _B_in["w3"],
        "B_w2": _B_in["w2"],
    }

def reference(A_x, A_wqkv, A_wo, B_x, B_w1, B_w3, B_w2):
    def _A_ref(x, wqkv, wo):
        B, S, D = x.shape
        H = 32; Dh = D // H
        qkv = (lambda x, *d: x.permute(*d))((x @ wqkv).reshape(B, S, 3, H, Dh), 2, 0, 3, 1, 4)
        q, k, v = qkv[0], qkv[1], qkv[2]
        phi = lambda t: torch.where(t > 0, t + 1, torch.exp(t)) + 1e-6
        pq, pk = phi(q), phi(k)
        kv = torch.einsum("bhsd,bhse->bhde", pk, v)
        z = torch.einsum("bhsd->bhd", pk)
        num = torch.einsum("bhqd,bhde->bhqe", pq, kv)
        den = torch.einsum("bhqd,bhd->bhq", pq, z)[..., None] + 1e-6
        o = num / den
        return (lambda x, *d: x.permute(*d))(o, 0, 2, 1, 3).reshape(B, S, D) @ wo

    def _B_ref(x, w1, w3, w2):
        gate = torch.einsum("bsd,df->bsf", x, w1)
        up = torch.einsum("bsd,df->bsf", x, w3)
        h = _silu(gate) * up
        out = torch.einsum("bsf,fd->bsd", h, w2)
        return out

    x = A_x
    xn = _layernorm(x, axis=-1)
    return x + _A_ref(xn, A_wqkv, A_wo) + _B_ref(xn, B_w1, B_w3, B_w2)
```

```cpp
#include <cuda_runtime.h>
#include <cuda_bf16.h>
#include <cuda.h>
#include <stdint.h>

namespace {

constexpr int NST = 11;
constexpr int STAGE_BYTES = 16384;
constexpr int XST0 = 3;
constexpr int OFF_STG = NST * STAGE_BYTES;
constexpr int OFF_MISC = OFF_STG + 32768;
constexpr int OFF_KVFRAG = OFF_MISC;
constexpr int OFF_KVSUM = OFF_MISC + 3072;
constexpr int OFF_ONES = OFF_MISC + 7424;
constexpr int OFF_BARS = OFF_MISC + 7680;
constexpr int BAR_FULL = OFF_BARS;
constexpr int BAR_EMPTY = BAR_FULL + 8 * NST;
constexpr int BAR_XFULL = BAR_EMPTY + 8 * NST;
constexpr int BAR_KVREADY = BAR_XFULL + 64;
constexpr int BAR_XCHG = BAR_KVREADY + 8;
constexpr int OFF_EPOCH = BAR_XCHG + 8;
constexpr int SMEM_BYTES = OFF_MISC + 8192;

constexpr unsigned SPIN_LIMIT = 1u << 24;

__device__ uint4 g_A2[16 * 2 * 18 * 4 * 256];
__device__ float4 g_kvp[8 * 32 * 272];
__device__ float4 g_kvs[8 * 272];
__device__ unsigned g_a2flag[16 * 8 * 4 * 2];
__device__ unsigned g_kvflag[8 * 32];
__device__ unsigned g_kvflag2[8 * 16];
__device__ unsigned g_epoch;
__device__ unsigned g_ticket;

__device__ __forceinline__ uint32_t smem_u32(const void* p) { return (uint32_t)__cvta_generic_to_shared(p); }
__device__ __forceinline__ void mbar_init(uint32_t bar, uint32_t cnt) {
    asm volatile("mbarrier.init.shared::cta.b64 [%0], %1;" ::"r"(bar), "r"(cnt) : "memory");
}
__device__ __forceinline__ void mbar_expect_tx(uint32_t bar, uint32_t bytes) {
    asm volatile("mbarrier.arrive.expect_tx.shared::cta.b64 _, [%0], %1;" ::"r"(bar), "r"(bytes) : "memory");
}
__device__ __forceinline__ void mbar_arrive(uint32_t bar) {
    asm volatile("mbarrier.arrive.shared::cta.b64 _, [%0];" ::"r"(bar) : "memory");
}
__device__ __forceinline__ void mbar_arrive_cta(uint32_t bar, uint32_t cta) {
    asm volatile(
        "{\n.reg .b32 ra;\nmapa.shared::cluster.u32 ra, %0, %1;\n"
        "mbarrier.arrive.shared::cluster.b64 _, [ra];\n}" ::"r"(bar), "r"(cta) : "memory");
}
__device__ __forceinline__ void mbar_wait(uint32_t bar, uint32_t parity) {
    asm volatile(
        "{\n.reg .pred p, q;\n.reg .u32 n;\nmov.u32 n, 0;\n"
        "WAIT_%=:\n"
        "mbarrier.try_wait.parity.shared::cta.b64 p, [%0], %1;\n"
        "@p bra.uni DONE_%=;\n"
        "add.u32 n, n, 1;\n"
        "setp.gt.u32 q, n, %2;\n"
        "@q trap;\n"
        "bra.uni WAIT_%=;\n"
        "DONE_%=:\n}"
        ::"r"(bar), "r"(parity), "n"(SPIN_LIMIT) : "memory");
}
__device__ __forceinline__ unsigned ld_acquire(const unsigned* p) {
    unsigned v;
    asm volatile("ld.acquire.gpu.global.u32 %0, [%1];" : "=r"(v) : "l"(p) : "memory");
    return v;
}
__device__ __forceinline__ void st_release(unsigned* p, unsigned v) {
    asm volatile("st.release.gpu.global.u32 [%0], %1;" ::"l"(p), "r"(v) : "memory");
}
__device__ __forceinline__ void wait_flag(const unsigned* p, unsigned epoch) {
    asm volatile(
        "{\n.reg .pred p, q;\n.reg .u32 n, v;\nmov.u32 n, 0;\n"
        "WAIT_%=:\n"
        "ld.acquire.gpu.global.u32 v, [%0];\n"
        "setp.eq.u32 p, v, %1;\n"
        "@p bra DONE_%=;\n"
        "nanosleep.u32 32;\n"
        "add.u32 n, n, 1;\n"
        "setp.gt.u32 q, n, %2;\n"
        "@q trap;\n"
        "bra WAIT_%=;\n"
        "DONE_%=:\n}"
        ::"l"(p), "r"(epoch), "n"(SPIN_LIMIT) : "memory");
}
__device__ __forceinline__ void tma_load(uint32_t dst, const CUtensorMap* tm, uint32_t bar, int x, int y) {
    asm volatile(
        "cp.async.bulk.tensor.2d.shared::cluster.global.mbarrier::complete_tx::bytes [%0], [%1, {%3, %4}], [%2];"
        ::"r"(dst), "l"(tm), "r"(bar), "r"(x), "r"(y) : "memory");
}
__device__ __forceinline__ void tma_load_mc(uint32_t dst, const CUtensorMap* tm, uint32_t bar, int x, int y) {
    asm volatile(
        "cp.async.bulk.tensor.2d.shared::cluster.global.mbarrier::complete_tx::bytes.multicast::cluster "
        "[%0], [%1, {%3, %4}], [%2], %5;"
        ::"r"(dst), "l"(tm), "r"(bar), "r"(x), "r"(y), "h"((uint16_t)3) : "memory");
}
__device__ __forceinline__ void prefetch_tm(const CUtensorMap* tm) {
    asm volatile("prefetch.tensormap [%0];" ::"l"(tm) : "memory");
}
__device__ __forceinline__ void bar_sync(int id, int n) { asm volatile("bar.sync %0, %1;" ::"r"(id), "r"(n) : "memory"); }
__device__ __forceinline__ void bar_arrive(int id, int n) { asm volatile("bar.arrive %0, %1;" ::"r"(id), "r"(n) : "memory"); }
__device__ __forceinline__ void wg_fence() { asm volatile("wgmma.fence.sync.aligned;" ::: "memory"); }
__device__ __forceinline__ void wg_commit() { asm volatile("wgmma.commit_group.sync.aligned;" ::: "memory"); }
template <int N>
__device__ __forceinline__ void wg_wait() { asm volatile("wgmma.wait_group.sync.aligned %0;" ::"n"(N) : "memory"); }

__device__ __forceinline__ uint64_t make_desc(uint32_t addr, uint32_t lbo, uint32_t sbo, uint64_t swz) {
    return (uint64_t)((addr & 0x3FFFF) >> 4) | ((uint64_t)(lbo >> 4) << 16) | ((uint64_t)(sbo >> 4) << 32) | (swz << 62);
}

#define ACC8(a, o) "+f"(a[o]), "+f"(a[o + 1]), "+f"(a[o + 2]), "+f"(a[o + 3]), "+f"(a[o + 4]), "+f"(a[o + 5]), "+f"(a[o + 6]), "+f"(a[o + 7])
__device__ __forceinline__ void wgmma_n128_rs(float (&d)[64], const uint32_t* a, uint64_t db, int scale_d) {
    asm volatile(
        "{\n.reg .pred p;\nsetp.ne.b32 p, %69, 0;\n"
        "wgmma.mma_async.sync.aligned.m64n128k16.f32.bf16.bf16 "
        "{%0,%1,%2,%3,%4,%5,%6,%7,%8,%9,%10,%11,%12,%13,%14,%15,%16,%17,%18,%19,%20,%21,%22,%23,%24,%25,%26,%27,%28,%29,%30,%31,"
        "%32,%33,%34,%35,%36,%37,%38,%39,%40,%41,%42,%43,%44,%45,%46,%47,%48,%49,%50,%51,%52,%53,%54,%55,%56,%57,%58,%59,%60,%61,%62,%63},"
        "{%64,%65,%66,%67}, %68, p, 1, 1, 1;\n}"
        : ACC8(d, 0), ACC8(d, 8), ACC8(d, 16), ACC8(d, 24), ACC8(d, 32), ACC8(d, 40), ACC8(d, 48), ACC8(d, 56)
        : "r"(a[0]), "r"(a[1]), "r"(a[2]), "r"(a[3]), "l"(db), "r"(scale_d));
}
__device__ __forceinline__ void wgmma_n64_rs(float (&d)[32], const uint32_t* a, uint64_t db, int scale_d) {
    asm volatile(
        "{\n.reg .pred p;\nsetp.ne.b32 p, %37, 0;\n"
        "wgmma.mma_async.sync.aligned.m64n64k16.f32.bf16.bf16 "
        "{%0,%1,%2,%3,%4,%5,%6,%7,%8,%9,%10,%11,%12,%13,%14,%15,%16,%17,%18,%19,%20,%21,%22,%23,%24,%25,%26,%27,%28,%29,%30,%31},"
        "{%32,%33,%34,%35}, %36, p, 1, 1, 1;\n}"
        : ACC8(d, 0), ACC8(d, 8), ACC8(d, 16), ACC8(d, 24)
        : "r"(a[0]), "r"(a[1]), "r"(a[2]), "r"(a[3]), "l"(db), "r"(scale_d));
}
__device__ __forceinline__ void wgmma_n64_ss_tt(float (&d)[32], uint64_t da, uint64_t db, int scale_d) {
    asm volatile(
        "{\n.reg .pred p;\nsetp.ne.b32 p, %34, 0;\n"
        "wgmma.mma_async.sync.aligned.m64n64k16.f32.bf16.bf16 "
        "{%0,%1,%2,%3,%4,%5,%6,%7,%8,%9,%10,%11,%12,%13,%14,%15,%16,%17,%18,%19,%20,%21,%22,%23,%24,%25,%26,%27,%28,%29,%30,%31},"
        "%32, %33, p, 1, 1, 1, 1;\n}"
        : ACC8(d, 0), ACC8(d, 8), ACC8(d, 16), ACC8(d, 24)
        : "l"(da), "l"(db), "r"(scale_d));
}
__device__ __forceinline__ void wgmma_n8_ss_tn(float (&d)[4], uint64_t da, uint64_t db, int scale_d) {
    asm volatile(
        "{\n.reg .pred p;\nsetp.ne.b32 p, %6, 0;\n"
        "wgmma.mma_async.sync.aligned.m64n8k16.f32.bf16.bf16 {%0,%1,%2,%3}, %4, %5, p, 1, 1, 1, 0;\n}"
        : "+f"(d[0]), "+f"(d[1]), "+f"(d[2]), "+f"(d[3])
        : "l"(da), "l"(db), "r"(scale_d));
}
template <int N>
__device__ __forceinline__ void acc_fence(float (&d)[N]) {
#pragma unroll
    for (int i = 0; i < N; i++) asm volatile("" : "+f"(d[i])::"memory");
}
__device__ __forceinline__ void mma16816(float (&c)[4], const uint32_t* a, uint32_t b0, uint32_t b1) {
    asm volatile(
        "mma.sync.aligned.m16n8k16.row.col.f32.bf16.bf16.f32 {%0,%1,%2,%3}, {%4,%5,%6,%7}, {%8,%9}, {%0,%1,%2,%3};"
        : "+f"(c[0]), "+f"(c[1]), "+f"(c[2]), "+f"(c[3])
        : "r"(a[0]), "r"(a[1]), "r"(a[2]), "r"(a[3]), "r"(b0), "r"(b1));
}
__device__ __forceinline__ uint32_t pack_bf16(float lo, float hi) {
    uint32_t r;
    asm("cvt.rn.bf16x2.f32 %0, %1, %2;" : "=r"(r) : "f"(hi), "f"(lo));
    return r;
}
__device__ __forceinline__ float bf_lo(uint32_t v) { return __uint_as_float(v << 16); }
__device__ __forceinline__ float bf_hi(uint32_t v) { return __uint_as_float(v & 0xffff0000u); }
__device__ __forceinline__ float bf16_round(float v) { return __bfloat162float(__float2bfloat16_rn(v)); }
__device__ __forceinline__ float phi_f(float t) { return (t > 0.f ? t + 1.f : __expf(t)) + 1e-6f; }
__device__ __forceinline__ float swiglu_f(float g, float u) { return __fdividef(g, 1.f + __expf(-g)) * u; }

struct Ring {
    int st;
    uint32_t ph;
    __device__ __forceinline__ void next() {
        if (++st == NST) { st = 0; ph ^= 1; }
    }
};

__device__ __forceinline__ void mainloop128(float (&acc)[64], const uint32_t (&xa)[128], Ring& rg, uint32_t sb,
                                            uint64_t desc128, int lane) {
    int prev_st = 0;
#pragma unroll
    for (int kb = 0; kb < 8; kb++) {
        mbar_wait(sb + BAR_FULL + 8 * rg.st, rg.ph);
        wg_fence();
        const uint64_t d = desc128 + (uint64_t)(rg.st * (STAGE_BYTES >> 4));
#pragma unroll
        for (int ks = 0; ks < 4; ks++) wgmma_n128_rs(acc, &xa[(kb * 4 + ks) * 4], d + ks * 128, (kb | ks) != 0);
        wg_commit();
        if (kb > 0) {
            wg_wait<1>();
            if (lane < 2) mbar_arrive_cta(sb + BAR_EMPTY + 8 * prev_st, lane);
        }
        prev_st = rg.st;
        rg.next();
    }
    wg_wait<0>();
    acc_fence(acc);
    if (lane < 2) mbar_arrive_cta(sb + BAR_EMPTY + 8 * prev_st, lane);
}
__device__ __forceinline__ void mainloop64x2(float (&a0)[32], float (&a1)[32], const uint32_t (&xa)[128], Ring& rg,
                                             uint32_t sb, uint64_t desc128, uint64_t desc64, int lane) {
    int prev_st = 0;
#pragma unroll
    for (int kb = 0; kb < 8; kb++) {
        mbar_wait(sb + BAR_FULL + 8 * rg.st, rg.ph);
        wg_fence();
        const uint64_t d = desc128 + (uint64_t)(rg.st * (STAGE_BYTES >> 4));
        const uint64_t d2 = desc64 + (uint64_t)(rg.st * (STAGE_BYTES >> 4));
#pragma unroll
        for (int ks = 0; ks < 4; ks++) {
            wgmma_n64_rs(a0, &xa[(kb * 4 + ks) * 4], d + ks * 128, (kb | ks) != 0);
            wgmma_n64_rs(a1, &xa[(kb * 4 + ks) * 4], d2 + ks * 64, (kb | ks) != 0);
        }
        wg_commit();
        if (kb > 0) {
            wg_wait<1>();
            if (lane < 2) mbar_arrive_cta(sb + BAR_EMPTY + 8 * prev_st, lane);
        }
        prev_st = rg.st;
        rg.next();
    }
    wg_wait<0>();
    acc_fence(a0);
    acc_fence(a1);
    if (lane < 2) mbar_arrive_cta(sb + BAR_EMPTY + 8 * prev_st, lane);
}

__global__ void __cluster_dims__(2, 1, 1) __launch_bounds__(384, 1)
fused_kernel(const __grid_constant__ CUtensorMap tm_x, const __grid_constant__ CUtensorMap tm_qkv,
             const __grid_constant__ CUtensorMap tm_w1, const __grid_constant__ CUtensorMap tm_w3,
             const __grid_constant__ CUtensorMap tm_w1h, const __grid_constant__ CUtensorMap tm_w3h,
             const __grid_constant__ CUtensorMap tm_w2, const __grid_constant__ CUtensorMap tm_w2h,
             const __grid_constant__ CUtensorMap tm_wo, const __nv_bfloat16* __restrict__ xg,
             __nv_bfloat16* __restrict__ outg) {
    extern __shared__ __align__(1024) uint8_t smem[];
    const uint32_t sb = smem_u32(smem);
    const int tid = threadIdx.x;
    const int warp = tid >> 5, lane = tid & 31;
    const int rank = blockIdx.x & 1;
    const int pair = blockIdx.x >> 1;
    const int c = pair & 7;
    const int m = (pair >> 3) * 2 + rank;
    const int m2 = (pair >> 3) * 2 + (c & 1);
    const int j2 = c >> 1;

    if (tid == 256) {
        if (sb & 1023) __trap();
        for (int i = 0; i < NST; i++) {
            mbar_init(sb + BAR_FULL + 8 * i, 1);
            mbar_init(sb + BAR_EMPTY + 8 * i, 16);
        }
        for (int i = 0; i < 8; i++) mbar_init(sb + BAR_XFULL + 8 * i, 1);
        mbar_init(sb + BAR_KVREADY, 1);
        mbar_init(sb + BAR_XCHG, 1);
        asm volatile("fence.mbarrier_init.release.cluster;" ::: "memory");
        asm volatile("fence.proxy.async.shared::cta;" ::: "memory");
        mbar_expect_tx(sb + BAR_XCHG, 32768);
        for (int kb = 0; kb < 8; kb++) {
            mbar_expect_tx(sb + BAR_XFULL + 8 * kb, 16384);
            tma_load(sb + (XST0 + kb) * STAGE_BYTES, &tm_x, sb + BAR_XFULL + 8 * kb, kb * 64, m * 128);
        }
        unsigned e = *(volatile unsigned*)&g_epoch + 1;
        *(volatile unsigned*)(smem + OFF_EPOCH) = e;
        __threadfence();
        unsigned t = atomicInc(&g_ticket, 127u);
        if (t == 127u) *(volatile unsigned*)&g_epoch = e;
    } else if (tid == 288) {
        prefetch_tm(&tm_qkv); prefetch_tm(&tm_w1); prefetch_tm(&tm_w3); prefetch_tm(&tm_w1h);
        prefetch_tm(&tm_w3h); prefetch_tm(&tm_w2); prefetch_tm(&tm_w2h); prefetch_tm(&tm_wo);
    } else if (tid >= 320) {
        ((uint32_t*)(smem + OFF_ONES))[tid - 320] = 0x3F803F80u;
        asm volatile("fence.proxy.async.shared::cta;" ::: "memory");
    }
    __syncthreads();
    asm volatile("barrier.cluster.arrive.release.aligned;\nbarrier.cluster.wait.acquire.aligned;" ::: "memory");
    const unsigned epoch = *(volatile unsigned*)(smem + OFF_EPOCH);

    if (warp >= 8) {
        asm volatile("setmaxnreg.dec.sync.aligned.u32 40;");
        if (warp == 8) {
            if (lane == 0) {
                int st = 0;
                uint32_t lap = 0;
                for (int it = 0; it < 40; it++) {
                    const int tile = it >> 3, kb = it & 7;
                    const uint32_t full = sb + BAR_FULL + 8 * st;
                    mbar_wait(sb + BAR_EMPTY + 8 * st, (st >= XST0) ? (lap & 1) : ((lap & 1) ^ 1));
                    mbar_expect_tx(full, STAGE_BYTES);
                    const uint32_t dst = sb + st * STAGE_BYTES;
                    if (tile == 0) {
                        tma_load_mc(dst + rank * 8192, &tm_qkv, full, 512 + 512 * rank + 64 * c, kb * 64);
                    } else if (tile < 4) {
                        tma_load_mc(dst + rank * 8192, rank ? &tm_w3 : &tm_w1, full, 224 * c + 64 * (tile - 1), kb * 64);
                    } else if (rank == 0) {
                        tma_load_mc(dst, &tm_qkv, full, 64 * c, kb * 64);
                    } else {
                        tma_load_mc(dst + 8192, &tm_w1h, full, 224 * c + 192, kb * 64);
                        tma_load_mc(dst + 12288, &tm_w3h, full, 224 * c + 192, kb * 64);
                    }
                    if (++st == NST) { st = 0; lap++; }
                }
                const unsigned* fl = g_a2flag + (m2 * 8 + rank * 4) * 8;
                for (int b = 0; b < 18; b++) {
                    const uint32_t full = sb + BAR_FULL + 8 * st;
                    const uint32_t dst = sb + st * STAGE_BYTES;
                    if (b < 12) {
                        const unsigned* f = fl + (b & 3) * 8 + (b >> 2) * 2;
                        wait_flag(f, epoch);
                        wait_flag(f + 1, epoch);
                    } else if (b < 14) {
                        const unsigned* f = fl + (b - 12) * 16 + 6;
                        wait_flag(f, epoch);
                        wait_flag(f + 1, epoch);
                        wait_flag(f + 8, epoch);
                        wait_flag(f + 9, epoch);
                    }
                    mbar_wait(sb + BAR_EMPTY + 8 * st, (st >= XST0) ? (lap & 1) : ((lap & 1) ^ 1));
                    mbar_expect_tx(full, STAGE_BYTES);
                    if (b < 12) {
                        const int row = 224 * (4 * rank + (b & 3)) + 64 * (b >> 2);
                        tma_load(dst, &tm_w2, full, 128 * j2, row);
                        tma_load(dst + 8192, &tm_w2, full, 128 * j2 + 64, row);
                    } else if (b < 14) {
                        const int row = 224 * (4 * rank + 2 * (b - 12)) + 192;
                        tma_load(dst, &tm_w2h, full, 128 * j2, row);
                        tma_load(dst + 4096, &tm_w2h, full, 128 * j2, row + 224);
                        tma_load(dst + 8192, &tm_w2h, full, 128 * j2 + 64, row);
                        tma_load(dst + 12288, &tm_w2h, full, 128 * j2 + 64, row + 224);
                    } else {
                        const int row = 64 * (4 * rank + (b - 14));
                        tma_load(dst, &tm_wo, full, 128 * j2, row);
                        tma_load(dst + 8192, &tm_wo, full, 128 * j2 + 64, row);
                    }
                    if (++st == NST) { st = 0; lap++; }
                }
            }
        } else if (warp < 11) {
            const int wg = warp - 9;
            for (int t = 0; t < 5; t++) {
                bar_sync(3 + wg * 2 + (t & 1), 160);
                if (lane == 0) {
                    __threadfence();
                    if (t == 0) st_release(&g_kvflag[c * 32 + m * 2 + wg], epoch);
                    else st_release(&g_a2flag[((m * 8 + c) * 4 + (t - 1)) * 2 + wg], epoch);
                }
            }
        } else {
            wait_flag(&g_kvflag[c * 32 + lane], epoch);
            __syncwarp();
            if (lane < 17) {
                const float4* src = g_kvp + (size_t)c * 32 * 272 + m * 17 + lane;
                float4 s = make_float4(0.f, 0.f, 0.f, 0.f);
#pragma unroll 8
                for (int p = 0; p < 32; p++) {
                    float4 v = __ldcg(src + p * 272);
                    s.x += v.x; s.y += v.y; s.z += v.z; s.w += v.w;
                }
                g_kvs[c * 272 + m * 17 + lane] = s;
            }
            __syncwarp();
            if (lane == 0) {
                __threadfence();
                st_release(&g_kvflag2[c * 16 + m], epoch);
            }
            if (lane < 16) wait_flag(&g_kvflag2[c * 16 + lane], epoch);
            __syncwarp();
            float4* ks4 = (float4*)(smem + OFF_KVSUM);
            for (int i = lane; i < 272; i += 32) ks4[i] = __ldcg(g_kvs + c * 272 + i);
            __syncwarp();
            const float* ks = (const float*)(smem + OFF_KVSUM);
            uint2* kf = (uint2*)(smem + OFF_KVFRAG);
            const int g = lane >> 2, t = lane & 3;
            for (int hh = 0; hh < 4; hh++) {
                const float* k = ks + hh * 272;
                for (int b = 0; b < 2; b++) {
                    uint2 v;
                    v.x = pack_bf16(k[(2 * t) * 16 + 8 * b + g], k[(2 * t + 1) * 16 + 8 * b + g]);
                    v.y = pack_bf16(k[(2 * t + 8) * 16 + 8 * b + g], k[(2 * t + 9) * 16 + 8 * b + g]);
                    kf[(hh * 3 + b) * 32 + lane] = v;
                }
                uint2 z;
                z.x = pack_bf16(k[256 + 2 * t], k[256 + 2 * t + 1]);
                z.y = pack_bf16(k[256 + 2 * t + 8], k[256 + 2 * t + 9]);
                kf[(hh * 3 + 2) * 32 + lane] = z;
            }
            __syncwarp();
            if (lane == 0) mbar_arrive(sb + BAR_KVREADY);
        }
    } else {
        asm volatile("setmaxnreg.inc.sync.aligned.u32 232;");
        const int wg = warp >> 2, w = warp & 3;
        const int g = lane >> 2, t = lane & 3;
        float acc[64];
        uint32_t xa[128];
        float rho0, rho1;

        {
            const int row = wg * 64 + w * 16 + (lane & 7) + ((lane >> 3) & 1) * 8;
            const uint32_t rbase = sb + XST0 * STAGE_BYTES + row * 128;
            const int hi = lane >> 4, r7 = lane & 7;
            float s0[4] = {0.f, 0.f, 0.f, 0.f}, s1[4] = {0.f, 0.f, 0.f, 0.f};
#pragma unroll
            for (int kb = 0; kb < 8; kb++) {
                mbar_wait(sb + BAR_XFULL + 8 * kb, 0);
#pragma unroll
                for (int ks = 0; ks < 4; ks++) {
                    uint32_t* a = &xa[(kb * 4 + ks) * 4];
                    const uint32_t addr = rbase + kb * STAGE_BYTES + (((2 * ks + hi) ^ r7) << 4);
                    asm volatile("ldmatrix.sync.aligned.m8n8.x4.shared.b16 {%0,%1,%2,%3}, [%4];"
                                 : "=r"(a[0]), "=r"(a[1]), "=r"(a[2]), "=r"(a[3]) : "r"(addr) : "memory");
                    if (ks & 1) mma16816(s1, a, 0x3F803F80u, 0x3F803F80u);
                    else mma16816(s0, a, 0x3F803F80u, 0x3F803F80u);
                }
            }
            const float mean0 = (s0[0] + s1[0]) * (1.f / 512.f), mean1 = (s0[2] + s1[2]) * (1.f / 512.f);
            __syncwarp();
            if (lane < 16) mbar_arrive_cta(sb + BAR_EMPTY + 8 * (XST0 + (lane >> 1)), lane & 1);
            const __nv_bfloat162 mb0 = __float2bfloat162_rn(mean0), mb1 = __float2bfloat162_rn(mean1);
#pragma unroll
            for (int i = 0; i < 128; i++) {
                __nv_bfloat162 v = *reinterpret_cast<__nv_bfloat162*>(&xa[i]);
                v = __hsub2(v, (i & 1) ? mb1 : mb0);
                xa[i] = *reinterpret_cast<uint32_t*>(&v);
            }
            float q0 = 0.f, q1 = 0.f, q2 = 0.f, q3 = 0.f;
#pragma unroll
            for (int i = 0; i < 128; i += 2) {
                float a0 = bf_lo(xa[i]), a1 = bf_hi(xa[i]), b0 = bf_lo(xa[i + 1]), b1 = bf_hi(xa[i + 1]);
                q0 = fmaf(a0, a0, q0); q1 = fmaf(a1, a1, q1);
                q2 = fmaf(b0, b0, q2); q3 = fmaf(b1, b1, q3);
            }
            q0 += q1; q2 += q3;
            q0 += __shfl_xor_sync(0xffffffffu, q0, 1); q2 += __shfl_xor_sync(0xffffffffu, q2, 1);
            q0 += __shfl_xor_sync(0xffffffffu, q0, 2); q2 += __shfl_xor_sync(0xffffffffu, q2, 2);
            const float dm0 = mean0 - __low2float(mb0), dm1 = mean1 - __low2float(mb1);
            const float var0 = fmaxf(q0 * (1.f / 512.f) - dm0 * dm0, 0.f), var1 = fmaxf(q2 * (1.f / 512.f) - dm1 * dm1, 0.f);
            rho0 = 1.f / bf16_round(sqrtf(bf16_round(bf16_round(var0) + 1e-5f)));
            rho1 = 1.f / bf16_round(sqrtf(bf16_round(bf16_round(var1) + 1e-5f)));
        }

        Ring rg = {0, 0};
        const uint64_t desc128 = make_desc(sb, 8192, 1024, 1);
        const uint64_t desc64 = make_desc(sb + 8192, 4096, 512, 2);
        uint4* a2w = g_A2 + (size_t)((m * 2 + (c >> 2)) * 18) * 4 * 256 + warp * 32 + lane;
        const int cc = c & 3;

#pragma unroll 1
        for (int tile = 0; tile < 4; tile++) {
            mainloop128(acc, xa, rg, sb, desc128, lane);

            if (tile == 0) {
                const uint32_t pkb = sb + OFF_STG + wg * 16384;
                const uint32_t r0 = pkb + (w * 16 + g) * 128 + t * 4;
#pragma unroll
                for (int nb = 0; nb < 8; nb++) {
                    const uint32_t off = (uint32_t)((nb ^ g) << 4);
                    uint32_t p0 = pack_bf16(phi_f(acc[nb * 4] * rho0), phi_f(acc[nb * 4 + 1] * rho0));
                    uint32_t p1 = pack_bf16(phi_f(acc[nb * 4 + 2] * rho1), phi_f(acc[nb * 4 + 3] * rho1));
                    uint32_t v0 = pack_bf16(acc[32 + nb * 4] * rho0, acc[32 + nb * 4 + 1] * rho0);
                    uint32_t v1 = pack_bf16(acc[32 + nb * 4 + 2] * rho1, acc[32 + nb * 4 + 3] * rho1);
                    asm volatile("st.shared.u32 [%0], %1;" ::"r"(r0 + off), "r"(p0) : "memory");
                    asm volatile("st.shared.u32 [%0], %1;" ::"r"(r0 + off + 1024), "r"(p1) : "memory");
                    asm volatile("st.shared.u32 [%0], %1;" ::"r"(r0 + off + 8192), "r"(v0) : "memory");
                    asm volatile("st.shared.u32 [%0], %1;" ::"r"(r0 + off + 8192 + 1024), "r"(v1) : "memory");
                }
                asm volatile("fence.proxy.async.shared::cta;" ::: "memory");
                bar_sync(1 + wg, 128);
                const uint64_t da = make_desc(pkb, 8192, 1024, 1);
                const uint64_t db = make_desc(pkb + 8192, 8192, 1024, 1);
                const uint64_t d1 = make_desc(sb + OFF_ONES, 128, 128, 0);
                float kva[32], za[4];
                wg_fence();
#pragma unroll
                for (int ks = 0; ks < 4; ks++) {
                    wgmma_n64_ss_tt(kva, da + ks * 128, db + ks * 128, ks != 0);
                    wgmma_n8_ss_tn(za, da + ks * 128, d1, ks != 0);
                }
                wg_commit();
                wg_wait<0>();
                acc_fence(kva);
                acc_fence(za);
                float* dst = (float*)(g_kvp + (size_t)(c * 32 + m * 2 + wg) * 272) + w * 272;
                float o[8];
#pragma unroll
                for (int i = 0; i < 8; i++)
                    o[i] = (w == 0) ? kva[i] : (w == 1) ? kva[8 + i] : (w == 2) ? kva[16 + i] : kva[24 + i];
                *(float2*)(dst + g * 16 + 2 * t) = make_float2(o[0], o[1]);
                *(float2*)(dst + (g + 8) * 16 + 2 * t) = make_float2(o[2], o[3]);
                *(float2*)(dst + g * 16 + 8 + 2 * t) = make_float2(o[4], o[5]);
                *(float2*)(dst + (g + 8) * 16 + 8 + 2 * t) = make_float2(o[6], o[7]);
                if (t == 0) {
                    dst[256 + g] = za[0];
                    dst[256 + g + 8] = za[2];
                }
            } else {
                uint4* dst = a2w + (size_t)((4 * (tile - 1) + cc) * 4) * 256;
#pragma unroll
                for (int ks = 0; ks < 4; ks++) {
                    const float* gp = &acc[ks * 8];
                    const float* up = &acc[32 + ks * 8];
                    uint4 v;
                    v.x = pack_bf16(swiglu_f(gp[0] * rho0, up[0] * rho0), swiglu_f(gp[1] * rho0, up[1] * rho0));
                    v.y = pack_bf16(swiglu_f(gp[2] * rho1, up[2] * rho1), swiglu_f(gp[3] * rho1, up[3] * rho1));
                    v.z = pack_bf16(swiglu_f(gp[4] * rho0, up[4] * rho0), swiglu_f(gp[5] * rho0, up[5] * rho0));
                    v.w = pack_bf16(swiglu_f(gp[6] * rho1, up[6] * rho1), swiglu_f(gp[7] * rho1, up[7] * rho1));
                    dst[ks * 256] = v;
                }
            }
            bar_arrive(3 + wg * 2 + (tile & 1), 160);
        }
        {
            float qa[32], gu[32];
            mainloop64x2(qa, gu, xa, rg, sb, desc128, desc64, lane);
            {
                uint4* dst = a2w + (size_t)((12 + (cc >> 1)) * 4 + 2 * (cc & 1)) * 256;
#pragma unroll
                for (int ks = 0; ks < 2; ks++) {
                    const float* gp = &gu[ks * 8];
                    const float* up = &gu[16 + ks * 8];
                    uint4 v;
                    v.x = pack_bf16(swiglu_f(gp[0] * rho0, up[0] * rho0), swiglu_f(gp[1] * rho0, up[1] * rho0));
                    v.y = pack_bf16(swiglu_f(gp[2] * rho1, up[2] * rho1), swiglu_f(gp[3] * rho1, up[3] * rho1));
                    v.z = pack_bf16(swiglu_f(gp[4] * rho0, up[4] * rho0), swiglu_f(gp[5] * rho0, up[5] * rho0));
                    v.w = pack_bf16(swiglu_f(gp[6] * rho1, up[6] * rho1), swiglu_f(gp[7] * rho1, up[7] * rho1));
                    dst[ks * 256] = v;
                }
                mbar_wait(sb + BAR_KVREADY, 0);
                const uint2* kf = (const uint2*)(smem + OFF_KVFRAG);
                dst = a2w + (size_t)((14 + cc) * 4) * 256;
#pragma unroll
                for (int hh = 0; hh < 4; hh++) {
                    const float* q = &qa[hh * 8];
                    uint32_t a[4];
                    a[0] = pack_bf16(phi_f(q[0] * rho0), phi_f(q[1] * rho0));
                    a[1] = pack_bf16(phi_f(q[2] * rho1), phi_f(q[3] * rho1));
                    a[2] = pack_bf16(phi_f(q[4] * rho0), phi_f(q[5] * rho0));
                    a[3] = pack_bf16(phi_f(q[6] * rho1), phi_f(q[7] * rho1));
                    float n0[4] = {0.f, 0.f, 0.f, 0.f}, n1[4] = {0.f, 0.f, 0.f, 0.f}, dn[4] = {0.f, 0.f, 0.f, 0.f};
                    const uint2 b0 = kf[(hh * 3 + 0) * 32 + lane], b1 = kf[(hh * 3 + 1) * 32 + lane],
                                bz = kf[(hh * 3 + 2) * 32 + lane];
                    mma16816(n0, a, b0.x, b0.y);
                    mma16816(n1, a, b1.x, b1.y);
                    mma16816(dn, a, bz.x, bz.y);
                    const float i0 = 1.f / (dn[0] + 1e-6f), i1 = 1.f / (dn[2] + 1e-6f);
                    uint4 v;
                    v.x = pack_bf16(n0[0] * i0, n0[1] * i0);
                    v.y = pack_bf16(n0[2] * i1, n0[3] * i1);
                    v.z = pack_bf16(n1[0] * i0, n1[1] * i0);
                    v.w = pack_bf16(n1[2] * i1, n1[3] * i1);
                    dst[hh * 256] = v;
                }
            }
            bar_arrive(3 + wg * 2, 160);
        }

        {
            const uint4* a2r = g_A2 + (size_t)((m2 * 2 + rank) * 18) * 4 * 256 + warp * 32 + lane;
            uint4 af[4][4];
            Ring pf = rg;
#pragma unroll
            for (int b = 0; b < 3; b++) {
                mbar_wait(sb + BAR_FULL + 8 * pf.st, pf.ph);
                pf.next();
#pragma unroll
                for (int ks = 0; ks < 4; ks++) af[b][ks] = __ldcg(a2r + (b * 4 + ks) * 256);
            }
            int prev_st = 0;
#pragma unroll
            for (int b = 0; b < 18; b++) {
                wg_fence();
                const uint64_t d = desc128 + (uint64_t)(rg.st * (STAGE_BYTES >> 4));
#pragma unroll
                for (int ks = 0; ks < 4; ks++)
                    wgmma_n128_rs(acc, reinterpret_cast<const uint32_t*>(&af[b & 3][ks]), d + ks * 128, (b | ks) != 0);
                wg_commit();
                if (b > 0) {
                    wg_wait<1>();
                    if (lane < 2) mbar_arrive(sb + BAR_EMPTY + 8 * prev_st);
                }
                prev_st = rg.st;
                rg.next();
                if (b + 3 < 18) {
                    mbar_wait(sb + BAR_FULL + 8 * pf.st, pf.ph);
                    pf.next();
#pragma unroll
                    for (int ks = 0; ks < 4; ks++) af[(b + 3) & 3][ks] = __ldcg(a2r + ((b + 3) * 4 + ks) * 256);
                }
            }
            const int row0 = m2 * 128 + wg * 64 + w * 16 + g;
            const int col0 = j2 * 128 + rank * 64 + 2 * t;
            uint32_t xr[16];
#pragma unroll
            for (int nb = 0; nb < 8; nb++) {
                xr[2 * nb] = __ldg((const uint32_t*)(xg + (size_t)row0 * 512 + col0 + nb * 8));
                xr[2 * nb + 1] = __ldg((const uint32_t*)(xg + (size_t)(row0 + 8) * 512 + col0 + nb * 8));
            }
            wg_wait<0>();
            acc_fence(acc);
            uint32_t rdst, rbar;
            asm volatile("mapa.shared::cluster.u32 %0, %1, %2;" : "=r"(rdst) : "r"(sb + OFF_STG + tid * 16), "r"(rank ^ 1));
            asm volatile("mapa.shared::cluster.u32 %0, %1, %2;" : "=r"(rbar) : "r"(sb + BAR_XCHG), "r"(rank ^ 1));
            float keep[32];
#pragma unroll
            for (int i = 0; i < 8; i++) {
                float s0 = rank ? acc[4 * i] : acc[32 + 4 * i], s1 = rank ? acc[4 * i + 1] : acc[33 + 4 * i];
                float s2 = rank ? acc[4 * i + 2] : acc[34 + 4 * i], s3 = rank ? acc[4 * i + 3] : acc[35 + 4 * i];
                asm volatile("st.async.shared::cluster.mbarrier::complete_tx::bytes.v4.f32 [%0], {%1,%2,%3,%4}, [%5];"
                             ::"r"(rdst + i * 4096), "f"(s0), "f"(s1), "f"(s2), "f"(s3), "r"(rbar) : "memory");
#pragma unroll
                for (int e = 0; e < 4; e++) keep[4 * i + e] = rank ? acc[32 + 4 * i + e] : acc[4 * i + e];
            }
            mbar_wait(sb + BAR_XCHG, 0);
            const float4* rx = (const float4*)(smem + OFF_STG) + tid;
#pragma unroll
            for (int nb = 0; nb < 8; nb++) {
                const float4 p = rx[nb * 256];
                const uint32_t o0 = pack_bf16(keep[4 * nb] + p.x + bf_lo(xr[2 * nb]), keep[4 * nb + 1] + p.y + bf_hi(xr[2 * nb]));
                const uint32_t o1 = pack_bf16(keep[4 * nb + 2] + p.z + bf_lo(xr[2 * nb + 1]), keep[4 * nb + 3] + p.w + bf_hi(xr[2 * nb + 1]));
                *(uint32_t*)(outg + (size_t)row0 * 512 + col0 + nb * 8) = o0;
                *(uint32_t*)(outg + (size_t)(row0 + 8) * 512 + col0 + nb * 8) = o1;
            }
        }
        asm volatile("barrier.cluster.arrive.relaxed.aligned;\nbarrier.cluster.wait.aligned;" ::: "memory");
    }
}

typedef CUresult (*EncodeFn)(CUtensorMap*, CUtensorMapDataType, cuuint32_t, void*, const cuuint64_t*, const cuuint64_t*,
                             const cuuint32_t*, const cuuint32_t*, CUtensorMapInterleave, CUtensorMapSwizzle,
                             CUtensorMapL2promotion, CUtensorMapFloatOOBfill);

void make_map(EncodeFn enc, CUtensorMap* tm, const void* ptr, int rows, int cols, int box_rows, int box_cols,
              CUtensorMapSwizzle swz) {
    cuuint64_t dims[2] = {(cuuint64_t)cols, (cuuint64_t)rows};
    cuuint64_t strides[1] = {(cuuint64_t)cols * 2};
    cuuint32_t box[2] = {(cuuint32_t)box_cols, (cuuint32_t)box_rows};
    cuuint32_t es[2] = {1, 1};
    enc(tm, CU_TENSOR_MAP_DATA_TYPE_BFLOAT16, 2, const_cast<void*>(ptr), dims, strides, box, es,
        CU_TENSOR_MAP_INTERLEAVE_NONE, swz, CU_TENSOR_MAP_L2_PROMOTION_L2_256B, CU_TENSOR_MAP_FLOAT_OOB_FILL_NONE);
}

}

extern "C" void kernel_launch(void* const* d_in, const int* in_sizes, int n_in, void* d_out, int out_size) {
    (void)in_sizes; (void)n_in; (void)out_size;
    static EncodeFn enc = nullptr;
    if (!enc) {
        void* fn = nullptr;
        cudaDriverEntryPointQueryResult qr;
        cudaGetDriverEntryPoint("cuTensorMapEncodeTiled", &fn, cudaEnableDefault, &qr);
        enc = (EncodeFn)fn;
        cudaFuncSetAttribute(fused_kernel, cudaFuncAttributeMaxDynamicSharedMemorySize, SMEM_BYTES);
    }
    const void* x = d_in[0];
    const void* wqkv = d_in[1];
    const void* wo = d_in[2];
    const void* w1 = d_in[4];
    const void* w3 = d_in[5];
    const void* w2 = d_in[6];
    CUtensorMap tx, tqkv, t1, t3, t1h, t3h, t2, t2h, two;
    make_map(enc, &tx, x, 2048, 512, 128, 64, CU_TENSOR_MAP_SWIZZLE_128B);
    make_map(enc, &tqkv, wqkv, 512, 1536, 64, 64, CU_TENSOR_MAP_SWIZZLE_128B);
    make_map(enc, &t1, w1, 512, 1792, 64, 64, CU_TENSOR_MAP_SWIZZLE_128B);
    make_map(enc, &t3, w3, 512, 1792, 64, 64, CU_TENSOR_MAP_SWIZZLE_128B);
    make_map(enc, &t1h, w1, 512, 1792, 64, 32, CU_TENSOR_MAP_SWIZZLE_64B);
    make_map(enc, &t3h, w3, 512, 1792, 64, 32, CU_TENSOR_MAP_SWIZZLE_64B);
    make_map(enc, &t2, w2, 1792, 512, 64, 64, CU_TENSOR_MAP_SWIZZLE_128B);
    make_map(enc, &t2h, w2, 1792, 512, 32, 64, CU_TENSOR_MAP_SWIZZLE_128B);
    make_map(enc, &two, wo, 512, 512, 64, 64, CU_TENSOR_MAP_SWIZZLE_128B);
    fused_kernel<<<128, 384, SMEM_BYTES>>>(tx, tqkv, t1, t3, t1h, t3h, t2, t2h, two, (const __nv_bfloat16*)x,
                                           (__nv_bfloat16*)d_out);
}
```

```cpp
#include <cuda_runtime.h>
#include <cuda_bf16.h>
#include <cuda.h>
#include <stdint.h>

namespace {

constexpr int NST = 11;
constexpr int STAGE_BYTES = 16384;
constexpr int XST0 = 3;
constexpr int OFF_STG = NST * STAGE_BYTES;
constexpr int OFF_MISC = OFF_STG + 32768;
constexpr int OFF_KVFRAG = OFF_MISC;
constexpr int OFF_KVSUM = OFF_MISC + 3072;
constexpr int OFF_ONES = OFF_MISC + 7424;
constexpr int OFF_BARS = OFF_MISC + 7680;
constexpr int BAR_FULL = OFF_BARS;
constexpr int BAR_EMPTY = BAR_FULL + 8 * NST;
constexpr int BAR_XFULL = BAR_EMPTY + 8 * NST;
constexpr int BAR_KVREADY = BAR_XFULL + 64;
constexpr int BAR_XCHG = BAR_KVREADY + 8;
constexpr int BAR_AREADY = BAR_XCHG + 8;
constexpr int SMEM_BYTES = OFF_MISC + 8192;

constexpr int APF = 5;
constexpr unsigned SPIN_LIMIT = 1u << 24;

__device__ uint4 g_A2[16 * 2 * 18 * 4 * 256];
__device__ float4 g_kvp[8 * 32 * 272];
__device__ float4 g_kvs[8 * 272];
__device__ unsigned g_a2flag[16 * 8 * 4 * 2];
__device__ unsigned g_kvflag[8 * 32];
__device__ unsigned g_kvflag2[8 * 16];
__device__ unsigned g_epoch;
__device__ unsigned g_ticket;

#define TS(role, i)

__device__ __forceinline__ uint32_t smem_u32(const void* p) { return (uint32_t)__cvta_generic_to_shared(p); }
__device__ __forceinline__ void mbar_init(uint32_t bar, uint32_t cnt) {
    asm volatile("mbarrier.init.shared::cta.b64 [%0], %1;" ::"r"(bar), "r"(cnt) : "memory");
}
__device__ __forceinline__ void mbar_expect_tx(uint32_t bar, uint32_t bytes) {
    asm volatile("mbarrier.arrive.expect_tx.shared::cta.b64 _, [%0], %1;" ::"r"(bar), "r"(bytes) : "memory");
}
__device__ __forceinline__ void mbar_arrive(uint32_t bar) {
    asm volatile("mbarrier.arrive.shared::cta.b64 _, [%0];" ::"r"(bar) : "memory");
}
__device__ __forceinline__ void mbar_arrive_cta(uint32_t bar, uint32_t cta) {
    asm volatile(
        "{\n.reg .b32 ra;\nmapa.shared::cluster.u32 ra, %0, %1;\n"
        "mbarrier.arrive.shared::cluster.b64 _, [ra];\n}" ::"r"(bar), "r"(cta) : "memory");
}
__device__ __forceinline__ void mbar_wait(uint32_t bar, uint32_t parity) {
    asm volatile(
        "{\n.reg .pred p, q;\n.reg .u32 n;\nmov.u32 n, 0;\n"
        "WAIT_%=:\n"
        "mbarrier.try_wait.parity.shared::cta.b64 p, [%0], %1;\n"
        "@p bra.uni DONE_%=;\n"
        "add.u32 n, n, 1;\n"
        "setp.gt.u32 q, n, %2;\n"
        "@q trap;\n"
        "bra.uni WAIT_%=;\n"
        "DONE_%=:\n}"
        ::"r"(bar), "r"(parity), "n"(SPIN_LIMIT) : "memory");
}
__device__ __forceinline__ unsigned ld_acquire(const unsigned* p) {
    unsigned v;
    asm volatile("ld.acquire.gpu.global.u32 %0, [%1];" : "=r"(v) : "l"(p) : "memory");
    return v;
}
__device__ __forceinline__ void st_release(unsigned* p, unsigned v) {
    asm volatile("st.release.gpu.global.u32 [%0], %1;" ::"l"(p), "r"(v) : "memory");
}
__device__ __forceinline__ void wait_flag(const unsigned* p, unsigned epoch) {
    asm volatile(
        "{\n.reg .pred p, q;\n.reg .u32 n, v;\nmov.u32 n, 0;\n"
        "WAIT_%=:\n"
        "ld.acquire.gpu.global.u32 v, [%0];\n"
        "setp.eq.u32 p, v, %1;\n"
        "@p bra DONE_%=;\n"
        "nanosleep.u32 32;\n"
        "add.u32 n, n, 1;\n"
        "setp.gt.u32 q, n, %2;\n"
        "@q trap;\n"
        "bra WAIT_%=;\n"
        "DONE_%=:\n}"
        ::"l"(p), "r"(epoch), "n"(SPIN_LIMIT) : "memory");
}
__device__ __forceinline__ unsigned read_epoch() {
    return __shfl_sync(0xffffffffu, *(volatile unsigned*)&g_epoch, 0) + 1;
}
__device__ __forceinline__ void tma_load(uint32_t dst, const CUtensorMap* tm, uint32_t bar, int x, int y) {
    asm volatile(
        "cp.async.bulk.tensor.2d.shared::cluster.global.mbarrier::complete_tx::bytes [%0], [%1, {%3, %4}], [%2];"
        ::"r"(dst), "l"(tm), "r"(bar), "r"(x), "r"(y) : "memory");
}
__device__ __forceinline__ void tma_load_mc(uint32_t dst, const CUtensorMap* tm, uint32_t bar, int x, int y) {
    asm volatile(
        "cp.async.bulk.tensor.2d.shared::cluster.global.mbarrier::complete_tx::bytes.multicast::cluster "
        "[%0], [%1, {%3, %4}], [%2], %5;"
        ::"r"(dst), "l"(tm), "r"(bar), "r"(x), "r"(y), "h"((uint16_t)3) : "memory");
}
__device__ __forceinline__ void prefetch_tm(const CUtensorMap* tm) {
    asm volatile("prefetch.tensormap [%0];" ::"l"(tm) : "memory");
}
__device__ __forceinline__ void bar_sync(int id, int n) { asm volatile("bar.sync %0, %1;" ::"r"(id), "r"(n) : "memory"); }
__device__ __forceinline__ void bar_arrive(int id, int n) { asm volatile("bar.arrive %0, %1;" ::"r"(id), "r"(n) : "memory"); }
__device__ __forceinline__ void wg_fence() { asm volatile("wgmma.fence.sync.aligned;" ::: "memory"); }
__device__ __forceinline__ void wg_commit() { asm volatile("wgmma.commit_group.sync.aligned;" ::: "memory"); }
template <int N>
__device__ __forceinline__ void wg_wait() { asm volatile("wgmma.wait_group.sync.aligned %0;" ::"n"(N) : "memory"); }

__device__ __forceinline__ uint64_t make_desc(uint32_t addr, uint32_t lbo, uint32_t sbo, uint64_t swz) {
    return (uint64_t)((addr & 0x3FFFF) >> 4) | ((uint64_t)(lbo >> 4) << 16) | ((uint64_t)(sbo >> 4) << 32) | (swz << 62);
}

#define ACC8(a, o) "+f"(a[o]), "+f"(a[o + 1]), "+f"(a[o + 2]), "+f"(a[o + 3]), "+f"(a[o + 4]), "+f"(a[o + 5]), "+f"(a[o + 6]), "+f"(a[o + 7])
__device__ __forceinline__ void wgmma_n128_rs(float (&d)[64], const uint32_t* a, uint64_t db, int scale_d) {
    asm volatile(
        "{\n.reg .pred p;\nsetp.ne.b32 p, %69, 0;\n"
        "wgmma.mma_async.sync.aligned.m64n128k16.f32.bf16.bf16 "
        "{%0,%1,%2,%3,%4,%5,%6,%7,%8,%9,%10,%11,%12,%13,%14,%15,%16,%17,%18,%19,%20,%21,%22,%23,%24,%25,%26,%27,%28,%29,%30,%31,"
        "%32,%33,%34,%35,%36,%37,%38,%39,%40,%41,%42,%43,%44,%45,%46,%47,%48,%49,%50,%51,%52,%53,%54,%55,%56,%57,%58,%59,%60,%61,%62,%63},"
        "{%64,%65,%66,%67}, %68, p, 1, 1, 1;\n}"
        : ACC8(d, 0), ACC8(d, 8), ACC8(d, 16), ACC8(d, 24), ACC8(d, 32), ACC8(d, 40), ACC8(d, 48), ACC8(d, 56)
        : "r"(a[0]), "r"(a[1]), "r"(a[2]), "r"(a[3]), "l"(db), "r"(scale_d));
}
__device__ __forceinline__ void wgmma_n64_rs(float (&d)[32], const uint32_t* a, uint64_t db, int scale_d) {
    asm volatile(
        "{\n.reg .pred p;\nsetp.ne.b32 p, %37, 0;\n"
        "wgmma.mma_async.sync.aligned.m64n64k16.f32.bf16.bf16 "
        "{%0,%1,%2,%3,%4,%5,%6,%7,%8,%9,%10,%11,%12,%13,%14,%15,%16,%17,%18,%19,%20,%21,%22,%23,%24,%25,%26,%27,%28,%29,%30,%31},"
        "{%32,%33,%34,%35}, %36, p, 1, 1, 1;\n}"
        : ACC8(d, 0), ACC8(d, 8), ACC8(d, 16), ACC8(d, 24)
        : "r"(a[0]), "r"(a[1]), "r"(a[2]), "r"(a[3]), "l"(db), "r"(scale_d));
}
__device__ __forceinline__ void wgmma_n64_ss_tt(float (&d)[32], uint64_t da, uint64_t db, int scale_d) {
    asm volatile(
        "{\n.reg .pred p;\nsetp.ne.b32 p, %34, 0;\n"
        "wgmma.mma_async.sync.aligned.m64n64k16.f32.bf16.bf16 "
        "{%0,%1,%2,%3,%4,%5,%6,%7,%8,%9,%10,%11,%12,%13,%14,%15,%16,%17,%18,%19,%20,%21,%22,%23,%24,%25,%26,%27,%28,%29,%30,%31},"
        "%32, %33, p, 1, 1, 1, 1;\n}"
        : ACC8(d, 0), ACC8(d, 8), ACC8(d, 16), ACC8(d, 24)
        : "l"(da), "l"(db), "r"(scale_d));
}
__device__ __forceinline__ void wgmma_n8_ss_tn(float (&d)[4], uint64_t da, uint64_t db, int scale_d) {
    asm volatile(
        "{\n.reg .pred p;\nsetp.ne.b32 p, %6, 0;\n"
        "wgmma.mma_async.sync.aligned.m64n8k16.f32.bf16.bf16 {%0,%1,%2,%3}, %4, %5, p, 1, 1, 1, 0;\n}"
        : "+f"(d[0]), "+f"(d[1]), "+f"(d[2]), "+f"(d[3])
        : "l"(da), "l"(db), "r"(scale_d));
}
template <int N>
__device__ __forceinline__ void acc_fence(float (&d)[N]) {
#pragma unroll
    for (int i = 0; i < N; i++) asm volatile("" : "+f"(d[i])::"memory");
}
__device__ __forceinline__ void mma16816(float (&c)[4], const uint32_t* a, uint32_t b0, uint32_t b1) {
    asm volatile(
        "mma.sync.aligned.m16n8k16.row.col.f32.bf16.bf16.f32 {%0,%1,%2,%3}, {%4,%5,%6,%7}, {%8,%9}, {%0,%1,%2,%3};"
        : "+f"(c[0]), "+f"(c[1]), "+f"(c[2]), "+f"(c[3])
        : "r"(a[0]), "r"(a[1]), "r"(a[2]), "r"(a[3]), "r"(b0), "r"(b1));
}
__device__ __forceinline__ uint32_t pack_bf16(float lo, float hi) {
    uint32_t r;
    asm("cvt.rn.bf16x2.f32 %0, %1, %2;" : "=r"(r) : "f"(hi), "f"(lo));
    return r;
}
__device__ __forceinline__ float bf_lo(uint32_t v) { return __uint_as_float(v << 16); }
__device__ __forceinline__ float bf_hi(uint32_t v) { return __uint_as_float(v & 0xffff0000u); }
__device__ __forceinline__ float bf16_round(float v) { return __bfloat162float(__float2bfloat16_rn(v)); }
__device__ __forceinline__ float phi_f(float t) { return (t > 0.f ? t + 1.f : __expf(t)) + 1e-6f; }
__device__ __forceinline__ float swiglu_f(float g, float u) { return __fdividef(g, 1.f + __expf(-g)) * u; }

struct Ring {
    int st;
    uint32_t ph;
    __device__ __forceinline__ void next() {
        if (++st == NST) { st = 0; ph ^= 1; }
    }
};

__device__ __forceinline__ void sumsq16(const uint32_t* a, float (&q)[4]) {
#pragma unroll
    for (int i = 0; i < 16; i += 2) {
        const float a0 = bf_lo(a[i]), a1 = bf_hi(a[i]), b0 = bf_lo(a[i + 1]), b1 = bf_hi(a[i + 1]);
        q[0] = fmaf(a0, a0, q[0]); q[1] = fmaf(a1, a1, q[1]);
        q[2] = fmaf(b0, b0, q[2]); q[3] = fmaf(b1, b1, q[3]);
    }
}
template <bool SUMSQ>
__device__ __forceinline__ void mainloop128(float (&acc)[64], const uint32_t (&xa)[128], Ring& rg, uint32_t sb,
                                            uint64_t desc128, int lane, int wg, float (&q)[4]) {
    int prev_st = 0;
    bar_sync(7 + wg, 256);
#pragma unroll
    for (int kb = 0; kb < 8; kb++) {
        mbar_wait(sb + BAR_FULL + 8 * rg.st, rg.ph);
        wg_fence();
        const uint64_t d = desc128 + (uint64_t)(rg.st * (STAGE_BYTES >> 4));
#pragma unroll
        for (int ks = 0; ks < 4; ks++) wgmma_n128_rs(acc, &xa[(kb * 4 + ks) * 4], d + ks * 128, (kb | ks) != 0);
        wg_commit();
        if (kb == 7) bar_arrive(8 - wg, 256);
        if (kb > 0) {
            wg_wait<1>();
            if (lane < 2) mbar_arrive_cta(sb + BAR_EMPTY + 8 * prev_st, lane);
            if (SUMSQ) sumsq16(&xa[(kb - 1) * 16], q);
        }
        prev_st = rg.st;
        rg.next();
    }
    wg_wait<0>();
    acc_fence(acc);
    if (lane < 2) mbar_arrive_cta(sb + BAR_EMPTY + 8 * prev_st, lane);
    if (SUMSQ) sumsq16(&xa[7 * 16], q);
}
__device__ __forceinline__ void mainloop64x2(float (&a0)[32], float (&a1)[32], const uint32_t (&xa)[128], Ring& rg,
                                             uint32_t sb, uint64_t desc128, uint64_t desc64, int lane, int wg) {
    int prev_st = 0;
    bar_sync(7 + wg, 256);
#pragma unroll
    for (int kb = 0; kb < 8; kb++) {
        mbar_wait(sb + BAR_FULL + 8 * rg.st, rg.ph);
        wg_fence();
        const uint64_t d = desc128 + (uint64_t)(rg.st * (STAGE_BYTES >> 4));
        const uint64_t d2 = desc64 + (uint64_t)(rg.st * (STAGE_BYTES >> 4));
#pragma unroll
        for (int ks = 0; ks < 4; ks++) {
            wgmma_n64_rs(a0, &xa[(kb * 4 + ks) * 4], d + ks * 128, (kb | ks) != 0);
            wgmma_n64_rs(a1, &xa[(kb * 4 + ks) * 4], d2 + ks * 64, (kb | ks) != 0);
        }
        wg_commit();
        if (kb == 7 && wg == 0) bar_arrive(8, 256);
        if (kb > 0) {
            wg_wait<1>();
            if (lane < 2) mbar_arrive_cta(sb + BAR_EMPTY + 8 * prev_st, lane);
        }
        prev_st = rg.st;
        rg.next();
    }
    wg_wait<0>();
    acc_fence(a0);
    acc_fence(a1);
    if (lane < 2) mbar_arrive_cta(sb + BAR_EMPTY + 8 * prev_st, lane);
}

__global__ void __cluster_dims__(2, 1, 1) __launch_bounds__(384, 1)
fused_kernel(const __grid_constant__ CUtensorMap tm_x, const __grid_constant__ CUtensorMap tm_qkv,
             const __grid_constant__ CUtensorMap tm_w1, const __grid_constant__ CUtensorMap tm_w3,
             const __grid_constant__ CUtensorMap tm_w1h, const __grid_constant__ CUtensorMap tm_w3h,
             const __grid_constant__ CUtensorMap tm_w2, const __grid_constant__ CUtensorMap tm_w2h,
             const __grid_constant__ CUtensorMap tm_wo, const __nv_bfloat16* __restrict__ xg,
             __nv_bfloat16* __restrict__ outg) {
    extern __shared__ __align__(1024) uint8_t smem[];
    const uint32_t sb = smem_u32(smem);
    const int tid = threadIdx.x;
    const int warp = tid >> 5, lane = tid & 31;
    const int rank = blockIdx.x & 1;
    const int pair = blockIdx.x >> 1;
    const int c = pair & 7;
    const int m = (pair >> 3) * 2 + rank;
    const int m2 = (pair >> 3) * 2 + (c & 1);
    const int j2 = c >> 1;

    TS(tid >> 7, 0);
    if (tid == 256) {
        if (sb & 1023) __trap();
        for (int i = 0; i < NST; i++) {
            mbar_init(sb + BAR_FULL + 8 * i, 1);
            mbar_init(sb + BAR_EMPTY + 8 * i, 16);
        }
        for (int i = 0; i < 8; i++) mbar_init(sb + BAR_XFULL + 8 * i, 1);
        mbar_init(sb + BAR_KVREADY, 1);
        mbar_init(sb + BAR_XCHG, 1);
        for (int i = 0; i < 18; i++) mbar_init(sb + BAR_AREADY + 8 * i, 1);
        asm volatile("fence.mbarrier_init.release.cluster;" ::: "memory");
        asm volatile("fence.proxy.async.shared::cta;" ::: "memory");
        TS(2, 20);
        mbar_expect_tx(sb + BAR_XCHG, 32768);
        for (int kb = 0; kb < 8; kb++) {
            mbar_expect_tx(sb + BAR_XFULL + 8 * kb, 16384);
            tma_load(sb + (XST0 + kb) * STAGE_BYTES, &tm_x, sb + BAR_XFULL + 8 * kb, kb * 64, m * 128);
        }
        TS(2, 21);
    } else if (tid == 288) {
        prefetch_tm(&tm_qkv); prefetch_tm(&tm_w1); prefetch_tm(&tm_w3); prefetch_tm(&tm_w1h);
        prefetch_tm(&tm_w3h); prefetch_tm(&tm_w2); prefetch_tm(&tm_w2h); prefetch_tm(&tm_wo);
    } else if (tid >= 320) {
        ((uint32_t*)(smem + OFF_ONES))[tid - 320] = 0x3F803F80u;
        asm volatile("fence.proxy.async.shared::cta;" ::: "memory");
    }
    __syncthreads();
    TS(tid >> 7, 22);
    asm volatile("barrier.cluster.arrive.release.aligned;\nbarrier.cluster.wait.acquire.aligned;" ::: "memory");

    if (warp >= 8) {
        asm volatile("setmaxnreg.dec.sync.aligned.u32 40;");
        if (warp == 8) {
            if (lane == 0) {
                int st = 0;
                uint32_t lap = 0;
                for (int it = 0; it < 40; it++) {
                    const int tile = it >> 3, kb = it & 7;
                    const uint32_t full = sb + BAR_FULL + 8 * st;
                    mbar_wait(sb + BAR_EMPTY + 8 * st, (st >= XST0) ? (lap & 1) : ((lap & 1) ^ 1));
                    mbar_expect_tx(full, STAGE_BYTES);
                    const uint32_t dst = sb + st * STAGE_BYTES;
                    if (tile == 0) {
                        tma_load_mc(dst + rank * 8192, &tm_qkv, full, 512 + 512 * rank + 64 * c, kb * 64);
                    } else if (tile < 4) {
                        tma_load_mc(dst + rank * 8192, rank ? &tm_w3 : &tm_w1, full, 224 * c + 64 * (tile - 1), kb * 64);
                    } else if (rank == 0) {
                        tma_load_mc(dst, &tm_qkv, full, 64 * c, kb * 64);
                    } else {
                        tma_load_mc(dst + 8192, &tm_w1h, full, 224 * c + 192, kb * 64);
                        tma_load_mc(dst + 12288, &tm_w3h, full, 224 * c + 192, kb * 64);
                    }
                    if (++st == NST) { st = 0; lap++; }
                }
                TS(2, 1);
                for (int b = 0; b < 18; b++) {
                    const uint32_t full = sb + BAR_FULL + 8 * st;
                    const uint32_t dst = sb + st * STAGE_BYTES;
                    mbar_wait(sb + BAR_EMPTY + 8 * st, (st >= XST0) ? (lap & 1) : ((lap & 1) ^ 1));
                    mbar_expect_tx(full, STAGE_BYTES);
                    if (b < 12) {
                        const int row = 224 * (4 * rank + (b & 3)) + 64 * (b >> 2);
                        tma_load(dst, &tm_w2, full, 128 * j2, row);
                        tma_load(dst + 8192, &tm_w2, full, 128 * j2 + 64, row);
                    } else if (b < 14) {
                        const int row = 224 * (4 * rank + 2 * (b - 12)) + 192;
                        tma_load(dst, &tm_w2h, full, 128 * j2, row);
                        tma_load(dst + 4096, &tm_w2h, full, 128 * j2, row + 224);
                        tma_load(dst + 8192, &tm_w2h, full, 128 * j2 + 64, row);
                        tma_load(dst + 12288, &tm_w2h, full, 128 * j2 + 64, row + 224);
                    } else {
                        const int row = 64 * (4 * rank + (b - 14));
                        tma_load(dst, &tm_wo, full, 128 * j2, row);
                        tma_load(dst + 8192, &tm_wo, full, 128 * j2 + 64, row);
                    }
                    TS(2, 2 + b);
                    if (++st == NST) { st = 0; lap++; }
                }
            }
        } else if (warp == 9) {
            const unsigned epoch = read_epoch();
            bar_arrive(9, 96);
            for (int i = 0; i < 10; i++) {
                const int wg = i & 1, t = i >> 1;
                bar_sync(3 + wg * 2 + (t & 1), 160);
                if (lane == 0) {
                    if (t == 0) st_release(&g_kvflag[c * 32 + m * 2 + wg], epoch);
                    else st_release(&g_a2flag[((m * 8 + c) * 4 + (t - 1)) * 2 + wg], epoch);
                }
            }
        } else if (warp == 10) {
            const unsigned epoch = read_epoch();
            bar_sync(9, 96);
            if (lane == 0) {
                const unsigned tk = atomicInc(&g_ticket, 127u);
                if (tk == 127u) *(volatile unsigned*)&g_epoch = epoch;
            }
            const volatile unsigned* fl = g_a2flag + (m2 * 8 + rank * 4) * 8 + lane;
            unsigned ready = 0;
            for (int b = 0; b < 18; b++) {
                const unsigned need = (b < 12) ? (3u << ((b & 3) * 8 + (b >> 2) * 2)) : (b < 14) ? (0xC0C0u << ((b - 12) * 16)) : 0u;
                if ((ready & need) != need) {
                    unsigned n = 0;
                    while (true) {
                        ready = __ballot_sync(0xffffffffu, *fl == epoch);
                        if ((ready & need) == need) break;
                        __nanosleep(100);
                        if (++n > SPIN_LIMIT) asm volatile("trap;");
                    }
                    asm volatile("fence.acq_rel.gpu;" ::: "memory");
                    __syncwarp();
                }
                if (lane == 0) mbar_arrive(sb + BAR_AREADY + 8 * b);
            }
        } else {
            const unsigned epoch = read_epoch();
            bar_arrive(9, 96);
            wait_flag(&g_kvflag[c * 32 + lane], epoch);
            __syncwarp();
            if (lane < 17) {
                const float4* src = g_kvp + (size_t)c * 32 * 272 + m * 17 + lane;
                float4 s = make_float4(0.f, 0.f, 0.f, 0.f);
#pragma unroll 8
                for (int p = 0; p < 32; p++) {
                    float4 v = __ldcg(src + p * 272);
                    s.x += v.x; s.y += v.y; s.z += v.z; s.w += v.w;
                }
                g_kvs[c * 272 + m * 17 + lane] = s;
            }
            __syncwarp();
            if (lane == 0) st_release(&g_kvflag2[c * 16 + m], epoch);
            if (lane < 16) wait_flag(&g_kvflag2[c * 16 + lane], epoch);
            __syncwarp();
            float4* ks4 = (float4*)(smem + OFF_KVSUM);
            for (int i = lane; i < 272; i += 32) ks4[i] = __ldcg(g_kvs + c * 272 + i);
            __syncwarp();
            const float* ks = (const float*)(smem + OFF_KVSUM);
            uint2* kf = (uint2*)(smem + OFF_KVFRAG);
            const int g = lane >> 2, t = lane & 3;
            for (int hh = 0; hh < 4; hh++) {
                const float* k = ks + hh * 272;
                for (int b = 0; b < 2; b++) {
                    uint2 v;
                    v.x = pack_bf16(k[(2 * t) * 16 + 8 * b + g], k[(2 * t + 1) * 16 + 8 * b + g]);
                    v.y = pack_bf16(k[(2 * t + 8) * 16 + 8 * b + g], k[(2 * t + 9) * 16 + 8 * b + g]);
                    kf[(hh * 3 + b) * 32 + lane] = v;
                }
                uint2 z;
                z.x = pack_bf16(k[256 + 2 * t], k[256 + 2 * t + 1]);
                z.y = pack_bf16(k[256 + 2 * t + 8], k[256 + 2 * t + 9]);
                kf[(hh * 3 + 2) * 32 + lane] = z;
            }
            __syncwarp();
            if (lane == 0) mbar_arrive(sb + BAR_KVREADY);
        }
    } else {
        asm volatile("setmaxnreg.inc.sync.aligned.u32 232;");
        const int wg = warp >> 2, w = warp & 3;
        const int g = lane >> 2, t = lane & 3;
        float acc[64];
        uint32_t xa[128];
        float rho0, rho1;

        TS(wg, 1);
        {
            const int row = wg * 64 + w * 16 + (lane & 7) + ((lane >> 3) & 1) * 8;
            const uint32_t rbase = sb + XST0 * STAGE_BYTES + row * 128;
            const int hi = lane >> 4, r7 = lane & 7;
            float sm[4][4];
#pragma unroll
            for (int i = 0; i < 16; i++) sm[i >> 2][i & 3] = 0.f;
            if (wg == 1) bar_arrive(7, 256);
#pragma unroll
            for (int kb = 0; kb < 8; kb++) {
                mbar_wait(sb + BAR_XFULL + 8 * kb, 0);
#pragma unroll
                for (int ks = 0; ks < 4; ks++) {
                    uint32_t* a = &xa[(kb * 4 + ks) * 4];
                    const uint32_t addr = rbase + kb * STAGE_BYTES + (((2 * ks + hi) ^ r7) << 4);
                    asm volatile("ldmatrix.sync.aligned.m8n8.x4.shared.b16 {%0,%1,%2,%3}, [%4];"
                                 : "=r"(a[0]), "=r"(a[1]), "=r"(a[2]), "=r"(a[3]) : "r"(addr) : "memory");
                    mma16816(sm[ks], a, 0x3F803F80u, 0x3F803F80u);
                }
            }
            TS(wg, 2);
            const float mean0 = ((sm[0][0] + sm[1][0]) + (sm[2][0] + sm[3][0])) * (1.f / 512.f);
            const float mean1 = ((sm[0][2] + sm[1][2]) + (sm[2][2] + sm[3][2])) * (1.f / 512.f);
            __syncwarp();
            if (lane < 16) mbar_arrive_cta(sb + BAR_EMPTY + 8 * (XST0 + (lane >> 1)), lane & 1);
            const __nv_bfloat162 mb0 = __float2bfloat162_rn(mean0), mb1 = __float2bfloat162_rn(mean1);
#pragma unroll
            for (int i = 0; i < 128; i++) {
                __nv_bfloat162 v = *reinterpret_cast<__nv_bfloat162*>(&xa[i]);
                v = __hsub2(v, (i & 1) ? mb1 : mb0);
                xa[i] = *reinterpret_cast<uint32_t*>(&v);
            }
            rho0 = mean0 - __low2float(mb0);
            rho1 = mean1 - __low2float(mb1);
        }

        TS(wg, 3);
        Ring rg = {0, 0};
        const uint64_t desc128 = make_desc(sb, 8192, 1024, 1);
        const uint64_t desc64 = make_desc(sb + 8192, 4096, 512, 2);
        uint4* a2w = g_A2 + (size_t)((m * 2 + (c >> 2)) * 18) * 4 * 256 + warp * 32 + lane;
        const int cc = c & 3;

        float qs[4] = {0.f, 0.f, 0.f, 0.f};
        {
            mainloop128<true>(acc, xa, rg, sb, desc128, lane, wg, qs);
            TS(wg, 4);
            float q0 = qs[0] + qs[1], q2 = qs[2] + qs[3];
            q0 += __shfl_xor_sync(0xffffffffu, q0, 1); q2 += __shfl_xor_sync(0xffffffffu, q2, 1);
            q0 += __shfl_xor_sync(0xffffffffu, q0, 2); q2 += __shfl_xor_sync(0xffffffffu, q2, 2);
            const float var0 = fmaxf(q0 * (1.f / 512.f) - rho0 * rho0, 0.f), var1 = fmaxf(q2 * (1.f / 512.f) - rho1 * rho1, 0.f);
            rho0 = 1.f / bf16_round(sqrtf(bf16_round(bf16_round(var0) + 1e-5f)));
            rho1 = 1.f / bf16_round(sqrtf(bf16_round(bf16_round(var1) + 1e-5f)));
            {
                const uint32_t pkb = sb + OFF_STG + wg * 16384;
                const uint32_t r0 = pkb + (w * 16 + g) * 128 + t * 4;
#pragma unroll
                for (int nb = 0; nb < 8; nb++) {
                    const uint32_t off = (uint32_t)((nb ^ g) << 4);
                    uint32_t p0 = pack_bf16(phi_f(acc[nb * 4] * rho0), phi_f(acc[nb * 4 + 1] * rho0));
                    uint32_t p1 = pack_bf16(phi_f(acc[nb * 4 + 2] * rho1), phi_f(acc[nb * 4 + 3] * rho1));
                    uint32_t v0 = pack_bf16(acc[32 + nb * 4] * rho0, acc[32 + nb * 4 + 1] * rho0);
                    uint32_t v1 = pack_bf16(acc[32 + nb * 4 + 2] * rho1, acc[32 + nb * 4 + 3] * rho1);
                    asm volatile("st.shared.u32 [%0], %1;" ::"r"(r0 + off), "r"(p0) : "memory");
                    asm volatile("st.shared.u32 [%0], %1;" ::"r"(r0 + off + 1024), "r"(p1) : "memory");
                    asm volatile("st.shared.u32 [%0], %1;" ::"r"(r0 + off + 8192), "r"(v0) : "memory");
                    asm volatile("st.shared.u32 [%0], %1;" ::"r"(r0 + off + 8192 + 1024), "r"(v1) : "memory");
                }
                asm volatile("fence.proxy.async.shared::cta;" ::: "memory");
                bar_sync(1 + wg, 128);
                const uint64_t da = make_desc(pkb, 8192, 1024, 1);
                const uint64_t db = make_desc(pkb + 8192, 8192, 1024, 1);
                const uint64_t d1 = make_desc(sb + OFF_ONES, 128, 128, 0);
                float kva[32], za[4];
                wg_fence();
#pragma unroll
                for (int ks = 0; ks < 4; ks++) {
                    wgmma_n64_ss_tt(kva, da + ks * 128, db + ks * 128, ks != 0);
                    wgmma_n8_ss_tn(za, da + ks * 128, d1, ks != 0);
                }
                wg_commit();
                wg_wait<0>();
                acc_fence(kva);
                acc_fence(za);
                float* dst = (float*)(g_kvp + (size_t)(c * 32 + m * 2 + wg) * 272) + w * 272;
                float o[8];
#pragma unroll
                for (int i = 0; i < 8; i++)
                    o[i] = (w == 0) ? kva[i] : (w == 1) ? kva[8 + i] : (w == 2) ? kva[16 + i] : kva[24 + i];
                *(float2*)(dst + g * 16 + 2 * t) = make_float2(o[0], o[1]);
                *(float2*)(dst + (g + 8) * 16 + 2 * t) = make_float2(o[2], o[3]);
                *(float2*)(dst + g * 16 + 8 + 2 * t) = make_float2(o[4], o[5]);
                *(float2*)(dst + (g + 8) * 16 + 8 + 2 * t) = make_float2(o[6], o[7]);
                if (t == 0) {
                    dst[256 + g] = za[0];
                    dst[256 + g + 8] = za[2];
                }
            }
            bar_arrive(3 + wg * 2, 160);
            TS(wg, 5);
        }
#pragma unroll 1
        for (int tile = 1; tile < 4; tile++) {
            mainloop128<false>(acc, xa, rg, sb, desc128, lane, wg, qs);
            TS(wg, 4 + 2 * tile);
            {
                uint4* dst = a2w + (size_t)((4 * (tile - 1) + cc) * 4) * 256;
#pragma unroll
                for (int ks = 0; ks < 4; ks++) {
                    const float* gp = &acc[ks * 8];
                    const float* up = &acc[32 + ks * 8];
                    uint4 v;
                    v.x = pack_bf16(swiglu_f(gp[0] * rho0, up[0] * rho0), swiglu_f(gp[1] * rho0, up[1] * rho0));
                    v.y = pack_bf16(swiglu_f(gp[2] * rho1, up[2] * rho1), swiglu_f(gp[3] * rho1, up[3] * rho1));
                    v.z = pack_bf16(swiglu_f(gp[4] * rho0, up[4] * rho0), swiglu_f(gp[5] * rho0, up[5] * rho0));
                    v.w = pack_bf16(swiglu_f(gp[6] * rho1, up[6] * rho1), swiglu_f(gp[7] * rho1, up[7] * rho1));
                    dst[ks * 256] = v;
                }
            }
            bar_arrive(3 + wg * 2 + (tile & 1), 160);
            TS(wg, 5 + 2 * tile);
        }
        const uint4* a2r = g_A2 + (size_t)((m2 * 2 + rank) * 18) * 4 * 256 + warp * 32 + lane;
        uint4 af[APF + 1][4];
        {
            float qa[32], gu[32];
            mainloop64x2(qa, gu, xa, rg, sb, desc128, desc64, lane, wg);
            TS(wg, 12);
#pragma unroll
            for (int b = 0; b < APF; b++) {
                mbar_wait(sb + BAR_AREADY + 8 * b, 0);
#pragma unroll
                for (int ks = 0; ks < 4; ks++) af[b][ks] = __ldcg(a2r + (b * 4 + ks) * 256);
            }
            {
                uint4* dst = a2w + (size_t)((12 + (cc >> 1)) * 4 + 2 * (cc & 1)) * 256;
#pragma unroll
                for (int ks = 0; ks < 2; ks++) {
                    const float* gp = &gu[ks * 8];
                    const float* up = &gu[16 + ks * 8];
                    uint4 v;
                    v.x = pack_bf16(swiglu_f(gp[0] * rho0, up[0] * rho0), swiglu_f(gp[1] * rho0, up[1] * rho0));
                    v.y = pack_bf16(swiglu_f(gp[2] * rho1, up[2] * rho1), swiglu_f(gp[3] * rho1, up[3] * rho1));
                    v.z = pack_bf16(swiglu_f(gp[4] * rho0, up[4] * rho0), swiglu_f(gp[5] * rho0, up[5] * rho0));
                    v.w = pack_bf16(swiglu_f(gp[6] * rho1, up[6] * rho1), swiglu_f(gp[7] * rho1, up[7] * rho1));
                    dst[ks * 256] = v;
                }
                TS(wg, 13);
                mbar_wait(sb + BAR_KVREADY, 0);
                TS(wg, 14);
                const uint2* kf = (const uint2*)(smem + OFF_KVFRAG);
                dst = a2w + (size_t)((14 + cc) * 4) * 256;
#pragma unroll
                for (int hh = 0; hh < 4; hh++) {
                    const float* q = &qa[hh * 8];
                    uint32_t a[4];
                    a[0] = pack_bf16(phi_f(q[0] * rho0), phi_f(q[1] * rho0));
                    a[1] = pack_bf16(phi_f(q[2] * rho1), phi_f(q[3] * rho1));
                    a[2] = pack_bf16(phi_f(q[4] * rho0), phi_f(q[5] * rho0));
                    a[3] = pack_bf16(phi_f(q[6] * rho1), phi_f(q[7] * rho1));
                    float n0[4] = {0.f, 0.f, 0.f, 0.f}, n1[4] = {0.f, 0.f, 0.f, 0.f}, dn[4] = {0.f, 0.f, 0.f, 0.f};
                    const uint2 b0 = kf[(hh * 3 + 0) * 32 + lane], b1 = kf[(hh * 3 + 1) * 32 + lane],
                                bz = kf[(hh * 3 + 2) * 32 + lane];
                    mma16816(n0, a, b0.x, b0.y);
                    mma16816(n1, a, b1.x, b1.y);
                    mma16816(dn, a, bz.x, bz.y);
                    const float i0 = __fdividef(1.f, dn[0] + 1e-6f), i1 = __fdividef(1.f, dn[2] + 1e-6f);
                    uint4 v;
                    v.x = pack_bf16(n0[0] * i0, n0[1] * i0);
                    v.y = pack_bf16(n0[2] * i1, n0[3] * i1);
                    v.z = pack_bf16(n1[0] * i0, n1[1] * i0);
                    v.w = pack_bf16(n1[2] * i1, n1[3] * i1);
                    dst[hh * 256] = v;
                }
            }
            bar_arrive(3 + wg * 2, 160);
            TS(wg, 15);
        }

        {
            int prev_st = 0;
            TS(wg, 16);
#pragma unroll
            for (int b = 0; b < 18; b++) {
                if (b == 12) TS(wg, 17);
                mbar_wait(sb + BAR_FULL + 8 * rg.st, rg.ph);
                wg_fence();
                const uint64_t d = desc128 + (uint64_t)(rg.st * (STAGE_BYTES >> 4));
#pragma unroll
                for (int ks = 0; ks < 4; ks++)
                    wgmma_n128_rs(acc, reinterpret_cast<const uint32_t*>(&af[b % (APF + 1)][ks]), d + ks * 128, (b | ks) != 0);
                wg_commit();
                if (b > 0) {
                    wg_wait<1>();
                    if (lane < 2) mbar_arrive(sb + BAR_EMPTY + 8 * prev_st);
                }
                prev_st = rg.st;
                rg.next();
                if (b + APF < 18) {
                    mbar_wait(sb + BAR_AREADY + 8 * (b + APF), 0);
#pragma unroll
                    for (int ks = 0; ks < 4; ks++)
                        af[(b + APF) % (APF + 1)][ks] = __ldcg(a2r + ((b + APF) * 4 + ks) * 256);
                }
            }
            const int row0 = m2 * 128 + wg * 64 + w * 16 + g;
            const int col0 = j2 * 128 + rank * 64 + 2 * t;
            uint32_t xr[16];
#pragma unroll
            for (int nb = 0; nb < 8; nb++) {
                xr[2 * nb] = __ldg((const uint32_t*)(xg + (size_t)row0 * 512 + col0 + nb * 8));
                xr[2 * nb + 1] = __ldg((const uint32_t*)(xg + (size_t)(row0 + 8) * 512 + col0 + nb * 8));
            }
            wg_wait<0>();
            acc_fence(acc);
            TS(wg, 18);
            uint32_t rdst, rbar;
            asm volatile("mapa.shared::cluster.u32 %0, %1, %2;" : "=r"(rdst) : "r"(sb + OFF_STG + tid * 16), "r"(rank ^ 1));
            asm volatile("mapa.shared::cluster.u32 %0, %1, %2;" : "=r"(rbar) : "r"(sb + BAR_XCHG), "r"(rank ^ 1));
            float keep[32];
#pragma unroll
            for (int i = 0; i < 8; i++) {
                float s0 = rank ? acc[4 * i] : acc[32 + 4 * i], s1 = rank ? acc[4 * i + 1] : acc[33 + 4 * i];
                float s2 = rank ? acc[4 * i + 2] : acc[34 + 4 * i], s3 = rank ? acc[4 * i + 3] : acc[35 + 4 * i];
                asm volatile("st.async.shared::cluster.mbarrier::complete_tx::bytes.v4.f32 [%0], {%1,%2,%3,%4}, [%5];"
                             ::"r"(rdst + i * 4096), "f"(s0), "f"(s1), "f"(s2), "f"(s3), "r"(rbar) : "memory");
#pragma unroll
                for (int e = 0; e < 4; e++) keep[4 * i + e] = rank ? acc[32 + 4 * i + e] : acc[4 * i + e];
            }
            mbar_wait(sb + BAR_XCHG, 0);
            TS(wg, 19);
            const float4* rx = (const float4*)(smem + OFF_STG) + tid;
#pragma unroll
            for (int nb = 0; nb < 8; nb++) {
                const float4 p = rx[nb * 256];
                const uint32_t o0 = pack_bf16(keep[4 * nb] + p.x + bf_lo(xr[2 * nb]), keep[4 * nb + 1] + p.y + bf_hi(xr[2 * nb]));
                const uint32_t o1 = pack_bf16(keep[4 * nb + 2] + p.z + bf_lo(xr[2 * nb + 1]), keep[4 * nb + 3] + p.w + bf_hi(xr[2 * nb + 1]));
                *(uint32_t*)(outg + (size_t)row0 * 512 + col0 + nb * 8) = o0;
                *(uint32_t*)(outg + (size_t)(row0 + 8) * 512 + col0 + nb * 8) = o1;
            }
        }
        TS(wg, 20);
        asm volatile("barrier.cluster.arrive.relaxed.aligned;\nbarrier.cluster.wait.aligned;" ::: "memory");
        TS(wg, 21);
    }
}

typedef CUresult (*EncodeFn)(CUtensorMap*, CUtensorMapDataType, cuuint32_t, void*, const cuuint64_t*, const cuuint64_t*,
                             const cuuint32_t*, const cuuint32_t*, CUtensorMapInterleave, CUtensorMapSwizzle,
                             CUtensorMapL2promotion, CUtensorMapFloatOOBfill);

void make_map(EncodeFn enc, CUtensorMap* tm, const void* ptr, int rows, int cols, int box_rows, int box_cols,
              CUtensorMapSwizzle swz) {
    cuuint64_t dims[2] = {(cuuint64_t)cols, (cuuint64_t)rows};
    cuuint64_t strides[1] = {(cuuint64_t)cols * 2};
    cuuint32_t box[2] = {(cuuint32_t)box_cols, (cuuint32_t)box_rows};
    cuuint32_t es[2] = {1, 1};
    enc(tm, CU_TENSOR_MAP_DATA_TYPE_BFLOAT16, 2, const_cast<void*>(ptr), dims, strides, box, es,
        CU_TENSOR_MAP_INTERLEAVE_NONE, swz, CU_TENSOR_MAP_L2_PROMOTION_L2_256B, CU_TENSOR_MAP_FLOAT_OOB_FILL_NONE);
}

}

extern "C" void kernel_launch(void* const* d_in, const int* in_sizes, int n_in, void* d_out, int out_size) {
    (void)in_sizes; (void)n_in; (void)out_size;
    static EncodeFn enc = nullptr;
    if (!enc) {
        void* fn = nullptr;
        cudaDriverEntryPointQueryResult qr;
        cudaGetDriverEntryPoint("cuTensorMapEncodeTiled", &fn, cudaEnableDefault, &qr);
        enc = (EncodeFn)fn;
        cudaFuncSetAttribute(fused_kernel, cudaFuncAttributeMaxDynamicSharedMemorySize, SMEM_BYTES);
    }
    const void* x = d_in[0];
    const void* wqkv = d_in[1];
    const void* wo = d_in[2];
    const void* w1 = d_in[4];
    const void* w3 = d_in[5];
    const void* w2 = d_in[6];
    CUtensorMap tx, tqkv, t1, t3, t1h, t3h, t2, t2h, two;
    make_map(enc, &tx, x, 2048, 512, 128, 64, CU_TENSOR_MAP_SWIZZLE_128B);
    make_map(enc, &tqkv, wqkv, 512, 1536, 64, 64, CU_TENSOR_MAP_SWIZZLE_128B);
    make_map(enc, &t1, w1, 512, 1792, 64, 64, CU_TENSOR_MAP_SWIZZLE_128B);
    make_map(enc, &t3, w3, 512, 1792, 64, 64, CU_TENSOR_MAP_SWIZZLE_128B);
    make_map(enc, &t1h, w1, 512, 1792, 64, 32, CU_TENSOR_MAP_SWIZZLE_64B);
    make_map(enc, &t3h, w3, 512, 1792, 64, 32, CU_TENSOR_MAP_SWIZZLE_64B);
    make_map(enc, &t2, w2, 1792, 512, 64, 64, CU_TENSOR_MAP_SWIZZLE_128B);
    make_map(enc, &t2h, w2, 1792, 512, 32, 64, CU_TENSOR_MAP_SWIZZLE_128B);
    make_map(enc, &two, wo, 512, 512, 64, 64, CU_TENSOR_MAP_SWIZZLE_128B);
    fused_kernel<<<128, 384, SMEM_BYTES>>>(tx, tqkv, t1, t3, t1h, t3h, t2, t2h, two, (const __nv_bfloat16*)x,
                                           (__nv_bfloat16*)d_out);
}
```

```cpp
#include <cuda_runtime.h>
#include <cuda_bf16.h>
#include <cuda.h>
#include <stdint.h>

namespace {

constexpr int NST = 11;
constexpr int STAGE_BYTES = 16384;
constexpr int XST0 = 3;
constexpr int OFF_STG = NST * STAGE_BYTES;
constexpr int OFF_MISC = OFF_STG + 32768;
constexpr int OFF_KVRAW = OFF_MISC;
constexpr int OFF_KVFRAG = OFF_MISC + 8704;
constexpr int OFF_COMB = OFF_MISC + 12544;
constexpr int OFF_ONES = OFF_MISC + 11776;
constexpr int OFF_BARS = OFF_MISC + 12032;
constexpr int BAR_FULL = OFF_BARS;
constexpr int BAR_EMPTY = BAR_FULL + 8 * NST;
constexpr int BAR_XFULL = BAR_EMPTY + 8 * NST;
constexpr int BAR_KVREADY = BAR_XFULL + 64;
constexpr int BAR_XCHG = BAR_KVREADY + 8;
constexpr int BAR_AREADY = BAR_XCHG + 8;
constexpr int BAR_EPOCH = BAR_AREADY + 8 * 18;
constexpr int OFF_EPOCH = BAR_EPOCH + 8;
constexpr int SMEM_BYTES = OFF_MISC + 12544 + 6144;

constexpr int APF = 5;
constexpr unsigned SPIN_LIMIT = 1u << 24;

__device__ uint4 g_A2[16 * 2 * 18 * 4 * 256];
__device__ uint4 g_kvp[8 * 16 * 544];
__device__ uint4 g_kvs[8 * 544];
__device__ unsigned g_a2flag[16 * 8 * 4 * 2];
__device__ unsigned g_epoch;
__device__ unsigned g_ticket;

#define TS(role, i)
#define TSW(role, i)

__device__ __forceinline__ uint32_t smem_u32(const void* p) { return (uint32_t)__cvta_generic_to_shared(p); }
__device__ __forceinline__ void mbar_init(uint32_t bar, uint32_t cnt) {
    asm volatile("mbarrier.init.shared::cta.b64 [%0], %1;" ::"r"(bar), "r"(cnt) : "memory");
}
__device__ __forceinline__ void mbar_expect_tx(uint32_t bar, uint32_t bytes) {
    asm volatile("mbarrier.arrive.expect_tx.shared::cta.b64 _, [%0], %1;" ::"r"(bar), "r"(bytes) : "memory");
}
__device__ __forceinline__ void mbar_arrive(uint32_t bar) {
    asm volatile("mbarrier.arrive.shared::cta.b64 _, [%0];" ::"r"(bar) : "memory");
}
__device__ __forceinline__ void mbar_arrive_cta(uint32_t bar, uint32_t cta) {
    asm volatile(
        "{\n.reg .b32 ra;\nmapa.shared::cluster.u32 ra, %0, %1;\n"
        "mbarrier.arrive.shared::cluster.b64 _, [ra];\n}" ::"r"(bar), "r"(cta) : "memory");
}
__device__ __forceinline__ void mbar_wait(uint32_t bar, uint32_t parity) {
    asm volatile(
        "{\n.reg .pred p, q;\n.reg .u32 n;\nmov.u32 n, 0;\n"
        "WAIT_%=:\n"
        "mbarrier.try_wait.parity.shared::cta.b64 p, [%0], %1;\n"
        "@p bra.uni DONE_%=;\n"
        "add.u32 n, n, 1;\n"
        "setp.gt.u32 q, n, %2;\n"
        "@q trap;\n"
        "bra.uni WAIT_%=;\n"
        "DONE_%=:\n}"
        ::"r"(bar), "r"(parity), "n"(SPIN_LIMIT) : "memory");
}
__device__ __forceinline__ unsigned ld_acquire(const unsigned* p) {
    unsigned v;
    asm volatile("ld.acquire.gpu.global.u32 %0, [%1];" : "=r"(v) : "l"(p) : "memory");
    return v;
}
__device__ __forceinline__ void st_release(unsigned* p, unsigned v) {
    asm volatile("st.release.gpu.global.u32 [%0], %1;" ::"l"(p), "r"(v) : "memory");
}
__device__ __forceinline__ unsigned read_epoch() {
    return __shfl_sync(0xffffffffu, *(volatile unsigned*)&g_epoch, 0) + 1;
}
__device__ __forceinline__ void tma_load(uint32_t dst, const CUtensorMap* tm, uint32_t bar, int x, int y) {
    asm volatile(
        "cp.async.bulk.tensor.2d.shared::cluster.global.mbarrier::complete_tx::bytes [%0], [%1, {%3, %4}], [%2];"
        ::"r"(dst), "l"(tm), "r"(bar), "r"(x), "r"(y) : "memory");
}
__device__ __forceinline__ void tma_load_mc(uint32_t dst, const CUtensorMap* tm, uint32_t bar, int x, int y) {
    asm volatile(
        "cp.async.bulk.tensor.2d.shared::cluster.global.mbarrier::complete_tx::bytes.multicast::cluster "
        "[%0], [%1, {%3, %4}], [%2], %5;"
        ::"r"(dst), "l"(tm), "r"(bar), "r"(x), "r"(y), "h"((uint16_t)3) : "memory");
}
__device__ __forceinline__ void prefetch_tm(const CUtensorMap* tm) {
    asm volatile("prefetch.tensormap [%0];" ::"l"(tm) : "memory");
}
__device__ __forceinline__ void bar_sync(int id, int n) { asm volatile("bar.sync %0, %1;" ::"r"(id), "r"(n) : "memory"); }
__device__ __forceinline__ void bar_arrive(int id, int n) { asm volatile("bar.arrive %0, %1;" ::"r"(id), "r"(n) : "memory"); }
__device__ __forceinline__ void wg_fence() { asm volatile("wgmma.fence.sync.aligned;" ::: "memory"); }
__device__ __forceinline__ void wg_commit() { asm volatile("wgmma.commit_group.sync.aligned;" ::: "memory"); }
template <int N>
__device__ __forceinline__ void wg_wait() { asm volatile("wgmma.wait_group.sync.aligned %0;" ::"n"(N) : "memory"); }

__device__ __forceinline__ uint64_t make_desc(uint32_t addr, uint32_t lbo, uint32_t sbo, uint64_t swz) {
    return (uint64_t)((addr & 0x3FFFF) >> 4) | ((uint64_t)(lbo >> 4) << 16) | ((uint64_t)(sbo >> 4) << 32) | (swz << 62);
}

#define ACC8(a, o) "+f"(a[o]), "+f"(a[o + 1]), "+f"(a[o + 2]), "+f"(a[o + 3]), "+f"(a[o + 4]), "+f"(a[o + 5]), "+f"(a[o + 6]), "+f"(a[o + 7])
__device__ __forceinline__ void wgmma_n128_rs(float (&d)[64], const uint32_t* a, uint64_t db, int scale_d) {
    asm volatile(
        "{\n.reg .pred p;\nsetp.ne.b32 p, %69, 0;\n"
        "wgmma.mma_async.sync.aligned.m64n128k16.f32.bf16.bf16 "
        "{%0,%1,%2,%3,%4,%5,%6,%7,%8,%9,%10,%11,%12,%13,%14,%15,%16,%17,%18,%19,%20,%21,%22,%23,%24,%25,%26,%27,%28,%29,%30,%31,"
        "%32,%33,%34,%35,%36,%37,%38,%39,%40,%41,%42,%43,%44,%45,%46,%47,%48,%49,%50,%51,%52,%53,%54,%55,%56,%57,%58,%59,%60,%61,%62,%63},"
        "{%64,%65,%66,%67}, %68, p, 1, 1, 1;\n}"
        : ACC8(d, 0), ACC8(d, 8), ACC8(d, 16), ACC8(d, 24), ACC8(d, 32), ACC8(d, 40), ACC8(d, 48), ACC8(d, 56)
        : "r"(a[0]), "r"(a[1]), "r"(a[2]), "r"(a[3]), "l"(db), "r"(scale_d));
}
__device__ __forceinline__ void wgmma_n64_rs(float (&d)[32], const uint32_t* a, uint64_t db, int scale_d) {
    asm volatile(
        "{\n.reg .pred p;\nsetp.ne.b32 p, %37, 0;\n"
        "wgmma.mma_async.sync.aligned.m64n64k16.f32.bf16.bf16 "
        "{%0,%1,%2,%3,%4,%5,%6,%7,%8,%9,%10,%11,%12,%13,%14,%15,%16,%17,%18,%19,%20,%21,%22,%23,%24,%25,%26,%27,%28,%29,%30,%31},"
        "{%32,%33,%34,%35}, %36, p, 1, 1, 1;\n}"
        : ACC8(d, 0), ACC8(d, 8), ACC8(d, 16), ACC8(d, 24)
        : "r"(a[0]), "r"(a[1]), "r"(a[2]), "r"(a[3]), "l"(db), "r"(scale_d));
}
__device__ __forceinline__ void wgmma_n64_ss_tt(float (&d)[32], uint64_t da, uint64_t db, int scale_d) {
    asm volatile(
        "{\n.reg .pred p;\nsetp.ne.b32 p, %34, 0;\n"
        "wgmma.mma_async.sync.aligned.m64n64k16.f32.bf16.bf16 "
        "{%0,%1,%2,%3,%4,%5,%6,%7,%8,%9,%10,%11,%12,%13,%14,%15,%16,%17,%18,%19,%20,%21,%22,%23,%24,%25,%26,%27,%28,%29,%30,%31},"
        "%32, %33, p, 1, 1, 1, 1;\n}"
        : ACC8(d, 0), ACC8(d, 8), ACC8(d, 16), ACC8(d, 24)
        : "l"(da), "l"(db), "r"(scale_d));
}
__device__ __forceinline__ void wgmma_n8_ss_tn(float (&d)[4], uint64_t da, uint64_t db, int scale_d) {
    asm volatile(
        "{\n.reg .pred p;\nsetp.ne.b32 p, %6, 0;\n"
        "wgmma.mma_async.sync.aligned.m64n8k16.f32.bf16.bf16 {%0,%1,%2,%3}, %4, %5, p, 1, 1, 1, 0;\n}"
        : "+f"(d[0]), "+f"(d[1]), "+f"(d[2]), "+f"(d[3])
        : "l"(da), "l"(db), "r"(scale_d));
}
template <int N>
__device__ __forceinline__ void acc_fence(float (&d)[N]) {
#pragma unroll
    for (int i = 0; i < N; i++) asm volatile("" : "+f"(d[i])::"memory");
}
__device__ __forceinline__ void mma16816(float (&c)[4], const uint32_t* a, uint32_t b0, uint32_t b1) {
    asm volatile(
        "mma.sync.aligned.m16n8k16.row.col.f32.bf16.bf16.f32 {%0,%1,%2,%3}, {%4,%5,%6,%7}, {%8,%9}, {%0,%1,%2,%3};"
        : "+f"(c[0]), "+f"(c[1]), "+f"(c[2]), "+f"(c[3])
        : "r"(a[0]), "r"(a[1]), "r"(a[2]), "r"(a[3]), "r"(b0), "r"(b1));
}
__device__ __forceinline__ uint32_t pack_bf16(float lo, float hi) {
    uint32_t r;
    asm("cvt.rn.bf16x2.f32 %0, %1, %2;" : "=r"(r) : "f"(hi), "f"(lo));
    return r;
}
__device__ __forceinline__ float bf_lo(uint32_t v) { return __uint_as_float(v << 16); }
__device__ __forceinline__ float bf_hi(uint32_t v) { return __uint_as_float(v & 0xffff0000u); }
__device__ __forceinline__ float bf16_round(float v) { return __bfloat162float(__float2bfloat16_rn(v)); }
__device__ __forceinline__ float sqrt_fast(float v) {
    float r;
    asm("sqrt.approx.ftz.f32 %0, %1;" : "=f"(r) : "f"(v));
    return r;
}
__device__ __forceinline__ float rcp_fast(float v) {
    float r;
    asm("rcp.approx.ftz.f32 %0, %1;" : "=f"(r) : "f"(v));
    return r;
}
__device__ __forceinline__ float ex2_fast(float v) {
    float r;
    asm("ex2.approx.ftz.f32 %0, %1;" : "=f"(r) : "f"(v));
    return r;
}
struct RowScale { float rho, rl, rho2; };
__device__ __forceinline__ float phi_f(float a, const RowScale& r) {
    return fmaf(fmaxf(a, 0.f), r.rho, ex2_fast(fminf(a, 0.f) * r.rl) + 1e-6f);
}
__device__ __forceinline__ float swiglu_f(float ga, float ua, const RowScale& r) {
    return (ga * ua) * r.rho2 * rcp_fast(1.f + ex2_fast(-ga * r.rl));
}
__device__ __forceinline__ uint4 swiglu8(const float* gp, const float* up, const RowScale& r0, const RowScale& r1) {
    uint4 v;
    v.x = pack_bf16(swiglu_f(gp[0], up[0], r0), swiglu_f(gp[1], up[1], r0));
    v.y = pack_bf16(swiglu_f(gp[2], up[2], r1), swiglu_f(gp[3], up[3], r1));
    v.z = pack_bf16(swiglu_f(gp[4], up[4], r0), swiglu_f(gp[5], up[5], r0));
    v.w = pack_bf16(swiglu_f(gp[6], up[6], r1), swiglu_f(gp[7], up[7], r1));
    return v;
}
__device__ __forceinline__ void cp_async16(uint32_t dst, const void* src) {
    asm volatile("cp.async.cg.shared.global [%0], [%1], 16;" ::"r"(dst), "l"(src) : "memory");
}

struct Ring {
    int st;
    uint32_t ph;
    __device__ __forceinline__ void next() {
        if (++st == NST) { st = 0; ph ^= 1; }
    }
};

__device__ __forceinline__ void sumsq16(uint32_t* a, float (&q)[4]) {
#pragma unroll
    for (int i = 0; i < 16; i++) asm volatile("" : "+r"(a[i]));
#pragma unroll
    for (int i = 0; i < 16; i += 2) {
        const float a0 = bf_lo(a[i]), a1 = bf_hi(a[i]), b0 = bf_lo(a[i + 1]), b1 = bf_hi(a[i + 1]);
        q[0] = fmaf(a0, a0, q[0]); q[1] = fmaf(a1, a1, q[1]);
        q[2] = fmaf(b0, b0, q[2]); q[3] = fmaf(b1, b1, q[3]);
    }
}
template <bool SUMSQ>
__device__ __forceinline__ void mainloop128(float (&acc)[64], uint32_t (&xa)[128], Ring& rg, uint32_t sb,
                                            uint64_t desc128, int lane, int wg, float (&q)[4]) {
    int prev_st = 0;
    bar_sync(7 + wg, 256);
#pragma unroll
    for (int kb = 0; kb < 8; kb++) {
        mbar_wait(sb + BAR_FULL + 8 * rg.st, rg.ph);
        wg_fence();
        const uint64_t d = desc128 + (uint64_t)(rg.st * (STAGE_BYTES >> 4));
#pragma unroll
        for (int ks = 0; ks < 4; ks++) wgmma_n128_rs(acc, &xa[(kb * 4 + ks) * 4], d + ks * 128, (kb | ks) != 0);
        wg_commit();
        if (kb == 7) bar_arrive(8 - wg, 256);
        if (kb > 0) {
            wg_wait<1>();
            if (lane < 2) mbar_arrive_cta(sb + BAR_EMPTY + 8 * prev_st, lane);
            if (SUMSQ) sumsq16(&xa[(kb - 1) * 16], q);
        }
        prev_st = rg.st;
        rg.next();
    }
    wg_wait<0>();
    acc_fence(acc);
    if (lane < 2) mbar_arrive_cta(sb + BAR_EMPTY + 8 * prev_st, lane);
    if (SUMSQ) sumsq16(&xa[7 * 16], q);
}
__device__ __forceinline__ void mainloop64x2(float (&a0)[32], float (&a1)[32], const uint32_t (&xa)[128], Ring& rg,
                                             uint32_t sb, uint64_t desc128, uint64_t desc64, int lane, int wg) {
    int prev_st = 0;
    bar_sync(7 + wg, 256);
#pragma unroll
    for (int kb = 0; kb < 8; kb++) {
        mbar_wait(sb + BAR_FULL + 8 * rg.st, rg.ph);
        wg_fence();
        const uint64_t d = desc128 + (uint64_t)(rg.st * (STAGE_BYTES >> 4));
        const uint64_t d2 = desc64 + (uint64_t)(rg.st * (STAGE_BYTES >> 4));
#pragma unroll
        for (int ks = 0; ks < 4; ks++) {
            wgmma_n64_rs(a0, &xa[(kb * 4 + ks) * 4], d + ks * 128, (kb | ks) != 0);
            wgmma_n64_rs(a1, &xa[(kb * 4 + ks) * 4], d2 + ks * 64, (kb | ks) != 0);
        }
        wg_commit();
        if (kb == 7 && wg == 0) bar_arrive(8, 256);
        if (kb > 0) {
            wg_wait<1>();
            if (lane < 2) mbar_arrive_cta(sb + BAR_EMPTY + 8 * prev_st, lane);
        }
        prev_st = rg.st;
        rg.next();
    }
    wg_wait<0>();
    acc_fence(a0);
    acc_fence(a1);
    if (lane < 2) mbar_arrive_cta(sb + BAR_EMPTY + 8 * prev_st, lane);
}

__global__ void __cluster_dims__(2, 1, 1) __launch_bounds__(384, 1)
fused_kernel(const __grid_constant__ CUtensorMap tm_x, const __grid_constant__ CUtensorMap tm_qkv,
             const __grid_constant__ CUtensorMap tm_w1, const __grid_constant__ CUtensorMap tm_w3,
             const __grid_constant__ CUtensorMap tm_w1h, const __grid_constant__ CUtensorMap tm_w3h,
             const __grid_constant__ CUtensorMap tm_w2, const __grid_constant__ CUtensorMap tm_w2h,
             const __grid_constant__ CUtensorMap tm_wo, const __nv_bfloat16* __restrict__ xg,
             __nv_bfloat16* __restrict__ outg) {
    extern __shared__ __align__(1024) uint8_t smem[];
    const uint32_t sb = smem_u32(smem);
    const int tid = threadIdx.x;
    const int warp = tid >> 5, lane = tid & 31;
    const int rank = blockIdx.x & 1;
    const int pair = blockIdx.x >> 1;
    const int c = pair & 7;
    const int m = (pair >> 3) * 2 + rank;
    const int m2 = (pair >> 3) * 2 + (c & 1);
    const int j2 = c >> 1;

    TS(tid >> 7, 0);
    if (tid == 256) {
#pragma unroll
        for (int i = 0; i < 8; i++) mbar_init(sb + BAR_XFULL + 8 * i, 1);
        asm volatile("fence.proxy.async.shared::cta;" ::: "memory");
#pragma unroll
        for (int kb = 0; kb < 8; kb++) {
            mbar_expect_tx(sb + BAR_XFULL + 8 * kb, 16384);
            tma_load(sb + (XST0 + kb) * STAGE_BYTES, &tm_x, sb + BAR_XFULL + 8 * kb, kb * 64, m * 128);
        }
        TS(2, 21);
    } else if (tid == 0) {
#pragma unroll
        for (int i = 0; i < NST; i++) mbar_init(sb + BAR_FULL + 8 * i, 1);
        asm volatile("fence.mbarrier_init.release.cluster;" ::: "memory");
    } else if (tid == 32) {
#pragma unroll
        for (int i = 0; i < NST; i++) mbar_init(sb + BAR_EMPTY + 8 * i, 16);
        asm volatile("fence.mbarrier_init.release.cluster;" ::: "memory");
    } else if (tid == 64) {
#pragma unroll
        for (int i = 0; i < 10; i++) mbar_init(sb + BAR_KVREADY + 8 * i, 1);
        mbar_expect_tx(sb + BAR_XCHG, 32768);
        asm volatile("fence.mbarrier_init.release.cluster;" ::: "memory");
    } else if (tid == 96) {
#pragma unroll
        for (int i = 10; i < 21; i++) mbar_init(sb + BAR_KVREADY + 8 * i, 1);
    } else if (tid == 288) {
        prefetch_tm(&tm_qkv);
        prefetch_tm(rank ? &tm_w3 : &tm_w1);
        prefetch_tm(&tm_w1h);
        prefetch_tm(&tm_w3h);
        prefetch_tm(&tm_w2);
        prefetch_tm(&tm_w2h);
        prefetch_tm(&tm_wo);
    } else if (tid >= 320) {
        ((uint32_t*)(smem + OFF_ONES))[tid - 320] = 0x3F803F80u;
        asm volatile("fence.proxy.async.shared::cta;" ::: "memory");
    }
    __syncthreads();
    TS(tid >> 7, 22);
    asm volatile("barrier.cluster.arrive.relaxed.aligned;\nbarrier.cluster.wait.acquire.aligned;" ::: "memory");

    if (warp >= 8) {
        asm volatile("setmaxnreg.dec.sync.aligned.u32 40;");
        if (warp == 8) {
            if (lane == 0) {
                int st = 0;
                uint32_t lap = 0;
                for (int it = 0; it < 40; it++) {
                    const int tile = it >> 3, kb = it & 7;
                    const uint32_t full = sb + BAR_FULL + 8 * st;
                    mbar_wait(sb + BAR_EMPTY + 8 * st, (st >= XST0) ? (lap & 1) : ((lap & 1) ^ 1));
                    mbar_expect_tx(full, STAGE_BYTES);
                    const uint32_t dst = sb + st * STAGE_BYTES;
                    if (tile == 0) {
                        tma_load_mc(dst + rank * 8192, &tm_qkv, full, 512 + 512 * rank + 64 * c, kb * 64);
                    } else if (tile < 4) {
                        tma_load_mc(dst + rank * 8192, rank ? &tm_w3 : &tm_w1, full, 224 * c + 64 * (tile - 1), kb * 64);
                    } else if (rank == 0) {
                        tma_load_mc(dst, &tm_qkv, full, 64 * c, kb * 64);
                    } else {
                        tma_load_mc(dst + 8192, &tm_w1h, full, 224 * c + 192, kb * 64);
                        tma_load_mc(dst + 12288, &tm_w3h, full, 224 * c + 192, kb * 64);
                    }
                    if (++st == NST) { st = 0; lap++; }
                }
                TS(2, 1);
                for (int b = 0; b < 18; b++) {
                    const uint32_t full = sb + BAR_FULL + 8 * st;
                    const uint32_t dst = sb + st * STAGE_BYTES;
                    mbar_wait(sb + BAR_EMPTY + 8 * st, (st >= XST0) ? (lap & 1) : ((lap & 1) ^ 1));
                    mbar_expect_tx(full, STAGE_BYTES);
                    if (b < 12) {
                        const int row = 224 * (4 * rank + (b & 3)) + 64 * (b >> 2);
                        tma_load(dst, &tm_w2, full, 128 * j2, row);
                        tma_load(dst + 8192, &tm_w2, full, 128 * j2 + 64, row);
                    } else if (b < 14) {
                        const int row = 224 * (4 * rank + 2 * (b - 12)) + 192;
                        tma_load(dst, &tm_w2h, full, 128 * j2, row);
                        tma_load(dst + 4096, &tm_w2h, full, 128 * j2, row + 224);
                        tma_load(dst + 8192, &tm_w2h, full, 128 * j2 + 64, row);
                        tma_load(dst + 12288, &tm_w2h, full, 128 * j2 + 64, row + 224);
                    } else {
                        const int row = 64 * (4 * rank + (b - 14));
                        tma_load(dst, &tm_wo, full, 128 * j2, row);
                        tma_load(dst + 8192, &tm_wo, full, 128 * j2 + 64, row);
                    }
                    TS(2, 2 + b);
                    if (++st == NST) { st = 0; lap++; }
                }
            }
        } else if (warp < 11) {
            const int wg = warp - 9;
            const unsigned epoch = read_epoch();
            bar_arrive(9, 96);
            for (int t = 1; t < 5; t++) {
                bar_sync(3 + wg * 2 + (t & 1), 160);
                if (lane == 0) st_release(&g_a2flag[((m * 8 + c) * 4 + (t - 1)) * 2 + wg], epoch);
                TSW(3, 2 * t + wg);
            }
        } else {
            const unsigned epoch = read_epoch();
            bar_sync(9, 96);
            if (lane == 0) {
                const unsigned tk = atomicInc(&g_ticket, 127u);
                if (tk == 127u) *(volatile unsigned*)&g_epoch = epoch;
            }
            if (lane == 0) *(volatile unsigned*)(smem + OFF_EPOCH) = epoch;
            __syncwarp();
            if (lane == 0) mbar_arrive(sb + BAR_EPOCH);
            const uint4* raw = (const uint4*)(smem + OFF_KVRAW);
            for (int level = 0; level < 2; level++) {
                unsigned n = 0;
                while (true) {
#pragma unroll 1
                    for (int k = 0; k < 17; k++) {
                        const int i = lane + 32 * k;
                        const uint4* src = level ? g_kvs + c * 544 + i
                                                 : g_kvp + (size_t)(c * 16 + i / 34) * 544 + 34 * m + i % 34;
                        cp_async16(sb + OFF_KVRAW + i * 16, src);
                    }
                    asm volatile("cp.async.wait_all;" ::: "memory");
                    bool ok = true;
#pragma unroll 1
                    for (int k = 0; k < 17; k++) {
                        const uint4 v = raw[lane + 32 * k];
                        ok = ok && v.y == epoch && v.w == epoch;
                    }
                    if (__all_sync(0xffffffffu, ok)) break;
                    __nanosleep(100);
                    if (++n > SPIN_LIMIT) asm volatile("trap;");
                }
                TSW(4, 2 * level);
                if (level == 0) {
                    for (int j = lane; j < 34; j += 32) {
                        float s0 = 0.f, s1 = 0.f;
#pragma unroll 4
                        for (int pp = 0; pp < 16; pp++) {
                            const uint4 v = raw[pp * 34 + j];
                            s0 += __uint_as_float(v.x);
                            s1 += __uint_as_float(v.z);
                        }
                        g_kvs[c * 544 + 34 * m + j] = make_uint4(__float_as_uint(s0), epoch, __float_as_uint(s1), epoch);
                    }
                    __syncwarp();
                    TSW(4, 1);
                }
            }
            const float* ks = (const float*)(smem + OFF_KVRAW);
            uint2* kf = (uint2*)(smem + OFF_KVFRAG);
            const int g = lane >> 2, t = lane & 3;
#pragma unroll 1
            for (int hh = 0; hh < 4; hh++) {
                const float* k = ks + hh * 544;
#pragma unroll
                for (int b = 0; b < 2; b++) {
                    uint2 v;
                    v.x = pack_bf16(k[2 * ((2 * t) * 16 + 8 * b + g)], k[2 * ((2 * t + 1) * 16 + 8 * b + g)]);
                    v.y = pack_bf16(k[2 * ((2 * t + 8) * 16 + 8 * b + g)], k[2 * ((2 * t + 9) * 16 + 8 * b + g)]);
                    kf[(hh * 3 + b) * 32 + lane] = v;
                }
                uint2 z;
                z.x = pack_bf16(k[2 * (256 + 2 * t)], k[2 * (256 + 2 * t + 1)]);
                z.y = pack_bf16(k[2 * (256 + 2 * t + 8)], k[2 * (256 + 2 * t + 9)]);
                kf[(hh * 3 + 2) * 32 + lane] = z;
            }
            __syncwarp();
            if (lane == 0) mbar_arrive(sb + BAR_KVREADY);
            TSW(4, 4);
            const unsigned* fl = g_a2flag + (m2 * 8 + rank * 4) * 8 + lane;
            unsigned ready = 0;
            for (int b = 0; b < 18; b++) {
                const unsigned need = (b < 12) ? (3u << ((b & 3) * 8 + (b >> 2) * 2)) : (b < 14) ? (0xC0C0u << ((b - 12) * 16)) : 0u;
                unsigned n = 0;
                while ((ready & need) != need) {
                    ready = __ballot_sync(0xffffffffu, ld_acquire(fl) == epoch);
                    if (++n > SPIN_LIMIT) asm volatile("trap;");
                }
                if (lane == 0) mbar_arrive(sb + BAR_AREADY + 8 * b);
                TSW(5, b);
            }
        }
    } else {
        asm volatile("setmaxnreg.inc.sync.aligned.u32 232;");
        const int wg = warp >> 2, w = warp & 3;
        const int g = lane >> 2, t = lane & 3;
        float acc[64];
        uint32_t xa[128];
        float rho0, rho1;
        RowScale r0, r1;

        TS(wg, 1);
        {
            const int row = wg * 64 + w * 16 + (lane & 7) + ((lane >> 3) & 1) * 8;
            const uint32_t rbase = sb + XST0 * STAGE_BYTES + row * 128;
            const int hi = lane >> 4, r7 = lane & 7;
            float sm[4][4];
#pragma unroll
            for (int i = 0; i < 16; i++) sm[i >> 2][i & 3] = 0.f;
            if (wg == 1) bar_arrive(7, 256);
#pragma unroll
            for (int kb = 0; kb < 8; kb++) {
                mbar_wait(sb + BAR_XFULL + 8 * kb, 0);
#pragma unroll
                for (int ks = 0; ks < 4; ks++) {
                    uint32_t* a = &xa[(kb * 4 + ks) * 4];
                    const uint32_t addr = rbase + kb * STAGE_BYTES + (((2 * ks + hi) ^ r7) << 4);
                    asm volatile("ldmatrix.sync.aligned.m8n8.x4.shared.b16 {%0,%1,%2,%3}, [%4];"
                                 : "=r"(a[0]), "=r"(a[1]), "=r"(a[2]), "=r"(a[3]) : "r"(addr) : "memory");
                    mma16816(sm[ks], a, 0x3F803F80u, 0x3F803F80u);
                }
            }
            TS(wg, 2);
            const float mean0 = ((sm[0][0] + sm[1][0]) + (sm[2][0] + sm[3][0])) * (1.f / 512.f);
            const float mean1 = ((sm[0][2] + sm[1][2]) + (sm[2][2] + sm[3][2])) * (1.f / 512.f);
            __syncwarp();
            if (lane < 16) mbar_arrive_cta(sb + BAR_EMPTY + 8 * (XST0 + (lane >> 1)), lane & 1);
            const __nv_bfloat162 mb0 = __float2bfloat162_rn(mean0), mb1 = __float2bfloat162_rn(mean1);
#pragma unroll
            for (int i = 0; i < 128; i++) {
                __nv_bfloat162 v = *reinterpret_cast<__nv_bfloat162*>(&xa[i]);
                v = __hsub2(v, (i & 1) ? mb1 : mb0);
                xa[i] = *reinterpret_cast<uint32_t*>(&v);
            }
            rho0 = mean0 - __low2float(mb0);
            rho1 = mean1 - __low2float(mb1);
        }

        TS(wg, 3);
        Ring rg = {0, 0};
        const uint64_t desc128 = make_desc(sb, 8192, 1024, 1);
        const uint64_t desc64 = make_desc(sb + 8192, 4096, 512, 2);
        uint4* a2w = g_A2 + (size_t)((m * 2 + (c >> 2)) * 18) * 4 * 256 + warp * 32 + lane;
        const int cc = c & 3;

        float qs[4] = {0.f, 0.f, 0.f, 0.f};
        {
            mainloop128<true>(acc, xa, rg, sb, desc128, lane, wg, qs);
            TS(wg, 4);
            float q0 = qs[0] + qs[1], q2 = qs[2] + qs[3];
            q0 += __shfl_xor_sync(0xffffffffu, q0, 1); q2 += __shfl_xor_sync(0xffffffffu, q2, 1);
            q0 += __shfl_xor_sync(0xffffffffu, q0, 2); q2 += __shfl_xor_sync(0xffffffffu, q2, 2);
            const float var0 = fmaxf(q0 * (1.f / 512.f) - rho0 * rho0, 0.f), var1 = fmaxf(q2 * (1.f / 512.f) - rho1 * rho1, 0.f);
            rho0 = rcp_fast(bf16_round(sqrt_fast(bf16_round(bf16_round(var0) + 1e-5f))));
            rho1 = rcp_fast(bf16_round(sqrt_fast(bf16_round(bf16_round(var1) + 1e-5f))));
            r0.rho = rho0; r0.rl = rho0 * 1.4426950408889634f; r0.rho2 = rho0 * rho0;
            r1.rho = rho1; r1.rl = rho1 * 1.4426950408889634f; r1.rho2 = rho1 * rho1;
            {
                TS(wg, 24);
                const uint32_t pkb = sb + OFF_STG + wg * 16384;
                const uint32_t ra = pkb + (w * 16 + g) * 128 + t * 4;
#pragma unroll
                for (int nb = 0; nb < 8; nb++) {
                    const uint32_t off = (uint32_t)((nb ^ g) << 4);
                    uint32_t p0 = pack_bf16(phi_f(acc[nb * 4], r0), phi_f(acc[nb * 4 + 1], r0));
                    uint32_t p1 = pack_bf16(phi_f(acc[nb * 4 + 2], r1), phi_f(acc[nb * 4 + 3], r1));
                    uint32_t v0 = pack_bf16(acc[32 + nb * 4] * rho0, acc[32 + nb * 4 + 1] * rho0);
                    uint32_t v1 = pack_bf16(acc[32 + nb * 4 + 2] * rho1, acc[32 + nb * 4 + 3] * rho1);
                    asm volatile("st.shared.u32 [%0], %1;" ::"r"(ra + off), "r"(p0) : "memory");
                    asm volatile("st.shared.u32 [%0], %1;" ::"r"(ra + off + 1024), "r"(p1) : "memory");
                    asm volatile("st.shared.u32 [%0], %1;" ::"r"(ra + off + 8192), "r"(v0) : "memory");
                    asm volatile("st.shared.u32 [%0], %1;" ::"r"(ra + off + 8192 + 1024), "r"(v1) : "memory");
                }
                TS(wg, 25);
                asm volatile("fence.proxy.async.shared::cta;" ::: "memory");
                bar_sync(1 + wg, 128);
                TS(wg, 26);
                const uint64_t da = make_desc(pkb, 8192, 1024, 1);
                const uint64_t db = make_desc(pkb + 8192, 8192, 1024, 1);
                const uint64_t d1 = make_desc(sb + OFF_ONES, 128, 128, 0);
                float kva[32], za[4];
                wg_fence();
#pragma unroll
                for (int ks = 0; ks < 4; ks++) {
                    wgmma_n64_ss_tt(kva, da + ks * 128, db + ks * 128, ks != 0);
                    wgmma_n8_ss_tn(za, da + ks * 128, d1, ks != 0);
                }
                wg_commit();
                wg_wait<0>();
                acc_fence(kva);
                acc_fence(za);
                TS(wg, 27);
                float o[8];
#pragma unroll
                for (int i = 0; i < 8; i++)
                    o[i] = (w == 0) ? kva[i] : (w == 1) ? kva[8 + i] : (w == 2) ? kva[16 + i] : kva[24 + i];
                float4* comb = (float4*)(smem + OFF_COMB) + (tid & 127);
                if (wg == 0) {
                    comb[0] = make_float4(o[0], o[1], o[2], o[3]);
                    comb[128] = make_float4(o[4], o[5], o[6], o[7]);
                    comb[256] = make_float4(za[0], za[2], 0.f, 0.f);
                    bar_arrive(10, 256);
                } else {
                    mbar_wait(sb + BAR_EPOCH, 0);
                    const unsigned epoch = *(volatile unsigned*)(smem + OFF_EPOCH);
                    bar_sync(10, 256);
                    const float4 a = comb[0], b = comb[128], zz = comb[256];
                    uint4* dst = g_kvp + (size_t)(c * 16 + m) * 544 + w * 136;
                    dst[g * 8 + t] = make_uint4(__float_as_uint(o[0] + a.x), epoch, __float_as_uint(o[1] + a.y), epoch);
                    dst[(g + 8) * 8 + t] = make_uint4(__float_as_uint(o[2] + a.z), epoch, __float_as_uint(o[3] + a.w), epoch);
                    dst[g * 8 + 4 + t] = make_uint4(__float_as_uint(o[4] + b.x), epoch, __float_as_uint(o[5] + b.y), epoch);
                    dst[(g + 8) * 8 + 4 + t] = make_uint4(__float_as_uint(o[6] + b.z), epoch, __float_as_uint(o[7] + b.w), epoch);
                    if (t == 0) {
                        uint2* dz = (uint2*)(dst + 128);
                        dz[g] = make_uint2(__float_as_uint(za[0] + zz.x), epoch);
                        dz[g + 8] = make_uint2(__float_as_uint(za[2] + zz.y), epoch);
                    }
                }
            }
            TS(wg, 5);
        }
#pragma unroll 1
        for (int tile = 1; tile < 4; tile++) {
            mainloop128<false>(acc, xa, rg, sb, desc128, lane, wg, qs);
            TS(wg, 4 + 2 * tile);
            {
                uint4* dst = a2w + (size_t)((4 * (tile - 1) + cc) * 4) * 256;
#pragma unroll
                for (int ks = 0; ks < 4; ks++) dst[ks * 256] = swiglu8(&acc[ks * 8], &acc[32 + ks * 8], r0, r1);
            }
            bar_arrive(3 + wg * 2 + (tile & 1), 160);
            TS(wg, 5 + 2 * tile);
        }
        const uint4* a2r = g_A2 + (size_t)((m2 * 2 + rank) * 18) * 4 * 256 + warp * 32 + lane;
        uint4 af[APF + 1][4];
        {
            float qa[32], gu[32];
            mainloop64x2(qa, gu, xa, rg, sb, desc128, desc64, lane, wg);
            TS(wg, 12);
#pragma unroll
            for (int b = 0; b < APF; b++) {
                mbar_wait(sb + BAR_AREADY + 8 * b, 0);
#pragma unroll
                for (int ks = 0; ks < 4; ks++) af[b][ks] = __ldcg(a2r + (b * 4 + ks) * 256);
            }
            {
                uint4* dst = a2w + (size_t)((12 + (cc >> 1)) * 4 + 2 * (cc & 1)) * 256;
#pragma unroll
                for (int ks = 0; ks < 2; ks++) dst[ks * 256] = swiglu8(&gu[ks * 8], &gu[16 + ks * 8], r0, r1);
                TS(wg, 13);
                mbar_wait(sb + BAR_KVREADY, 0);
                TS(wg, 14);
                const uint2* kf = (const uint2*)(smem + OFF_KVFRAG);
                dst = a2w + (size_t)((14 + cc) * 4) * 256;
#pragma unroll
                for (int hh = 0; hh < 4; hh++) {
                    const float* q = &qa[hh * 8];
                    uint32_t a[4];
                    a[0] = pack_bf16(phi_f(q[0], r0), phi_f(q[1], r0));
                    a[1] = pack_bf16(phi_f(q[2], r1), phi_f(q[3], r1));
                    a[2] = pack_bf16(phi_f(q[4], r0), phi_f(q[5], r0));
                    a[3] = pack_bf16(phi_f(q[6], r1), phi_f(q[7], r1));
                    float n0[4] = {0.f, 0.f, 0.f, 0.f}, n1[4] = {0.f, 0.f, 0.f, 0.f}, dn[4] = {0.f, 0.f, 0.f, 0.f};
                    const uint2 b0 = kf[(hh * 3 + 0) * 32 + lane], b1 = kf[(hh * 3 + 1) * 32 + lane],
                                bz = kf[(hh * 3 + 2) * 32 + lane];
                    mma16816(n0, a, b0.x, b0.y);
                    mma16816(n1, a, b1.x, b1.y);
                    mma16816(dn, a, bz.x, bz.y);
                    const float i0 = rcp_fast(dn[0] + 1e-6f), i1 = rcp_fast(dn[2] + 1e-6f);
                    uint4 v;
                    v.x = pack_bf16(n0[0] * i0, n0[1] * i0);
                    v.y = pack_bf16(n0[2] * i1, n0[3] * i1);
                    v.z = pack_bf16(n1[0] * i0, n1[1] * i0);
                    v.w = pack_bf16(n1[2] * i1, n1[3] * i1);
                    dst[hh * 256] = v;
                }
            }
            bar_arrive(3 + wg * 2, 160);
            TS(wg, 15);
        }

        {
            int prev_st = 0;
            TS(wg, 16);
#pragma unroll
            for (int b = 0; b < 18; b++) {
                if (b == 12) TS(wg, 17);
                mbar_wait(sb + BAR_FULL + 8 * rg.st, rg.ph);
                wg_fence();
                const uint64_t d = desc128 + (uint64_t)(rg.st * (STAGE_BYTES >> 4));
#pragma unroll
                for (int ks = 0; ks < 4; ks++)
                    wgmma_n128_rs(acc, reinterpret_cast<const uint32_t*>(&af[b % (APF + 1)][ks]), d + ks * 128, (b | ks) != 0);
                wg_commit();
                if (b > 0) {
                    wg_wait<1>();
                    if (lane < 2) mbar_arrive(sb + BAR_EMPTY + 8 * prev_st);
                }
                prev_st = rg.st;
                rg.next();
                if (b + APF < 18) {
                    mbar_wait(sb + BAR_AREADY + 8 * (b + APF), 0);
#pragma unroll
                    for (int ks = 0; ks < 4; ks++)
                        af[(b + APF) % (APF + 1)][ks] = __ldcg(a2r + ((b + APF) * 4 + ks) * 256);
                }
            }
            const int row0 = m2 * 128 + wg * 64 + w * 16 + g;
            const int col0 = j2 * 128 + rank * 64 + 2 * t;
            uint32_t xr[16];
#pragma unroll
            for (int nb = 0; nb < 8; nb++) {
                xr[2 * nb] = __ldg((const uint32_t*)(xg + (size_t)row0 * 512 + col0 + nb * 8));
                xr[2 * nb + 1] = __ldg((const uint32_t*)(xg + (size_t)(row0 + 8) * 512 + col0 + nb * 8));
            }
            wg_wait<0>();
            acc_fence(acc);
            TS(wg, 18);
            uint32_t rdst, rbar;
            asm volatile("mapa.shared::cluster.u32 %0, %1, %2;" : "=r"(rdst) : "r"(sb + OFF_STG + tid * 16), "r"(rank ^ 1));
            asm volatile("mapa.shared::cluster.u32 %0, %1, %2;" : "=r"(rbar) : "r"(sb + BAR_XCHG), "r"(rank ^ 1));
            float keep[32];
#pragma unroll
            for (int i = 0; i < 8; i++) {
                float s0 = rank ? acc[4 * i] : acc[32 + 4 * i], s1 = rank ? acc[4 * i + 1] : acc[33 + 4 * i];
                float s2 = rank ? acc[4 * i + 2] : acc[34 + 4 * i], s3 = rank ? acc[4 * i + 3] : acc[35 + 4 * i];
                asm volatile("st.async.shared::cluster.mbarrier::complete_tx::bytes.v4.f32 [%0], {%1,%2,%3,%4}, [%5];"
                             ::"r"(rdst + i * 4096), "f"(s0), "f"(s1), "f"(s2), "f"(s3), "r"(rbar) : "memory");
#pragma unroll
                for (int e = 0; e < 4; e++) keep[4 * i + e] = rank ? acc[32 + 4 * i + e] : acc[4 * i + e];
            }
            mbar_wait(sb + BAR_XCHG, 0);
            TS(wg, 19);
            const float4* rx = (const float4*)(smem + OFF_STG) + tid;
#pragma unroll
            for (int nb = 0; nb < 8; nb++) {
                const float4 p = rx[nb * 256];
                const uint32_t o0 = pack_bf16(keep[4 * nb] + p.x + bf_lo(xr[2 * nb]), keep[4 * nb + 1] + p.y + bf_hi(xr[2 * nb]));
                const uint32_t o1 = pack_bf16(keep[4 * nb + 2] + p.z + bf_lo(xr[2 * nb + 1]), keep[4 * nb + 3] + p.w + bf_hi(xr[2 * nb + 1]));
                *(uint32_t*)(outg + (size_t)row0 * 512 + col0 + nb * 8) = o0;
                *(uint32_t*)(outg + (size_t)(row0 + 8) * 512 + col0 + nb * 8) = o1;
            }
        }
        TS(wg, 20);
        asm volatile("barrier.cluster.arrive.relaxed.aligned;\nbarrier.cluster.wait.aligned;" ::: "memory");
        TS(wg, 21);
    }
}

typedef CUresult (*EncodeFn)(CUtensorMap*, CUtensorMapDataType, cuuint32_t, void*, const cuuint64_t*, const cuuint64_t*,
                             const cuuint32_t*, const cuuint32_t*, CUtensorMapInterleave, CUtensorMapSwizzle,
                             CUtensorMapL2promotion, CUtensorMapFloatOOBfill);

void make_map(EncodeFn enc, CUtensorMap* tm, const void* ptr, int rows, int cols, int box_rows, int box_cols,
              CUtensorMapSwizzle swz) {
    cuuint64_t dims[2] = {(cuuint64_t)cols, (cuuint64_t)rows};
    cuuint64_t strides[1] = {(cuuint64_t)cols * 2};
    cuuint32_t box[2] = {(cuuint32_t)box_cols, (cuuint32_t)box_rows};
    cuuint32_t es[2] = {1, 1};
    enc(tm, CU_TENSOR_MAP_DATA_TYPE_BFLOAT16, 2, const_cast<void*>(ptr), dims, strides, box, es,
        CU_TENSOR_MAP_INTERLEAVE_NONE, swz, CU_TENSOR_MAP_L2_PROMOTION_L2_256B, CU_TENSOR_MAP_FLOAT_OOB_FILL_NONE);
}

}

extern "C" void kernel_launch(void* const* d_in, const int* in_sizes, int n_in, void* d_out, int out_size) {
    (void)in_sizes; (void)n_in; (void)out_size;
    static EncodeFn enc = nullptr;
    if (!enc) {
        void* fn = nullptr;
        cudaDriverEntryPointQueryResult qr;
        cudaGetDriverEntryPoint("cuTensorMapEncodeTiled", &fn, cudaEnableDefault, &qr);
        enc = (EncodeFn)fn;
        cudaFuncSetAttribute(fused_kernel, cudaFuncAttributeMaxDynamicSharedMemorySize, SMEM_BYTES);
    }
    const void* x = d_in[0];
    const void* wqkv = d_in[1];
    const void* wo = d_in[2];
    const void* w1 = d_in[4];
    const void* w3 = d_in[5];
    const void* w2 = d_in[6];
    CUtensorMap tx, tqkv, t1, t3, t1h, t3h, t2, t2h, two;
    make_map(enc, &tx, x, 2048, 512, 128, 64, CU_TENSOR_MAP_SWIZZLE_128B);
    make_map(enc, &tqkv, wqkv, 512, 1536, 64, 64, CU_TENSOR_MAP_SWIZZLE_128B);
    make_map(enc, &t1, w1, 512, 1792, 64, 64, CU_TENSOR_MAP_SWIZZLE_128B);
    make_map(enc, &t3, w3, 512, 1792, 64, 64, CU_TENSOR_MAP_SWIZZLE_128B);
    make_map(enc, &t1h, w1, 512, 1792, 64, 32, CU_TENSOR_MAP_SWIZZLE_64B);
    make_map(enc, &t3h, w3, 512, 1792, 64, 32, CU_TENSOR_MAP_SWIZZLE_64B);
    make_map(enc, &t2, w2, 1792, 512, 64, 64, CU_TENSOR_MAP_SWIZZLE_128B);
    make_map(enc, &t2h, w2, 1792, 512, 32, 64, CU_TENSOR_MAP_SWIZZLE_128B);
    make_map(enc, &two, wo, 512, 512, 64, 64, CU_TENSOR_MAP_SWIZZLE_128B);
    fused_kernel<<<128, 384, SMEM_BYTES>>>(tx, tqkv, t1, t3, t1h, t3h, t2, t2h, two, (const __nv_bfloat16*)x,
                                           (__nv_bfloat16*)d_out);
}
```

```cpp
#include <cuda_runtime.h>
#include <cuda_bf16.h>
#include <cuda.h>
#include <stdint.h>

namespace {

constexpr int NST = 13;
constexpr int STAGE_BYTES = 16384;
constexpr int XST0 = 5;
constexpr int SCR0 = 8;
constexpr int OFF_MISC = NST * STAGE_BYTES;
constexpr int OFF_KVRAW = OFF_MISC;
constexpr int OFF_KVFRAG = OFF_MISC + 8704;
constexpr int OFF_ONES = OFF_MISC + 11776;
constexpr int OFF_BARS = OFF_MISC + 12032;
constexpr int OFF_COMB = OFF_MISC + 12544;
constexpr int BAR_FULL = OFF_BARS;
constexpr int BAR_EMPTY = BAR_FULL + 8 * NST;
constexpr int BAR_XFULL = BAR_EMPTY + 8 * NST;
constexpr int BAR_KVREADY = BAR_XFULL + 64;
constexpr int BAR_XCHG = BAR_KVREADY + 8;
constexpr int BAR_AREADY = BAR_XCHG + 8;
constexpr int BAR_EPOCH = BAR_AREADY + 8 * 18;
constexpr int BAR_XRDY = BAR_EPOCH + 8;
constexpr int OFF_EPOCH = BAR_XRDY + 8;
constexpr int SMEM_BYTES = OFF_MISC + 12544 + 6144;

constexpr int APF = 5;
constexpr unsigned SPIN_LIMIT = 1u << 24;

__device__ uint4 g_A2[16 * 2 * 18 * 4 * 256];
__device__ uint4 g_kvp[8 * 16 * 544];
__device__ uint4 g_kvs[8 * 544];
__device__ unsigned g_a2flag[16 * 8 * 4 * 2];
__device__ unsigned g_epoch;
__device__ unsigned g_ticket;

#define TS(role, i)
#define TSW(role, i)

__device__ __forceinline__ uint32_t smem_u32(const void* p) { return (uint32_t)__cvta_generic_to_shared(p); }
__device__ __forceinline__ void mbar_init(uint32_t bar, uint32_t cnt) {
    asm volatile("mbarrier.init.shared::cta.b64 [%0], %1;" ::"r"(bar), "r"(cnt) : "memory");
}
__device__ __forceinline__ void mbar_expect_tx(uint32_t bar, uint32_t bytes) {
    asm volatile("mbarrier.arrive.expect_tx.shared::cta.b64 _, [%0], %1;" ::"r"(bar), "r"(bytes) : "memory");
}
__device__ __forceinline__ void mbar_arrive(uint32_t bar) {
    asm volatile("mbarrier.arrive.shared::cta.b64 _, [%0];" ::"r"(bar) : "memory");
}
__device__ __forceinline__ void mbar_arrive_cta(uint32_t bar, uint32_t cta) {
    asm volatile(
        "{\n.reg .b32 ra;\nmapa.shared::cluster.u32 ra, %0, %1;\n"
        "mbarrier.arrive.shared::cluster.b64 _, [ra];\n}" ::"r"(bar), "r"(cta) : "memory");
}
__device__ __forceinline__ void mbar_wait(uint32_t bar, uint32_t parity) {
    asm volatile(
        "{\n.reg .pred p, q;\n.reg .u32 n;\nmov.u32 n, 0;\n"
        "WAIT_%=:\n"
        "mbarrier.try_wait.parity.shared::cta.b64 p, [%0], %1;\n"
        "@p bra.uni DONE_%=;\n"
        "add.u32 n, n, 1;\n"
        "setp.gt.u32 q, n, %2;\n"
        "@q trap;\n"
        "bra.uni WAIT_%=;\n"
        "DONE_%=:\n}"
        ::"r"(bar), "r"(parity), "n"(SPIN_LIMIT) : "memory");
}
__device__ __forceinline__ unsigned ld_acquire(const unsigned* p) {
    unsigned v;
    asm volatile("ld.acquire.gpu.global.u32 %0, [%1];" : "=r"(v) : "l"(p) : "memory");
    return v;
}
__device__ __forceinline__ void st_release(unsigned* p, unsigned v) {
    asm volatile("st.release.gpu.global.u32 [%0], %1;" ::"l"(p), "r"(v) : "memory");
}
__device__ __forceinline__ unsigned read_epoch() {
    return __shfl_sync(0xffffffffu, *(volatile unsigned*)&g_epoch, 0) + 1;
}
__device__ __forceinline__ void tma_load(uint32_t dst, const CUtensorMap* tm, uint32_t bar, int x, int y) {
    asm volatile(
        "cp.async.bulk.tensor.2d.shared::cluster.global.mbarrier::complete_tx::bytes [%0], [%1, {%3, %4}], [%2];"
        ::"r"(dst), "l"(tm), "r"(bar), "r"(x), "r"(y) : "memory");
}
__device__ __forceinline__ void tma_load_mc(uint32_t dst, const CUtensorMap* tm, uint32_t bar, int x, int y) {
    asm volatile(
        "cp.async.bulk.tensor.2d.shared::cluster.global.mbarrier::complete_tx::bytes.multicast::cluster "
        "[%0], [%1, {%3, %4}], [%2], %5;"
        ::"r"(dst), "l"(tm), "r"(bar), "r"(x), "r"(y), "h"((uint16_t)3) : "memory");
}
__device__ __forceinline__ void prefetch_tm(const CUtensorMap* tm) {
    asm volatile("prefetch.tensormap [%0];" ::"l"(tm) : "memory");
}
__device__ __forceinline__ void l2_prefetch(const void* p, uint32_t bytes) {
    asm volatile("cp.async.bulk.prefetch.L2.global [%0], %1;" ::"l"(p), "r"(bytes) : "memory");
}
__device__ __forceinline__ void bar_sync(int id, int n) { asm volatile("bar.sync %0, %1;" ::"r"(id), "r"(n) : "memory"); }
__device__ __forceinline__ void bar_arrive(int id, int n) { asm volatile("bar.arrive %0, %1;" ::"r"(id), "r"(n) : "memory"); }
__device__ __forceinline__ void wg_fence() { asm volatile("wgmma.fence.sync.aligned;" ::: "memory"); }
__device__ __forceinline__ void wg_commit() { asm volatile("wgmma.commit_group.sync.aligned;" ::: "memory"); }
template <int N>
__device__ __forceinline__ void wg_wait() { asm volatile("wgmma.wait_group.sync.aligned %0;" ::"n"(N) : "memory"); }

__device__ __forceinline__ uint64_t make_desc(uint32_t addr, uint32_t lbo, uint32_t sbo, uint64_t swz) {
    return (uint64_t)((addr & 0x3FFFF) >> 4) | ((uint64_t)(lbo >> 4) << 16) | ((uint64_t)(sbo >> 4) << 32) | (swz << 62);
}

#define ACC8(a, o) "+f"(a[o]), "+f"(a[o + 1]), "+f"(a[o + 2]), "+f"(a[o + 3]), "+f"(a[o + 4]), "+f"(a[o + 5]), "+f"(a[o + 6]), "+f"(a[o + 7])
__device__ __forceinline__ void wgmma_n128_rs(float (&d)[64], const uint32_t* a, uint64_t db, int scale_d) {
    asm volatile(
        "{\n.reg .pred p;\nsetp.ne.b32 p, %69, 0;\n"
        "wgmma.mma_async.sync.aligned.m64n128k16.f32.bf16.bf16 "
        "{%0,%1,%2,%3,%4,%5,%6,%7,%8,%9,%10,%11,%12,%13,%14,%15,%16,%17,%18,%19,%20,%21,%22,%23,%24,%25,%26,%27,%28,%29,%30,%31,"
        "%32,%33,%34,%35,%36,%37,%38,%39,%40,%41,%42,%43,%44,%45,%46,%47,%48,%49,%50,%51,%52,%53,%54,%55,%56,%57,%58,%59,%60,%61,%62,%63},"
        "{%64,%65,%66,%67}, %68, p, 1, 1, 1;\n}"
        : ACC8(d, 0), ACC8(d, 8), ACC8(d, 16), ACC8(d, 24), ACC8(d, 32), ACC8(d, 40), ACC8(d, 48), ACC8(d, 56)
        : "r"(a[0]), "r"(a[1]), "r"(a[2]), "r"(a[3]), "l"(db), "r"(scale_d));
}
__device__ __forceinline__ void wgmma_n64_rs(float (&d)[32], const uint32_t* a, uint64_t db, int scale_d) {
    asm volatile(
        "{\n.reg .pred p;\nsetp.ne.b32 p, %37, 0;\n"
        "wgmma.mma_async.sync.aligned.m64n64k16.f32.bf16.bf16 "
        "{%0,%1,%2,%3,%4,%5,%6,%7,%8,%9,%10,%11,%12,%13,%14,%15,%16,%17,%18,%19,%20,%21,%22,%23,%24,%25,%26,%27,%28,%29,%30,%31},"
        "{%32,%33,%34,%35}, %36, p, 1, 1, 1;\n}"
        : ACC8(d, 0), ACC8(d, 8), ACC8(d, 16), ACC8(d, 24)
        : "r"(a[0]), "r"(a[1]), "r"(a[2]), "r"(a[3]), "l"(db), "r"(scale_d));
}
__device__ __forceinline__ void wgmma_n64_ss_tt(float (&d)[32], uint64_t da, uint64_t db, int scale_d) {
    asm volatile(
        "{\n.reg .pred p;\nsetp.ne.b32 p, %34, 0;\n"
        "wgmma.mma_async.sync.aligned.m64n64k16.f32.bf16.bf16 "
        "{%0,%1,%2,%3,%4,%5,%6,%7,%8,%9,%10,%11,%12,%13,%14,%15,%16,%17,%18,%19,%20,%21,%22,%23,%24,%25,%26,%27,%28,%29,%30,%31},"
        "%32, %33, p, 1, 1, 1, 1;\n}"
        : ACC8(d, 0), ACC8(d, 8), ACC8(d, 16), ACC8(d, 24)
        : "l"(da), "l"(db), "r"(scale_d));
}
__device__ __forceinline__ void wgmma_n8_ss_tn(float (&d)[4], uint64_t da, uint64_t db, int scale_d) {
    asm volatile(
        "{\n.reg .pred p;\nsetp.ne.b32 p, %6, 0;\n"
        "wgmma.mma_async.sync.aligned.m64n8k16.f32.bf16.bf16 {%0,%1,%2,%3}, %4, %5, p, 1, 1, 1, 0;\n}"
        : "+f"(d[0]), "+f"(d[1]), "+f"(d[2]), "+f"(d[3])
        : "l"(da), "l"(db), "r"(scale_d));
}
template <int N>
__device__ __forceinline__ void acc_fence(float (&d)[N]) {
#pragma unroll
    for (int i = 0; i < N; i++) asm volatile("" : "+f"(d[i])::"memory");
}
__device__ __forceinline__ void mma16816(float (&c)[4], const uint32_t* a, uint32_t b0, uint32_t b1) {
    asm volatile(
        "mma.sync.aligned.m16n8k16.row.col.f32.bf16.bf16.f32 {%0,%1,%2,%3}, {%4,%5,%6,%7}, {%8,%9}, {%0,%1,%2,%3};"
        : "+f"(c[0]), "+f"(c[1]), "+f"(c[2]), "+f"(c[3])
        : "r"(a[0]), "r"(a[1]), "r"(a[2]), "r"(a[3]), "r"(b0), "r"(b1));
}
__device__ __forceinline__ uint32_t pack_bf16(float lo, float hi) {
    uint32_t r;
    asm("cvt.rn.bf16x2.f32 %0, %1, %2;" : "=r"(r) : "f"(hi), "f"(lo));
    return r;
}
__device__ __forceinline__ float bf_lo(uint32_t v) { return __uint_as_float(v << 16); }
__device__ __forceinline__ float bf_hi(uint32_t v) { return __uint_as_float(v & 0xffff0000u); }
__device__ __forceinline__ float bf16_round(float v) { return __bfloat162float(__float2bfloat16_rn(v)); }
__device__ __forceinline__ float sqrt_fast(float v) {
    float r;
    asm("sqrt.approx.ftz.f32 %0, %1;" : "=f"(r) : "f"(v));
    return r;
}
__device__ __forceinline__ float rcp_fast(float v) {
    float r;
    asm("rcp.approx.ftz.f32 %0, %1;" : "=f"(r) : "f"(v));
    return r;
}
__device__ __forceinline__ float ex2_fast(float v) {
    float r;
    asm("ex2.approx.ftz.f32 %0, %1;" : "=f"(r) : "f"(v));
    return r;
}
struct RowScale { float rho, rl, rho2; };
__device__ __forceinline__ float phi_f(float a, const RowScale& r) {
    return fmaf(fmaxf(a, 0.f), r.rho, ex2_fast(fminf(a, 0.f) * r.rl) + 1e-6f);
}
__device__ __forceinline__ float swiglu_f(float ga, float ua, const RowScale& r) {
    return (ga * ua) * r.rho2 * rcp_fast(1.f + ex2_fast(-ga * r.rl));
}
__device__ __forceinline__ uint4 swiglu8(const float* gp, const float* up, const RowScale& r0, const RowScale& r1) {
    uint4 v;
    v.x = pack_bf16(swiglu_f(gp[0], up[0], r0), swiglu_f(gp[1], up[1], r0));
    v.y = pack_bf16(swiglu_f(gp[2], up[2], r1), swiglu_f(gp[3], up[3], r1));
    v.z = pack_bf16(swiglu_f(gp[4], up[4], r0), swiglu_f(gp[5], up[5], r0));
    v.w = pack_bf16(swiglu_f(gp[6], up[6], r1), swiglu_f(gp[7], up[7], r1));
    return v;
}
__device__ __forceinline__ void cp_async16(uint32_t dst, const void* src) {
    asm volatile("cp.async.cg.shared.global [%0], [%1], 16;" ::"r"(dst), "l"(src) : "memory");
}

struct Ring {
    int st;
    uint32_t ph;
    __device__ __forceinline__ void next() {
        if (++st == NST) { st = 0; ph ^= 1; }
    }
};

__device__ __forceinline__ void sumsq16(uint32_t* a, float (&q)[4]) {
#pragma unroll
    for (int i = 0; i < 16; i++) asm volatile("" : "+r"(a[i]));
#pragma unroll
    for (int i = 0; i < 16; i += 2) {
        const float a0 = bf_lo(a[i]), a1 = bf_hi(a[i]), b0 = bf_lo(a[i + 1]), b1 = bf_hi(a[i + 1]);
        q[0] = fmaf(a0, a0, q[0]); q[1] = fmaf(a1, a1, q[1]);
        q[2] = fmaf(b0, b0, q[2]); q[3] = fmaf(b1, b1, q[3]);
    }
}
template <bool SUMSQ>
__device__ __forceinline__ void mainloop128(float (&acc)[64], uint32_t (&xa)[128], Ring& rg, uint32_t sb,
                                            uint64_t desc128, int lane, int wg, float (&q)[4]) {
    int prev_st = 0;
    bar_sync(7 + wg, 256);
#pragma unroll
    for (int kb = 0; kb < 8; kb++) {
        mbar_wait(sb + BAR_FULL + 8 * rg.st, rg.ph);
        wg_fence();
        const uint64_t d = desc128 + (uint64_t)(rg.st * (STAGE_BYTES >> 4));
#pragma unroll
        for (int ks = 0; ks < 4; ks++) wgmma_n128_rs(acc, &xa[(kb * 4 + ks) * 4], d + ks * 128, (kb | ks) != 0);
        wg_commit();
        if (kb == 7) bar_arrive(8 - wg, 256);
        if (kb > 0) {
            wg_wait<1>();
            if (lane < 2) mbar_arrive_cta(sb + BAR_EMPTY + 8 * prev_st, lane);
            if (SUMSQ) sumsq16(&xa[(kb - 1) * 16], q);
        }
        prev_st = rg.st;
        rg.next();
    }
    wg_wait<0>();
    acc_fence(acc);
    if (lane < 2) mbar_arrive_cta(sb + BAR_EMPTY + 8 * prev_st, lane);
    if (SUMSQ) sumsq16(&xa[7 * 16], q);
}
__device__ __forceinline__ void mainloop64x2(float (&a0)[32], float (&a1)[32], const uint32_t (&xa)[128], Ring& rg,
                                             uint32_t sb, uint64_t desc128, uint64_t desc64, int lane, int wg) {
    int prev_st = 0;
    bar_sync(7 + wg, 256);
#pragma unroll
    for (int kb = 0; kb < 8; kb++) {
        mbar_wait(sb + BAR_FULL + 8 * rg.st, rg.ph);
        wg_fence();
        const uint64_t d = desc128 + (uint64_t)(rg.st * (STAGE_BYTES >> 4));
        const uint64_t d2 = desc64 + (uint64_t)(rg.st * (STAGE_BYTES >> 4));
#pragma unroll
        for (int ks = 0; ks < 4; ks++) {
            wgmma_n64_rs(a0, &xa[(kb * 4 + ks) * 4], d + ks * 128, (kb | ks) != 0);
            wgmma_n64_rs(a1, &xa[(kb * 4 + ks) * 4], d2 + ks * 64, (kb | ks) != 0);
        }
        wg_commit();
        if (kb == 7 && wg == 0) bar_arrive(8, 256);
        if (kb > 0) {
            wg_wait<1>();
            if (lane < 2) mbar_arrive_cta(sb + BAR_EMPTY + 8 * prev_st, lane);
        }
        prev_st = rg.st;
        rg.next();
    }
    wg_wait<0>();
    acc_fence(a0);
    acc_fence(a1);
    if (lane < 2) mbar_arrive_cta(sb + BAR_EMPTY + 8 * prev_st, lane);
}

__global__ void __cluster_dims__(2, 1, 1) __launch_bounds__(384, 1)
fused_kernel(const __grid_constant__ CUtensorMap tm_x, const __grid_constant__ CUtensorMap tm_qkv,
             const __grid_constant__ CUtensorMap tm_w1, const __grid_constant__ CUtensorMap tm_w3,
             const __grid_constant__ CUtensorMap tm_w1h, const __grid_constant__ CUtensorMap tm_w3h,
             const __grid_constant__ CUtensorMap tm_w2, const __grid_constant__ CUtensorMap tm_w2h,
             const __grid_constant__ CUtensorMap tm_wo, const __nv_bfloat16* __restrict__ xg,
             __nv_bfloat16* __restrict__ outg, const char* __restrict__ p_qkv, const char* __restrict__ p_w1,
             const char* __restrict__ p_w3, const char* __restrict__ p_w2, const char* __restrict__ p_wo) {
    extern __shared__ __align__(1024) uint8_t smem[];
    const uint32_t sb = smem_u32(smem);
    const int tid = threadIdx.x;
    const int warp = tid >> 5, lane = tid & 31;
    const int rank = blockIdx.x & 1;
    const int pair = blockIdx.x >> 1;
    const int c = pair & 7;
    const int m = (pair >> 3) * 2 + rank;
    const int m2 = (pair >> 3) * 2 + (c & 1);
    const int j2 = c >> 1;

    TS(tid >> 7, 0);
    if (tid == 256) {
#pragma unroll
        for (int i = 0; i < 8; i++) mbar_init(sb + BAR_XFULL + 8 * i, 1);
        asm volatile("fence.proxy.async.shared::cta;" ::: "memory");
#pragma unroll
        for (int kb = 0; kb < 8; kb++) {
            mbar_expect_tx(sb + BAR_XFULL + 8 * kb, 16384);
            tma_load(sb + (XST0 + kb) * STAGE_BYTES, &tm_x, sb + BAR_XFULL + 8 * kb, kb * 64, m * 128);
        }
        TS(2, 21);
    } else if (tid == 0) {
#pragma unroll
        for (int i = 0; i < NST; i++) mbar_init(sb + BAR_FULL + 8 * i, 1);
        asm volatile("fence.mbarrier_init.release.cluster;" ::: "memory");
    } else if (tid == 32) {
#pragma unroll
        for (int i = 0; i < NST; i++) mbar_init(sb + BAR_EMPTY + 8 * i, 16);
        asm volatile("fence.mbarrier_init.release.cluster;" ::: "memory");
    } else if (tid == 64) {
#pragma unroll
        for (int i = 0; i < 10; i++) mbar_init(sb + BAR_KVREADY + 8 * i, 1);
        mbar_expect_tx(sb + BAR_XCHG, 32768);
        asm volatile("fence.mbarrier_init.release.cluster;" ::: "memory");
    } else if (tid == 96) {
#pragma unroll
        for (int i = 10; i < 22; i++) mbar_init(sb + BAR_KVREADY + 8 * i, 1);
        asm volatile("fence.mbarrier_init.release.cluster;" ::: "memory");
    } else if (tid == 288) {
        prefetch_tm(&tm_qkv);
        prefetch_tm(rank ? &tm_w3 : &tm_w1);
        prefetch_tm(&tm_w1h);
        prefetch_tm(&tm_w3h);
        prefetch_tm(&tm_w2);
        prefetch_tm(&tm_w2h);
        prefetch_tm(&tm_wo);
    } else if (tid >= 320) {
        ((uint32_t*)(smem + OFF_ONES))[tid - 320] = 0x3F803F80u;
        asm volatile("fence.proxy.async.shared::cta;" ::: "memory");
    }
    __syncthreads();
    TS(tid >> 7, 22);
    asm volatile("barrier.cluster.arrive.relaxed.aligned;\nbarrier.cluster.wait.acquire.aligned;" ::: "memory");

    if (warp >= 8) {
        asm volatile("setmaxnreg.dec.sync.aligned.u32 40;");
        if (warp == 8) {
            if (lane == 0) {
                int st = 0;
                uint32_t lap = 0;
                for (int it = 0; it < 40; it++) {
                    const int tile = it >> 3, kb = it & 7;
                    const uint32_t full = sb + BAR_FULL + 8 * st;
                    mbar_wait(sb + BAR_EMPTY + 8 * st, (st >= XST0) ? (lap & 1) : ((lap & 1) ^ 1));
                    mbar_expect_tx(full, STAGE_BYTES);
                    const uint32_t dst = sb + st * STAGE_BYTES;
                    if (tile == 0) {
                        tma_load_mc(dst + rank * 8192, &tm_qkv, full, 512 + 512 * rank + 64 * c, kb * 64);
                    } else if (tile < 4) {
                        tma_load_mc(dst + rank * 8192, rank ? &tm_w3 : &tm_w1, full, 224 * c + 64 * (tile - 1), kb * 64);
                    } else if (rank == 0) {
                        tma_load_mc(dst, &tm_qkv, full, 64 * c, kb * 64);
                    } else {
                        tma_load_mc(dst + 8192, &tm_w1h, full, 224 * c + 192, kb * 64);
                        tma_load_mc(dst + 12288, &tm_w3h, full, 224 * c + 192, kb * 64);
                    }
                    if (++st == NST) { st = 0; lap++; }
                    if (it == 7) {
                        mbar_wait(sb + BAR_EMPTY + 8 * SCR0, 0);
                        mbar_arrive(sb + BAR_FULL + 8 * SCR0);
                        mbar_wait(sb + BAR_EMPTY + 8 * (SCR0 + 1), 0);
                        mbar_arrive(sb + BAR_FULL + 8 * (SCR0 + 1));
                        st += 2;
                    }
                }
                TS(2, 1);
                for (int b = 0; b < 18; b++) {
                    const uint32_t full = sb + BAR_FULL + 8 * st;
                    const uint32_t dst = sb + st * STAGE_BYTES;
                    mbar_wait(sb + BAR_EMPTY + 8 * st, (st >= XST0) ? (lap & 1) : ((lap & 1) ^ 1));
                    mbar_expect_tx(full, STAGE_BYTES);
                    if (b < 12) {
                        const int row = 224 * (4 * rank + (b & 3)) + 64 * (b >> 2);
                        tma_load(dst, &tm_w2, full, 128 * j2, row);
                        tma_load(dst + 8192, &tm_w2, full, 128 * j2 + 64, row);
                    } else if (b < 14) {
                        const int row = 224 * (4 * rank + 2 * (b - 12)) + 192;
                        tma_load(dst, &tm_w2h, full, 128 * j2, row);
                        tma_load(dst + 4096, &tm_w2h, full, 128 * j2, row + 224);
                        tma_load(dst + 8192, &tm_w2h, full, 128 * j2 + 64, row);
                        tma_load(dst + 12288, &tm_w2h, full, 128 * j2 + 64, row + 224);
                    } else {
                        const int row = 64 * (4 * rank + (b - 14));
                        tma_load(dst, &tm_wo, full, 128 * j2, row);
                        tma_load(dst + 8192, &tm_wo, full, 128 * j2 + 64, row);
                    }
                    TS(2, 2 + b);
                    if (++st == NST) { st = 0; lap++; }
                }
                mbar_wait(sb + BAR_EMPTY + 8 * SCR0, lap & 1);
                mbar_wait(sb + BAR_EMPTY + 8 * (SCR0 + 1), lap & 1);
                mbar_arrive_cta(sb + BAR_XRDY, rank ^ 1);
            }
        } else if (warp < 11) {
            const int wg = warp - 9;
            const unsigned epoch = read_epoch();
            bar_arrive(9, 96);
            for (int t = 1; t < 5; t++) {
                bar_sync(3 + wg * 2 + (t & 1), 160);
                if (lane == 0) st_release(&g_a2flag[((m * 8 + c) * 4 + (t - 1)) * 2 + wg], epoch);
                TSW(3, 2 * t + wg);
            }
        } else {
            const unsigned epoch = read_epoch();
            bar_sync(9, 96);
            if (lane == 0) {
                const unsigned tk = atomicInc(&g_ticket, 127u);
                if (tk == 127u) *(volatile unsigned*)&g_epoch = epoch;
            }
            if (lane == 0) *(volatile unsigned*)(smem + OFF_EPOCH) = epoch;
            __syncwarp();
            if (lane == 0) mbar_arrive(sb + BAR_EPOCH);
            const uint4* raw = (const uint4*)(smem + OFF_KVRAW);
            bar_sync(11, 160);
#pragma unroll 1
            for (int level = 0; level < 2; level++) {
                const uint4* base = level ? g_kvs + c * 544 : g_kvp + (size_t)c * 16 * 544 + 34 * m;
                unsigned n = 0;
                while (true) {
                    int j = lane, off = lane;
#pragma unroll
                    for (int k = 0; k < 17; k++) {
                        cp_async16(sb + OFF_KVRAW + (lane + 32 * k) * 16, base + off);
                        j += 32; off += 32;
                        if (level == 0 && j >= 34) { j -= 34; off += 544 - 34; }
                    }
                    asm volatile("cp.async.wait_all;" ::: "memory");
                    unsigned bad = 0;
#pragma unroll 4
                    for (int k = 0; k < 17; k++) {
                        const uint4 v = raw[lane + 32 * k];
                        bad |= (v.y ^ epoch) | (v.w ^ epoch);
                    }
                    if (__all_sync(0xffffffffu, bad == 0)) break;
                    __nanosleep(50);
                    if (++n > SPIN_LIMIT) asm volatile("trap;");
                }
                TSW(4, 2 * level);
                if (level == 0) {
                    for (int j = lane; j < 34; j += 32) {
                        float s0 = 0.f, s1 = 0.f;
#pragma unroll 4
                        for (int pp = 0; pp < 16; pp++) {
                            const uint4 v = raw[pp * 34 + j];
                            s0 += __uint_as_float(v.x);
                            s1 += __uint_as_float(v.z);
                        }
                        g_kvs[c * 544 + 34 * m + j] = make_uint4(__float_as_uint(s0), epoch, __float_as_uint(s1), epoch);
                    }
                    __syncwarp();
                    TSW(4, 1);
                }
            }
            const float* ks = (const float*)(smem + OFF_KVRAW);
            uint2* kf = (uint2*)(smem + OFF_KVFRAG);
            const int g = lane >> 2, t = lane & 3;
#pragma unroll 2
            for (int hh = 0; hh < 4; hh++) {
                const float* k = ks + hh * 544;
#pragma unroll
                for (int b = 0; b < 2; b++) {
                    uint2 v;
                    v.x = pack_bf16(k[2 * ((2 * t) * 16 + 8 * b + g)], k[2 * ((2 * t + 1) * 16 + 8 * b + g)]);
                    v.y = pack_bf16(k[2 * ((2 * t + 8) * 16 + 8 * b + g)], k[2 * ((2 * t + 9) * 16 + 8 * b + g)]);
                    kf[(hh * 3 + b) * 32 + lane] = v;
                }
                uint2 z;
                z.x = pack_bf16(k[2 * (256 + 2 * t)], k[2 * (256 + 2 * t + 1)]);
                z.y = pack_bf16(k[2 * (256 + 2 * t + 8)], k[2 * (256 + 2 * t + 9)]);
                kf[(hh * 3 + 2) * 32 + lane] = z;
            }
            __syncwarp();
            if (lane == 0) mbar_arrive(sb + BAR_KVREADY);
            TSW(4, 4);
            const unsigned* fl = g_a2flag + (m2 * 8 + rank * 4) * 8 + lane;
            unsigned ready = 0;
            for (int b = 0; b < 18; b++) {
                const unsigned need = (b < 12) ? (3u << ((b & 3) * 8 + (b >> 2) * 2)) : (b < 14) ? (0xC0C0u << ((b - 12) * 16)) : 0u;
                unsigned n = 0;
                while ((ready & need) != need) {
                    ready = __ballot_sync(0xffffffffu, ld_acquire(fl) == epoch);
                    if (++n > SPIN_LIMIT) asm volatile("trap;");
                }
                if (lane == 0) mbar_arrive(sb + BAR_AREADY + 8 * b);
                TSW(5, b);
            }
        }
    } else {
        asm volatile("setmaxnreg.inc.sync.aligned.u32 232;");
        const int wg = warp >> 2, w = warp & 3;
        const int g = lane >> 2, t = lane & 3;
        float acc[64];
        uint32_t xa[128];
        float rho0, rho1;
        RowScale r0, r1;

        TS(wg, 1);
        {
            const int row = wg * 64 + w * 16 + (lane & 7) + ((lane >> 3) & 1) * 8;
            const uint32_t rbase = sb + XST0 * STAGE_BYTES + row * 128;
            const int hi = lane >> 4, r7 = lane & 7;
            float sm[4][4];
#pragma unroll
            for (int i = 0; i < 16; i++) sm[i >> 2][i & 3] = 0.f;
            if (wg == 1) bar_arrive(7, 256);
#pragma unroll
            for (int kb = 0; kb < 8; kb++) {
                mbar_wait(sb + BAR_XFULL + 8 * kb, 0);
#pragma unroll
                for (int ks = 0; ks < 4; ks++) {
                    uint32_t* a = &xa[(kb * 4 + ks) * 4];
                    const uint32_t addr = rbase + kb * STAGE_BYTES + (((2 * ks + hi) ^ r7) << 4);
                    asm volatile("ldmatrix.sync.aligned.m8n8.x4.shared.b16 {%0,%1,%2,%3}, [%4];"
                                 : "=r"(a[0]), "=r"(a[1]), "=r"(a[2]), "=r"(a[3]) : "r"(addr) : "memory");
                    mma16816(sm[ks], a, 0x3F803F80u, 0x3F803F80u);
                }
            }
            TS(wg, 2);
            const float mean0 = ((sm[0][0] + sm[1][0]) + (sm[2][0] + sm[3][0])) * (1.f / 512.f);
            const float mean1 = ((sm[0][2] + sm[1][2]) + (sm[2][2] + sm[3][2])) * (1.f / 512.f);
            __syncwarp();
            if (lane < 16) mbar_arrive_cta(sb + BAR_EMPTY + 8 * (XST0 + (lane >> 1)), lane & 1);
            const __nv_bfloat162 mb0 = __float2bfloat162_rn(mean0), mb1 = __float2bfloat162_rn(mean1);
#pragma unroll
            for (int i = 0; i < 128; i++) {
                __nv_bfloat162 v = *reinterpret_cast<__nv_bfloat162*>(&xa[i]);
                v = __hsub2(v, (i & 1) ? mb1 : mb0);
                xa[i] = *reinterpret_cast<uint32_t*>(&v);
            }
            rho0 = mean0 - __low2float(mb0);
            rho1 = mean1 - __low2float(mb1);
        }

        TS(wg, 3);
        Ring rg = {0, 0};
        const uint64_t desc128 = make_desc(sb, 8192, 1024, 1);
        const uint64_t desc64 = make_desc(sb + 8192, 4096, 512, 2);
        uint4* a2w = g_A2 + (size_t)((m * 2 + (c >> 2)) * 18) * 4 * 256 + warp * 32 + lane;
        const int cc = c & 3;

        float qs[4] = {0.f, 0.f, 0.f, 0.f};
        {
            mainloop128<true>(acc, xa, rg, sb, desc128, lane, wg, qs);
            TS(wg, 4);
            float q0 = qs[0] + qs[1], q2 = qs[2] + qs[3];
            q0 += __shfl_xor_sync(0xffffffffu, q0, 1); q2 += __shfl_xor_sync(0xffffffffu, q2, 1);
            q0 += __shfl_xor_sync(0xffffffffu, q0, 2); q2 += __shfl_xor_sync(0xffffffffu, q2, 2);
            const float var0 = fmaxf(q0 * (1.f / 512.f) - rho0 * rho0, 0.f), var1 = fmaxf(q2 * (1.f / 512.f) - rho1 * rho1, 0.f);
            rho0 = rcp_fast(bf16_round(sqrt_fast(bf16_round(bf16_round(var0) + 1e-5f))));
            rho1 = rcp_fast(bf16_round(sqrt_fast(bf16_round(bf16_round(var1) + 1e-5f))));
            r0.rho = rho0; r0.rl = rho0 * 1.4426950408889634f; r0.rho2 = rho0 * rho0;
            r1.rho = rho1; r1.rl = rho1 * 1.4426950408889634f; r1.rho2 = rho1 * rho1;
            {
                TS(wg, 24);
                const uint32_t pkb = sb + (SCR0 + wg) * STAGE_BYTES;
                mbar_wait(sb + BAR_FULL + 8 * (SCR0 + wg), 0);
                rg.next();
                rg.next();
                const uint32_t ra = pkb + (w * 16 + g) * 128 + t * 4;
#pragma unroll
                for (int nb = 0; nb < 8; nb++) {
                    const uint32_t off = (uint32_t)((nb ^ g) << 4);
                    uint32_t p0 = pack_bf16(phi_f(acc[nb * 4], r0), phi_f(acc[nb * 4 + 1], r0));
                    uint32_t p1 = pack_bf16(phi_f(acc[nb * 4 + 2], r1), phi_f(acc[nb * 4 + 3], r1));
                    uint32_t v0 = pack_bf16(acc[32 + nb * 4] * rho0, acc[32 + nb * 4 + 1] * rho0);
                    uint32_t v1 = pack_bf16(acc[32 + nb * 4 + 2] * rho1, acc[32 + nb * 4 + 3] * rho1);
                    asm volatile("st.shared.u32 [%0], %1;" ::"r"(ra + off), "r"(p0) : "memory");
                    asm volatile("st.shared.u32 [%0], %1;" ::"r"(ra + off + 1024), "r"(p1) : "memory");
                    asm volatile("st.shared.u32 [%0], %1;" ::"r"(ra + off + 8192), "r"(v0) : "memory");
                    asm volatile("st.shared.u32 [%0], %1;" ::"r"(ra + off + 8192 + 1024), "r"(v1) : "memory");
                }
                TS(wg, 25);
                asm volatile("fence.proxy.async.shared::cta;" ::: "memory");
                bar_sync(1 + wg, 128);
                TS(wg, 26);
                const uint64_t da = make_desc(pkb, 8192, 1024, 1);
                const uint64_t db = make_desc(pkb + 8192, 8192, 1024, 1);
                const uint64_t d1 = make_desc(sb + OFF_ONES, 128, 128, 0);
                float kva[32], za[4];
                wg_fence();
#pragma unroll
                for (int ks = 0; ks < 4; ks++) {
                    wgmma_n64_ss_tt(kva, da + ks * 128, db + ks * 128, ks != 0);
                    wgmma_n8_ss_tn(za, da + ks * 128, d1, ks != 0);
                }
                wg_commit();
                wg_wait<0>();
                acc_fence(kva);
                acc_fence(za);
                if (lane < 4) mbar_arrive_cta(sb + BAR_EMPTY + 8 * (SCR0 + (lane >> 1)), lane & 1);
                TS(wg, 27);
                float o[8];
#pragma unroll
                for (int i = 0; i < 8; i++)
                    o[i] = (w == 0) ? kva[i] : (w == 1) ? kva[8 + i] : (w == 2) ? kva[16 + i] : kva[24 + i];
                float4* comb = (float4*)(smem + OFF_COMB) + (tid & 127);
                if (wg == 0) {
                    comb[0] = make_float4(o[0], o[1], o[2], o[3]);
                    comb[128] = make_float4(o[4], o[5], o[6], o[7]);
                    comb[256] = make_float4(za[0], za[2], 0.f, 0.f);
                    bar_arrive(10, 256);
                } else {
                    mbar_wait(sb + BAR_EPOCH, 0);
                    const unsigned epoch = *(volatile unsigned*)(smem + OFF_EPOCH);
                    bar_sync(10, 256);
                    const float4 a = comb[0], b = comb[128], zz = comb[256];
                    uint4* dst = g_kvp + (size_t)(c * 16 + m) * 544 + w * 136;
                    dst[g * 8 + t] = make_uint4(__float_as_uint(o[0] + a.x), epoch, __float_as_uint(o[1] + a.y), epoch);
                    dst[(g + 8) * 8 + t] = make_uint4(__float_as_uint(o[2] + a.z), epoch, __float_as_uint(o[3] + a.w), epoch);
                    dst[g * 8 + 4 + t] = make_uint4(__float_as_uint(o[4] + b.x), epoch, __float_as_uint(o[5] + b.y), epoch);
                    dst[(g + 8) * 8 + 4 + t] = make_uint4(__float_as_uint(o[6] + b.z), epoch, __float_as_uint(o[7] + b.w), epoch);
                    if (t == 0) {
                        uint2* dz = (uint2*)(dst + 128);
                        dz[g] = make_uint2(__float_as_uint(za[0] + zz.x), epoch);
                        dz[g + 8] = make_uint2(__float_as_uint(za[2] + zz.y), epoch);
                    }
                    bar_arrive(11, 160);
                }
            }
            TS(wg, 5);
        }
#pragma unroll 1
        for (int tile = 1; tile < 4; tile++) {
            mainloop128<false>(acc, xa, rg, sb, desc128, lane, wg, qs);
            TS(wg, 4 + 2 * tile);
            {
                uint4* dst = a2w + (size_t)((4 * (tile - 1) + cc) * 4) * 256;
#pragma unroll
                for (int ks = 0; ks < 4; ks++) dst[ks * 256] = swiglu8(&acc[ks * 8], &acc[32 + ks * 8], r0, r1);
            }
            bar_arrive(3 + wg * 2 + (tile & 1), 160);
            TS(wg, 5 + 2 * tile);
        }
        const uint4* a2r = g_A2 + (size_t)((m2 * 2 + rank) * 18) * 4 * 256 + warp * 32 + lane;
        uint4 af[APF + 1][4];
        {
            float qa[32], gu[32];
            mainloop64x2(qa, gu, xa, rg, sb, desc128, desc64, lane, wg);
            TS(wg, 12);
#pragma unroll
            for (int b = 0; b < APF; b++) {
                mbar_wait(sb + BAR_AREADY + 8 * b, 0);
#pragma unroll
                for (int ks = 0; ks < 4; ks++) af[b][ks] = __ldcg(a2r + (b * 4 + ks) * 256);
            }
            {
                uint4* dst = a2w + (size_t)((12 + (cc >> 1)) * 4 + 2 * (cc & 1)) * 256;
#pragma unroll
                for (int ks = 0; ks < 2; ks++) dst[ks * 256] = swiglu8(&gu[ks * 8], &gu[16 + ks * 8], r0, r1);
                TS(wg, 13);
                mbar_wait(sb + BAR_KVREADY, 0);
                TS(wg, 14);
                const uint2* kf = (const uint2*)(smem + OFF_KVFRAG);
                dst = a2w + (size_t)((14 + cc) * 4) * 256;
#pragma unroll
                for (int hh = 0; hh < 4; hh++) {
                    const float* q = &qa[hh * 8];
                    uint32_t a[4];
                    a[0] = pack_bf16(phi_f(q[0], r0), phi_f(q[1], r0));
                    a[1] = pack_bf16(phi_f(q[2], r1), phi_f(q[3], r1));
                    a[2] = pack_bf16(phi_f(q[4], r0), phi_f(q[5], r0));
                    a[3] = pack_bf16(phi_f(q[6], r1), phi_f(q[7], r1));
                    float n0[4] = {0.f, 0.f, 0.f, 0.f}, n1[4] = {0.f, 0.f, 0.f, 0.f}, dn[4] = {0.f, 0.f, 0.f, 0.f};
                    const uint2 b0 = kf[(hh * 3 + 0) * 32 + lane], b1 = kf[(hh * 3 + 1) * 32 + lane],
                                bz = kf[(hh * 3 + 2) * 32 + lane];
                    mma16816(n0, a, b0.x, b0.y);
                    mma16816(n1, a, b1.x, b1.y);
                    mma16816(dn, a, bz.x, bz.y);
                    const float i0 = rcp_fast(dn[0] + 1e-6f), i1 = rcp_fast(dn[2] + 1e-6f);
                    uint4 v;
                    v.x = pack_bf16(n0[0] * i0, n0[1] * i0);
                    v.y = pack_bf16(n0[2] * i1, n0[3] * i1);
                    v.z = pack_bf16(n1[0] * i0, n1[1] * i0);
                    v.w = pack_bf16(n1[2] * i1, n1[3] * i1);
                    dst[hh * 256] = v;
                }
            }
            bar_arrive(3 + wg * 2, 160);
            TS(wg, 15);
        }

        {
            int prev_st = 0;
            TS(wg, 16);
#pragma unroll
            for (int b = 0; b < 18; b++) {
                if (b == 12) TS(wg, 17);
                mbar_wait(sb + BAR_FULL + 8 * rg.st, rg.ph);
                wg_fence();
                const uint64_t d = desc128 + (uint64_t)(rg.st * (STAGE_BYTES >> 4));
#pragma unroll
                for (int ks = 0; ks < 4; ks++)
                    wgmma_n128_rs(acc, reinterpret_cast<const uint32_t*>(&af[b % (APF + 1)][ks]), d + ks * 128, (b | ks) != 0);
                wg_commit();
                if (b > 0) {
                    wg_wait<1>();
                    if (lane < 2) mbar_arrive(sb + BAR_EMPTY + 8 * prev_st);
                }
                prev_st = rg.st;
                rg.next();
                if (b + APF < 18) {
                    mbar_wait(sb + BAR_AREADY + 8 * (b + APF), 0);
#pragma unroll
                    for (int ks = 0; ks < 4; ks++)
                        af[(b + APF) % (APF + 1)][ks] = __ldcg(a2r + ((b + APF) * 4 + ks) * 256);
                }
            }
            const int row0 = m2 * 128 + wg * 64 + w * 16 + g;
            const int col0 = j2 * 128 + rank * 64 + 2 * t;
            uint32_t xr[16];
#pragma unroll
            for (int nb = 0; nb < 8; nb++) {
                xr[2 * nb] = __ldg((const uint32_t*)(xg + (size_t)row0 * 512 + col0 + nb * 8));
                xr[2 * nb + 1] = __ldg((const uint32_t*)(xg + (size_t)(row0 + 8) * 512 + col0 + nb * 8));
            }
            wg_wait<0>();
            acc_fence(acc);
            TS(wg, 18);
            uint32_t rdst, rbar;
            asm volatile("mapa.shared::cluster.u32 %0, %1, %2;"
                         : "=r"(rdst) : "r"(sb + (SCR0 + wg) * STAGE_BYTES + (tid & 127) * 16), "r"(rank ^ 1));
            mbar_wait(sb + BAR_XRDY, 0);
            asm volatile("mapa.shared::cluster.u32 %0, %1, %2;" : "=r"(rbar) : "r"(sb + BAR_XCHG), "r"(rank ^ 1));
            float keep[32];
#pragma unroll
            for (int i = 0; i < 8; i++) {
                float s0 = rank ? acc[4 * i] : acc[32 + 4 * i], s1 = rank ? acc[4 * i + 1] : acc[33 + 4 * i];
                float s2 = rank ? acc[4 * i + 2] : acc[34 + 4 * i], s3 = rank ? acc[4 * i + 3] : acc[35 + 4 * i];
                asm volatile("st.async.shared::cluster.mbarrier::complete_tx::bytes.v4.f32 [%0], {%1,%2,%3,%4}, [%5];"
                             ::"r"(rdst + i * 2048), "f"(s0), "f"(s1), "f"(s2), "f"(s3), "r"(rbar) : "memory");
#pragma unroll
                for (int e = 0; e < 4; e++) keep[4 * i + e] = rank ? acc[32 + 4 * i + e] : acc[4 * i + e];
            }
            mbar_wait(sb + BAR_XCHG, 0);
            TS(wg, 19);
            const float4* rx = (const float4*)(smem + (SCR0 + wg) * STAGE_BYTES) + (tid & 127);
#pragma unroll
            for (int nb = 0; nb < 8; nb++) {
                const float4 p = rx[nb * 128];
                const uint32_t o0 = pack_bf16(keep[4 * nb] + p.x + bf_lo(xr[2 * nb]), keep[4 * nb + 1] + p.y + bf_hi(xr[2 * nb]));
                const uint32_t o1 = pack_bf16(keep[4 * nb + 2] + p.z + bf_lo(xr[2 * nb + 1]), keep[4 * nb + 3] + p.w + bf_hi(xr[2 * nb + 1]));
                *(uint32_t*)(outg + (size_t)row0 * 512 + col0 + nb * 8) = o0;
                *(uint32_t*)(outg + (size_t)(row0 + 8) * 512 + col0 + nb * 8) = o1;
            }
        }
        TS(wg, 20);
        asm volatile("barrier.cluster.arrive.relaxed.aligned;\nbarrier.cluster.wait.aligned;" ::: "memory");
        TS(wg, 21);
    }
}

typedef CUresult (*EncodeFn)(CUtensorMap*, CUtensorMapDataType, cuuint32_t, void*, const cuuint64_t*, const cuuint64_t*,
                             const cuuint32_t*, const cuuint32_t*, CUtensorMapInterleave, CUtensorMapSwizzle,
                             CUtensorMapL2promotion, CUtensorMapFloatOOBfill);

void make_map(EncodeFn enc, CUtensorMap* tm, const void* ptr, int rows, int cols, int box_rows, int box_cols,
              CUtensorMapSwizzle swz) {
    cuuint64_t dims[2] = {(cuuint64_t)cols, (cuuint64_t)rows};
    cuuint64_t strides[1] = {(cuuint64_t)cols * 2};
    cuuint32_t box[2] = {(cuuint32_t)box_cols, (cuuint32_t)box_rows};
    cuuint32_t es[2] = {1, 1};
    enc(tm, CU_TENSOR_MAP_DATA_TYPE_BFLOAT16, 2, const_cast<void*>(ptr), dims, strides, box, es,
        CU_TENSOR_MAP_INTERLEAVE_NONE, swz, CU_TENSOR_MAP_L2_PROMOTION_L2_256B, CU_TENSOR_MAP_FLOAT_OOB_FILL_NONE);
}

}

extern "C" void kernel_launch(void* const* d_in, const int* in_sizes, int n_in, void* d_out, int out_size) {
    (void)in_sizes; (void)n_in; (void)out_size;
    static EncodeFn enc = nullptr;
    if (!enc) {
        void* fn = nullptr;
        cudaDriverEntryPointQueryResult qr;
        cudaGetDriverEntryPoint("cuTensorMapEncodeTiled", &fn, cudaEnableDefault, &qr);
        enc = (EncodeFn)fn;
        cudaFuncSetAttribute(fused_kernel, cudaFuncAttributeMaxDynamicSharedMemorySize, SMEM_BYTES);
    }
    const void* x = d_in[0];
    const void* wqkv = d_in[1];
    const void* wo = d_in[2];
    const void* w1 = d_in[4];
    const void* w3 = d_in[5];
    const void* w2 = d_in[6];
    CUtensorMap tx, tqkv, t1, t3, t1h, t3h, t2, t2h, two;
    make_map(enc, &tx, x, 2048, 512, 128, 64, CU_TENSOR_MAP_SWIZZLE_128B);
    make_map(enc, &tqkv, wqkv, 512, 1536, 64, 64, CU_TENSOR_MAP_SWIZZLE_128B);
    make_map(enc, &t1, w1, 512, 1792, 64, 64, CU_TENSOR_MAP_SWIZZLE_128B);
    make_map(enc, &t3, w3, 512, 1792, 64, 64, CU_TENSOR_MAP_SWIZZLE_128B);
    make_map(enc, &t1h, w1, 512, 1792, 64, 32, CU_TENSOR_MAP_SWIZZLE_64B);
    make_map(enc, &t3h, w3, 512, 1792, 64, 32, CU_TENSOR_MAP_SWIZZLE_64B);
    make_map(enc, &t2, w2, 1792, 512, 64, 64, CU_TENSOR_MAP_SWIZZLE_128B);
    make_map(enc, &t2h, w2, 1792, 512, 32, 64, CU_TENSOR_MAP_SWIZZLE_128B);
    make_map(enc, &two, wo, 512, 512, 64, 64, CU_TENSOR_MAP_SWIZZLE_128B);
    fused_kernel<<<128, 384, SMEM_BYTES>>>(tx, tqkv, t1, t3, t1h, t3h, t2, t2h, two, (const __nv_bfloat16*)x,
                                           (__nv_bfloat16*)d_out, (const char*)wqkv, (const char*)w1, (const char*)w3,
                                           (const char*)w2, (const char*)wo);
}
```

```cpp
#include <cuda_runtime.h>
#include <cuda_bf16.h>
#include <cuda.h>
#include <stdint.h>

namespace {

constexpr int NST = 13;
constexpr int STAGE_BYTES = 16384;
constexpr int XST0 = 5;
constexpr int SCR0 = 8;
constexpr int OFF_MISC = NST * STAGE_BYTES;
constexpr int OFF_KVRAW = OFF_MISC;
constexpr int OFF_KVFRAG = OFF_MISC + 8704;
constexpr int OFF_ONES = OFF_MISC + 11776;
constexpr int OFF_BARS = OFF_MISC + 12032;
constexpr int OFF_COMB = OFF_MISC + 12544;
constexpr int BAR_FULL = OFF_BARS;
constexpr int BAR_EMPTY = BAR_FULL + 8 * NST;
constexpr int BAR_XFULL = BAR_EMPTY + 8 * NST;
constexpr int BAR_KVREADY = BAR_XFULL + 64;
constexpr int BAR_XCHG = BAR_KVREADY + 8;
constexpr int BAR_AREADY = BAR_XCHG + 8;
constexpr int BAR_EPOCH = BAR_AREADY + 8 * 18;
constexpr int BAR_XRDY = BAR_EPOCH + 8;
constexpr int OFF_EPOCH = BAR_XRDY + 8;
constexpr int SMEM_BYTES = OFF_MISC + 12544 + 6144;

constexpr int APF = 5;
constexpr unsigned SPIN_LIMIT = 1u << 24;

__device__ uint4 g_A2[16 * 2 * 18 * 4 * 256];
__device__ uint4 g_kvp[8 * 16 * 544];
__device__ uint4 g_kvs[8 * 544];
__device__ unsigned g_a2flag[16 * 8 * 4 * 2];
__device__ unsigned g_epoch;
__device__ unsigned g_ticket;

#define TS(role, i)
#define TSW(role, i)

__device__ __forceinline__ uint32_t smem_u32(const void* p) { return (uint32_t)__cvta_generic_to_shared(p); }
__device__ __forceinline__ void mbar_init(uint32_t bar, uint32_t cnt) {
    asm volatile("mbarrier.init.shared::cta.b64 [%0], %1;" ::"r"(bar), "r"(cnt) : "memory");
}
__device__ __forceinline__ void mbar_expect_tx(uint32_t bar, uint32_t bytes) {
    asm volatile("mbarrier.arrive.expect_tx.shared::cta.b64 _, [%0], %1;" ::"r"(bar), "r"(bytes) : "memory");
}
__device__ __forceinline__ void mbar_arrive(uint32_t bar) {
    asm volatile("mbarrier.arrive.shared::cta.b64 _, [%0];" ::"r"(bar) : "memory");
}
__device__ __forceinline__ void mbar_arrive_cta(uint32_t bar, uint32_t cta) {
    asm volatile(
        "{\n.reg .b32 ra;\nmapa.shared::cluster.u32 ra, %0, %1;\n"
        "mbarrier.arrive.shared::cluster.b64 _, [ra];\n}" ::"r"(bar), "r"(cta) : "memory");
}
__device__ __forceinline__ void mbar_wait(uint32_t bar, uint32_t parity) {
    asm volatile(
        "{\n.reg .pred p, q;\n.reg .u32 n;\nmov.u32 n, 0;\n"
        "WAIT_%=:\n"
        "mbarrier.try_wait.parity.shared::cta.b64 p, [%0], %1;\n"
        "@p bra.uni DONE_%=;\n"
        "add.u32 n, n, 1;\n"
        "setp.gt.u32 q, n, %2;\n"
        "@q trap;\n"
        "bra.uni WAIT_%=;\n"
        "DONE_%=:\n}"
        ::"r"(bar), "r"(parity), "n"(SPIN_LIMIT) : "memory");
}
__device__ __forceinline__ unsigned ld_acquire(const unsigned* p) {
    unsigned v;
    asm volatile("ld.acquire.gpu.global.u32 %0, [%1];" : "=r"(v) : "l"(p) : "memory");
    return v;
}
__device__ __forceinline__ void st_release(unsigned* p, unsigned v) {
    asm volatile("st.release.gpu.global.u32 [%0], %1;" ::"l"(p), "r"(v) : "memory");
}
__device__ __forceinline__ unsigned read_epoch() {
    return __shfl_sync(0xffffffffu, *(volatile unsigned*)&g_epoch, 0) + 1;
}
__device__ __forceinline__ void tma_load(uint32_t dst, const CUtensorMap* tm, uint32_t bar, int x, int y) {
    asm volatile(
        "cp.async.bulk.tensor.2d.shared::cluster.global.mbarrier::complete_tx::bytes [%0], [%1, {%3, %4}], [%2];"
        ::"r"(dst), "l"(tm), "r"(bar), "r"(x), "r"(y) : "memory");
}
__device__ __forceinline__ void tma_load_mc(uint32_t dst, const CUtensorMap* tm, uint32_t bar, int x, int y) {
    asm volatile(
        "cp.async.bulk.tensor.2d.shared::cluster.global.mbarrier::complete_tx::bytes.multicast::cluster "
        "[%0], [%1, {%3, %4}], [%2], %5;"
        ::"r"(dst), "l"(tm), "r"(bar), "r"(x), "r"(y), "h"((uint16_t)3) : "memory");
}
__device__ __forceinline__ void prefetch_tm(const CUtensorMap* tm) {
    asm volatile("prefetch.tensormap [%0];" ::"l"(tm) : "memory");
}
__device__ __forceinline__ void l2_prefetch(const void* p, uint32_t bytes) {
    asm volatile("cp.async.bulk.prefetch.L2.global [%0], %1;" ::"l"(p), "r"(bytes) : "memory");
}
__device__ __forceinline__ void bar_sync(int id, int n) { asm volatile("bar.sync %0, %1;" ::"r"(id), "r"(n) : "memory"); }
__device__ __forceinline__ void bar_arrive(int id, int n) { asm volatile("bar.arrive %0, %1;" ::"r"(id), "r"(n) : "memory"); }
__device__ __forceinline__ void wg_fence() { asm volatile("wgmma.fence.sync.aligned;" ::: "memory"); }
__device__ __forceinline__ void wg_commit() { asm volatile("wgmma.commit_group.sync.aligned;" ::: "memory"); }
template <int N>
__device__ __forceinline__ void wg_wait() { asm volatile("wgmma.wait_group.sync.aligned %0;" ::"n"(N) : "memory"); }

__device__ __forceinline__ uint64_t make_desc(uint32_t addr, uint32_t lbo, uint32_t sbo, uint64_t swz) {
    return (uint64_t)((addr & 0x3FFFF) >> 4) | ((uint64_t)(lbo >> 4) << 16) | ((uint64_t)(sbo >> 4) << 32) | (swz << 62);
}

#define ACC8(a, o) "+f"(a[o]), "+f"(a[o + 1]), "+f"(a[o + 2]), "+f"(a[o + 3]), "+f"(a[o + 4]), "+f"(a[o + 5]), "+f"(a[o + 6]), "+f"(a[o + 7])
constexpr uint32_t DHI128 = (1024u >> 4) | (1u << 30);
constexpr uint32_t DHI64 = (512u >> 4) | (2u << 30);
__device__ __forceinline__ void wgmma_n128_rs(float (&d)[64], const uint32_t* a, uint32_t db, int scale_d) {
    asm volatile(
        "{\n.reg .pred p;\n.reg .b64 dd;\nsetp.ne.b32 p, %69, 0;\nmov.b64 dd, {%68, %70};\n"
        "wgmma.mma_async.sync.aligned.m64n128k16.f32.bf16.bf16 "
        "{%0,%1,%2,%3,%4,%5,%6,%7,%8,%9,%10,%11,%12,%13,%14,%15,%16,%17,%18,%19,%20,%21,%22,%23,%24,%25,%26,%27,%28,%29,%30,%31,"
        "%32,%33,%34,%35,%36,%37,%38,%39,%40,%41,%42,%43,%44,%45,%46,%47,%48,%49,%50,%51,%52,%53,%54,%55,%56,%57,%58,%59,%60,%61,%62,%63},"
        "{%64,%65,%66,%67}, dd, p, 1, 1, 1;\n}"
        : ACC8(d, 0), ACC8(d, 8), ACC8(d, 16), ACC8(d, 24), ACC8(d, 32), ACC8(d, 40), ACC8(d, 48), ACC8(d, 56)
        : "r"(a[0]), "r"(a[1]), "r"(a[2]), "r"(a[3]), "r"(db), "r"(scale_d), "n"(DHI128));
}
template <uint32_t HI>
__device__ __forceinline__ void wgmma_n64_rs(float (&d)[32], const uint32_t* a, uint32_t db, int scale_d) {
    asm volatile(
        "{\n.reg .pred p;\n.reg .b64 dd;\nsetp.ne.b32 p, %37, 0;\nmov.b64 dd, {%36, %38};\n"
        "wgmma.mma_async.sync.aligned.m64n64k16.f32.bf16.bf16 "
        "{%0,%1,%2,%3,%4,%5,%6,%7,%8,%9,%10,%11,%12,%13,%14,%15,%16,%17,%18,%19,%20,%21,%22,%23,%24,%25,%26,%27,%28,%29,%30,%31},"
        "{%32,%33,%34,%35}, dd, p, 1, 1, 1;\n}"
        : ACC8(d, 0), ACC8(d, 8), ACC8(d, 16), ACC8(d, 24)
        : "r"(a[0]), "r"(a[1]), "r"(a[2]), "r"(a[3]), "r"(db), "r"(scale_d), "n"(HI));
}
__device__ __forceinline__ void wgmma_n64_ss_tt(float (&d)[32], uint64_t da, uint64_t db, int scale_d) {
    asm volatile(
        "{\n.reg .pred p;\nsetp.ne.b32 p, %34, 0;\n"
        "wgmma.mma_async.sync.aligned.m64n64k16.f32.bf16.bf16 "
        "{%0,%1,%2,%3,%4,%5,%6,%7,%8,%9,%10,%11,%12,%13,%14,%15,%16,%17,%18,%19,%20,%21,%22,%23,%24,%25,%26,%27,%28,%29,%30,%31},"
        "%32, %33, p, 1, 1, 1, 1;\n}"
        : ACC8(d, 0), ACC8(d, 8), ACC8(d, 16), ACC8(d, 24)
        : "l"(da), "l"(db), "r"(scale_d));
}
__device__ __forceinline__ void wgmma_n8_ss_tn(float (&d)[4], uint64_t da, uint64_t db, int scale_d) {
    asm volatile(
        "{\n.reg .pred p;\nsetp.ne.b32 p, %6, 0;\n"
        "wgmma.mma_async.sync.aligned.m64n8k16.f32.bf16.bf16 {%0,%1,%2,%3}, %4, %5, p, 1, 1, 1, 0;\n}"
        : "+f"(d[0]), "+f"(d[1]), "+f"(d[2]), "+f"(d[3])
        : "l"(da), "l"(db), "r"(scale_d));
}
template <int N>
__device__ __forceinline__ void acc_fence(float (&d)[N]) {
#pragma unroll
    for (int i = 0; i < N; i++) asm volatile("" : "+f"(d[i])::"memory");
}
__device__ __forceinline__ void mma16816(float (&c)[4], const uint32_t* a, uint32_t b0, uint32_t b1) {
    asm volatile(
        "mma.sync.aligned.m16n8k16.row.col.f32.bf16.bf16.f32 {%0,%1,%2,%3}, {%4,%5,%6,%7}, {%8,%9}, {%0,%1,%2,%3};"
        : "+f"(c[0]), "+f"(c[1]), "+f"(c[2]), "+f"(c[3])
        : "r"(a[0]), "r"(a[1]), "r"(a[2]), "r"(a[3]), "r"(b0), "r"(b1));
}
__device__ __forceinline__ uint32_t pack_bf16(float lo, float hi) {
    uint32_t r;
    asm("cvt.rn.bf16x2.f32 %0, %1, %2;" : "=r"(r) : "f"(hi), "f"(lo));
    return r;
}
__device__ __forceinline__ float bf_lo(uint32_t v) { return __uint_as_float(v << 16); }
__device__ __forceinline__ float bf_hi(uint32_t v) { return __uint_as_float(v & 0xffff0000u); }
__device__ __forceinline__ float bf16_round(float v) { return __bfloat162float(__float2bfloat16_rn(v)); }
__device__ __forceinline__ float sqrt_fast(float v) {
    float r;
    asm("sqrt.approx.ftz.f32 %0, %1;" : "=f"(r) : "f"(v));
    return r;
}
__device__ __forceinline__ float rcp_fast(float v) {
    float r;
    asm("rcp.approx.ftz.f32 %0, %1;" : "=f"(r) : "f"(v));
    return r;
}
__device__ __forceinline__ float ex2_fast(float v) {
    float r;
    asm("ex2.approx.ftz.f32 %0, %1;" : "=f"(r) : "f"(v));
    return r;
}
struct RowScale { float rho, rl, var; };
__device__ __forceinline__ float phi_f(float a, const RowScale& r) {
    return fmaf(fmaxf(a, 0.f), r.rho, ex2_fast(fminf(a, 0.f) * r.rl) + 1e-6f);
}
__device__ __forceinline__ float swiglu_f(float ga, float ua, const RowScale& r) {
    return (ga * ua) * rcp_fast(fmaf(ex2_fast(-ga * r.rl), r.var, r.var));
}
__device__ __forceinline__ uint4 swiglu8(const float* gp, const float* up, const RowScale& r0, const RowScale& r1) {
    uint4 v;
    v.x = pack_bf16(swiglu_f(gp[0], up[0], r0), swiglu_f(gp[1], up[1], r0));
    v.y = pack_bf16(swiglu_f(gp[2], up[2], r1), swiglu_f(gp[3], up[3], r1));
    v.z = pack_bf16(swiglu_f(gp[4], up[4], r0), swiglu_f(gp[5], up[5], r0));
    v.w = pack_bf16(swiglu_f(gp[6], up[6], r1), swiglu_f(gp[7], up[7], r1));
    return v;
}
__device__ __forceinline__ void cp_async16(uint32_t dst, const void* src) {
    asm volatile("cp.async.cg.shared.global [%0], [%1], 16;" ::"r"(dst), "l"(src) : "memory");
}

__device__ __forceinline__ int ring_lap(int u) { return (u * 79) >> 10; }
__device__ __forceinline__ int ring_slot(int u) { return u - NST * ring_lap(u); }

__device__ __forceinline__ void sumsq_mma(const uint32_t (&xa)[128], int lane, float& q0, float& q1) {
    float c0[2][4], c1[2][4];
#pragma unroll
    for (int i = 0; i < 8; i++) { c0[i >> 2][i & 3] = 0.f; c1[i >> 2][i & 3] = 0.f; }
#pragma unroll
    for (int k = 0; k < 32; k++) {
        mma16816(c0[k & 1], &xa[4 * k], xa[4 * k], xa[4 * k + 2]);
        mma16816(c1[k & 1], &xa[4 * k], xa[4 * k + 1], xa[4 * k + 3]);
    }
    const int g = lane >> 2;
    const float d0 = (g & 1) ? c0[0][1] + c0[1][1] : c0[0][0] + c0[1][0];
    const float d1 = (g & 1) ? c1[0][3] + c1[1][3] : c1[0][2] + c1[1][2];
    const int src = (lane & ~3) | (g >> 1);
    q0 = __shfl_sync(0xffffffffu, d0, src);
    q1 = __shfl_sync(0xffffffffu, d1, src);
}
__device__ __forceinline__ void mainloop128(float (&acc)[64], const uint32_t (&xa)[128], int u0, uint32_t sb,
                                            uint32_t desc128, int lane, int wg) {
    bar_sync(7 + wg, 256);
#pragma unroll
    for (int kb = 0; kb < 8; kb++) {
        const int st = ring_slot(u0 + kb);
        mbar_wait(sb + BAR_FULL + 8 * st, ring_lap(u0 + kb) & 1);
        wg_fence();
        const uint32_t d = desc128 + st * (STAGE_BYTES >> 4);
#pragma unroll
        for (int ks = 0; ks < 4; ks++) wgmma_n128_rs(acc, &xa[(kb * 4 + ks) * 4], d + ks * 128, (kb | ks) != 0);
        wg_commit();
        if (kb == 7) bar_arrive(8 - wg, 256);
        if (kb > 0) {
            wg_wait<1>();
            if (lane < 2) mbar_arrive_cta(sb + BAR_EMPTY + 8 * ring_slot(u0 + kb - 1), lane);
        }
    }
    wg_wait<0>();
    acc_fence(acc);
    if (lane < 2) mbar_arrive_cta(sb + BAR_EMPTY + 8 * ring_slot(u0 + 7), lane);
}
__device__ __forceinline__ void mainloop64x2(float (&a0)[32], float (&a1)[32], const uint32_t (&xa)[128], int u0,
                                             uint32_t sb, uint32_t desc128, int lane, int wg) {
    bar_sync(7 + wg, 256);
#pragma unroll
    for (int kb = 0; kb < 8; kb++) {
        const int st = ring_slot(u0 + kb);
        mbar_wait(sb + BAR_FULL + 8 * st, ring_lap(u0 + kb) & 1);
        wg_fence();
        const uint32_t d = desc128 + st * (STAGE_BYTES >> 4);
        const uint32_t d2 = d + (8192 >> 4) - ((4096u >> 4) << 16);
#pragma unroll
        for (int ks = 0; ks < 4; ks++) {
            wgmma_n64_rs<DHI128>(a0, &xa[(kb * 4 + ks) * 4], d + ks * 128, (kb | ks) != 0);
            wgmma_n64_rs<DHI64>(a1, &xa[(kb * 4 + ks) * 4], d2 + ks * 64, (kb | ks) != 0);
        }
        wg_commit();
        if (kb == 7 && wg == 0) bar_arrive(8, 256);
        if (kb > 0) {
            wg_wait<1>();
            if (lane < 2) mbar_arrive_cta(sb + BAR_EMPTY + 8 * ring_slot(u0 + kb - 1), lane);
        }
    }
    wg_wait<0>();
    acc_fence(a0);
    acc_fence(a1);
    if (lane < 2) mbar_arrive_cta(sb + BAR_EMPTY + 8 * ring_slot(u0 + 7), lane);
}

__global__ void __cluster_dims__(2, 1, 1) __launch_bounds__(384, 1)
fused_kernel(const __grid_constant__ CUtensorMap tm_x, const __grid_constant__ CUtensorMap tm_qkv,
             const __grid_constant__ CUtensorMap tm_w1, const __grid_constant__ CUtensorMap tm_w3,
             const __grid_constant__ CUtensorMap tm_w1h, const __grid_constant__ CUtensorMap tm_w3h,
             const __grid_constant__ CUtensorMap tm_w2, const __grid_constant__ CUtensorMap tm_w2h,
             const __grid_constant__ CUtensorMap tm_wo, const __nv_bfloat16* __restrict__ xg,
             __nv_bfloat16* __restrict__ outg, const char* __restrict__ p_qkv, const char* __restrict__ p_w1,
             const char* __restrict__ p_w3, const char* __restrict__ p_w2, const char* __restrict__ p_wo) {
    extern __shared__ __align__(1024) uint8_t smem[];
    const uint32_t sb = smem_u32(smem);
    const int tid = threadIdx.x;
    const int warp = tid >> 5, lane = tid & 31;
    const int rank = blockIdx.x & 1;
    const int pair = blockIdx.x >> 1;
    const int c = pair & 7;
    const int m = (pair >> 3) * 2 + rank;
    const int m2 = (pair >> 3) * 2 + (c & 1);
    const int j2 = c >> 1;

    TS(tid >> 7, 0);
    if (tid == 256) {
#pragma unroll
        for (int i = 0; i < 8; i++) mbar_init(sb + BAR_XFULL + 8 * i, 1);
        asm volatile("fence.proxy.async.shared::cta;" ::: "memory");
#pragma unroll
        for (int kb = 0; kb < 8; kb++) {
            mbar_expect_tx(sb + BAR_XFULL + 8 * kb, 16384);
            tma_load(sb + (XST0 + kb) * STAGE_BYTES, &tm_x, sb + BAR_XFULL + 8 * kb, kb * 64, m * 128);
        }
        TS(2, 21);
    } else if (tid == 0) {
#pragma unroll
        for (int i = 0; i < NST; i++) mbar_init(sb + BAR_FULL + 8 * i, 1);
        asm volatile("fence.mbarrier_init.release.cluster;" ::: "memory");
    } else if (tid == 32) {
#pragma unroll
        for (int i = 0; i < NST; i++) mbar_init(sb + BAR_EMPTY + 8 * i, 16);
        asm volatile("fence.mbarrier_init.release.cluster;" ::: "memory");
    } else if (tid == 64) {
#pragma unroll
        for (int i = 0; i < 10; i++) mbar_init(sb + BAR_KVREADY + 8 * i, 1);
        mbar_expect_tx(sb + BAR_XCHG, 32768);
        asm volatile("fence.mbarrier_init.release.cluster;" ::: "memory");
    } else if (tid == 96) {
#pragma unroll
        for (int i = 10; i < 22; i++) mbar_init(sb + BAR_KVREADY + 8 * i, 1);
        asm volatile("fence.mbarrier_init.release.cluster;" ::: "memory");
    } else if (tid == 288) {
        prefetch_tm(&tm_qkv);
        prefetch_tm(rank ? &tm_w3 : &tm_w1);
        prefetch_tm(&tm_w1h);
        prefetch_tm(&tm_w3h);
        prefetch_tm(&tm_w2);
        prefetch_tm(&tm_w2h);
        prefetch_tm(&tm_wo);
    } else if (tid >= 320) {
        ((uint32_t*)(smem + OFF_ONES))[tid - 320] = 0x3F803F80u;
        asm volatile("fence.proxy.async.shared::cta;" ::: "memory");
    }
    __syncthreads();
    TS(tid >> 7, 22);
    asm volatile("barrier.cluster.arrive.relaxed.aligned;\nbarrier.cluster.wait.acquire.aligned;" ::: "memory");

    if (warp >= 8) {
        asm volatile("setmaxnreg.dec.sync.aligned.u32 40;");
        if (warp == 8) {
            if (lane == 0) {
                int st = 0;
                uint32_t lap = 0;
                for (int it = 0; it < 40; it++) {
                    const int tile = it >> 3, kb = it & 7;
                    const uint32_t full = sb + BAR_FULL + 8 * st;
                    mbar_wait(sb + BAR_EMPTY + 8 * st, (st >= XST0) ? (lap & 1) : ((lap & 1) ^ 1));
                    mbar_expect_tx(full, STAGE_BYTES);
                    const uint32_t dst = sb + st * STAGE_BYTES;
                    if (tile == 0) {
                        tma_load_mc(dst + rank * 8192, &tm_qkv, full, 512 + 512 * rank + 64 * c, kb * 64);
                    } else if (tile < 4) {
                        tma_load_mc(dst + rank * 8192, rank ? &tm_w3 : &tm_w1, full, 224 * c + 64 * (tile - 1), kb * 64);
                    } else if (rank == 0) {
                        tma_load_mc(dst, &tm_qkv, full, 64 * c, kb * 64);
                    } else {
                        tma_load_mc(dst + 8192, &tm_w1h, full, 224 * c + 192, kb * 64);
                        tma_load_mc(dst + 12288, &tm_w3h, full, 224 * c + 192, kb * 64);
                    }
                    if (++st == NST) { st = 0; lap++; }
                    if (it == 7) {
                        mbar_wait(sb + BAR_EMPTY + 8 * SCR0, 0);
                        mbar_arrive(sb + BAR_FULL + 8 * SCR0);
                        mbar_wait(sb + BAR_EMPTY + 8 * (SCR0 + 1), 0);
                        mbar_arrive(sb + BAR_FULL + 8 * (SCR0 + 1));
                        st += 2;
                    }
                }
                TS(2, 1);
                for (int b = 0; b < 18; b++) {
                    const uint32_t full = sb + BAR_FULL + 8 * st;
                    const uint32_t dst = sb + st * STAGE_BYTES;
                    mbar_wait(sb + BAR_EMPTY + 8 * st, (st >= XST0) ? (lap & 1) : ((lap & 1) ^ 1));
                    mbar_expect_tx(full, STAGE_BYTES);
                    if (b < 12) {
                        const int row = 224 * (4 * rank + (b & 3)) + 64 * (b >> 2);
                        tma_load(dst, &tm_w2, full, 128 * j2, row);
                        tma_load(dst + 8192, &tm_w2, full, 128 * j2 + 64, row);
                    } else if (b < 14) {
                        const int row = 224 * (4 * rank + 2 * (b - 12)) + 192;
                        tma_load(dst, &tm_w2h, full, 128 * j2, row);
                        tma_load(dst + 4096, &tm_w2h, full, 128 * j2, row + 224);
                        tma_load(dst + 8192, &tm_w2h, full, 128 * j2 + 64, row);
                        tma_load(dst + 12288, &tm_w2h, full, 128 * j2 + 64, row + 224);
                    } else {
                        const int row = 64 * (4 * rank + (b - 14));
                        tma_load(dst, &tm_wo, full, 128 * j2, row);
                        tma_load(dst + 8192, &tm_wo, full, 128 * j2 + 64, row);
                    }
                    TS(2, 2 + b);
                    if (++st == NST) { st = 0; lap++; }
                }
                mbar_wait(sb + BAR_EMPTY + 8 * SCR0, lap & 1);
                mbar_wait(sb + BAR_EMPTY + 8 * (SCR0 + 1), lap & 1);
                mbar_arrive_cta(sb + BAR_XRDY, rank ^ 1);
            }
        } else if (warp < 11) {
            const int wg = warp - 9;
            const unsigned epoch = read_epoch();
            bar_arrive(9, 96);
            for (int t = 1; t < 5; t++) {
                bar_sync(3 + wg * 2 + (t & 1), 160);
                if (lane == 0) st_release(&g_a2flag[((m * 8 + c) * 4 + (t - 1)) * 2 + wg], epoch);
                TSW(3, 2 * t + wg);
            }
        } else {
            const unsigned epoch = read_epoch();
            bar_sync(9, 96);
            if (lane == 0) {
                const unsigned tk = atomicInc(&g_ticket, 127u);
                if (tk == 127u) *(volatile unsigned*)&g_epoch = epoch;
            }
            if (lane == 0) *(volatile unsigned*)(smem + OFF_EPOCH) = epoch;
            __syncwarp();
            if (lane == 0) mbar_arrive(sb + BAR_EPOCH);
            const uint4* raw = (const uint4*)(smem + OFF_KVRAW);
            bar_sync(11, 160);
#pragma unroll 1
            for (int level = 0; level < 2; level++) {
                const uint4* base = level ? g_kvs + c * 544 : g_kvp + (size_t)c * 16 * 544 + 34 * m;
                unsigned n = 0;
                while (true) {
                    int j = lane, off = lane;
#pragma unroll
                    for (int k = 0; k < 17; k++) {
                        cp_async16(sb + OFF_KVRAW + (lane + 32 * k) * 16, base + off);
                        j += 32; off += 32;
                        if (level == 0 && j >= 34) { j -= 34; off += 544 - 34; }
                    }
                    asm volatile("cp.async.wait_all;" ::: "memory");
                    unsigned bad = 0;
#pragma unroll 4
                    for (int k = 0; k < 17; k++) {
                        const uint4 v = raw[lane + 32 * k];
                        bad |= (v.y ^ epoch) | (v.w ^ epoch);
                    }
                    if (__all_sync(0xffffffffu, bad == 0)) break;
                    __nanosleep(50);
                    if (++n > SPIN_LIMIT) asm volatile("trap;");
                }
                TSW(4, 2 * level);
                if (level == 0) {
                    for (int j = lane; j < 34; j += 32) {
                        float s0 = 0.f, s1 = 0.f;
#pragma unroll 4
                        for (int pp = 0; pp < 16; pp++) {
                            const uint4 v = raw[pp * 34 + j];
                            s0 += __uint_as_float(v.x);
                            s1 += __uint_as_float(v.z);
                        }
                        g_kvs[c * 544 + 34 * m + j] = make_uint4(__float_as_uint(s0), epoch, __float_as_uint(s1), epoch);
                    }
                    __syncwarp();
                    TSW(4, 1);
                }
            }
            const float* ks = (const float*)(smem + OFF_KVRAW);
            uint2* kf = (uint2*)(smem + OFF_KVFRAG);
            const int g = lane >> 2, t = lane & 3;
#pragma unroll 2
            for (int hh = 0; hh < 4; hh++) {
                const float* k = ks + hh * 544;
#pragma unroll
                for (int b = 0; b < 2; b++) {
                    uint2 v;
                    v.x = pack_bf16(k[2 * ((2 * t) * 16 + 8 * b + g)], k[2 * ((2 * t + 1) * 16 + 8 * b + g)]);
                    v.y = pack_bf16(k[2 * ((2 * t + 8) * 16 + 8 * b + g)], k[2 * ((2 * t + 9) * 16 + 8 * b + g)]);
                    kf[(hh * 3 + b) * 32 + lane] = v;
                }
                uint2 z;
                z.x = pack_bf16(k[2 * (256 + 2 * t)], k[2 * (256 + 2 * t + 1)]);
                z.y = pack_bf16(k[2 * (256 + 2 * t + 8)], k[2 * (256 + 2 * t + 9)]);
                kf[(hh * 3 + 2) * 32 + lane] = z;
            }
            __syncwarp();
            if (lane == 0) mbar_arrive(sb + BAR_KVREADY);
            TSW(4, 4);
            const unsigned* fl = g_a2flag + (m2 * 8 + rank * 4) * 8 + lane;
            unsigned ready = 0;
            for (int b = 0; b < 18; b++) {
                const unsigned need = (b < 12) ? (3u << ((b & 3) * 8 + (b >> 2) * 2)) : (b < 14) ? (0xC0C0u << ((b - 12) * 16)) : 0u;
                unsigned n = 0;
                while ((ready & need) != need) {
                    ready = __ballot_sync(0xffffffffu, ld_acquire(fl) == epoch);
                    if (++n > SPIN_LIMIT) asm volatile("trap;");
                }
                if (lane == 0) mbar_arrive(sb + BAR_AREADY + 8 * b);
                TSW(5, b);
            }
        }
    } else {
        asm volatile("setmaxnreg.inc.sync.aligned.u32 232;");
        const int wg = warp >> 2, w = warp & 3;
        const int g = lane >> 2, t = lane & 3;
        float acc[64];
        uint32_t xa[128];
        float rho0, rho1;
        RowScale r0, r1;

        TS(wg, 1);
        {
            const int row = wg * 64 + w * 16 + (lane & 7) + ((lane >> 3) & 1) * 8;
            const uint32_t rbase = sb + XST0 * STAGE_BYTES + row * 128;
            const int hi = lane >> 4, r7 = lane & 7;
            float sm[4][4];
#pragma unroll
            for (int i = 0; i < 16; i++) sm[i >> 2][i & 3] = 0.f;
            if (wg == 1) bar_arrive(7, 256);
#pragma unroll
            for (int kb = 0; kb < 8; kb++) {
                mbar_wait(sb + BAR_XFULL + 8 * kb, 0);
#pragma unroll
                for (int ks = 0; ks < 4; ks++) {
                    uint32_t* a = &xa[(kb * 4 + ks) * 4];
                    const uint32_t addr = rbase + kb * STAGE_BYTES + (((2 * ks + hi) ^ r7) << 4);
                    asm volatile("ldmatrix.sync.aligned.m8n8.x4.shared.b16 {%0,%1,%2,%3}, [%4];"
                                 : "=r"(a[0]), "=r"(a[1]), "=r"(a[2]), "=r"(a[3]) : "r"(addr) : "memory");
                    mma16816(sm[ks], a, 0x3F803F80u, 0x3F803F80u);
                }
            }
            TS(wg, 2);
            const float mean0 = ((sm[0][0] + sm[1][0]) + (sm[2][0] + sm[3][0])) * (1.f / 512.f);
            const float mean1 = ((sm[0][2] + sm[1][2]) + (sm[2][2] + sm[3][2])) * (1.f / 512.f);
            __syncwarp();
            if (lane < 16) mbar_arrive_cta(sb + BAR_EMPTY + 8 * (XST0 + (lane >> 1)), lane & 1);
            const __nv_bfloat162 mb0 = __float2bfloat162_rn(mean0), mb1 = __float2bfloat162_rn(mean1);
#pragma unroll
            for (int i = 0; i < 128; i++) {
                __nv_bfloat162 v = *reinterpret_cast<__nv_bfloat162*>(&xa[i]);
                v = __hsub2(v, (i & 1) ? mb1 : mb0);
                xa[i] = *reinterpret_cast<uint32_t*>(&v);
            }
            rho0 = mean0 - __low2float(mb0);
            rho1 = mean1 - __low2float(mb1);
        }

        TS(wg, 3);
        const uint32_t desc128 = ((sb & 0x3FFFF) >> 4) | ((8192u >> 4) << 16);
        uint4* a2w = g_A2 + (size_t)((m * 2 + (c >> 2)) * 18) * 4 * 256 + warp * 32 + lane;
        const int cc = c & 3;

        {
            float q0, q2;
            if (wg == 1) sumsq_mma(xa, lane, q0, q2);
            mainloop128(acc, xa, 0, sb, desc128, lane, wg);
            TS(wg, 4);
            if (wg == 0) sumsq_mma(xa, lane, q0, q2);
            const float var0 = fmaxf(q0 * (1.f / 512.f) - rho0 * rho0, 0.f), var1 = fmaxf(q2 * (1.f / 512.f) - rho1 * rho1, 0.f);
            const float sd0 = bf16_round(sqrt_fast(bf16_round(bf16_round(var0) + 1e-5f)));
            const float sd1 = bf16_round(sqrt_fast(bf16_round(bf16_round(var1) + 1e-5f)));
            rho0 = rcp_fast(sd0);
            rho1 = rcp_fast(sd1);
            r0.rho = rho0; r0.rl = rho0 * 1.4426950408889634f; r0.var = sd0 * sd0;
            r1.rho = rho1; r1.rl = rho1 * 1.4426950408889634f; r1.var = sd1 * sd1;
            {
                TS(wg, 24);
                const uint32_t pkb = sb + (SCR0 + wg) * STAGE_BYTES;
                mbar_wait(sb + BAR_FULL + 8 * (SCR0 + wg), 0);
                const uint32_t ra = pkb + (w * 16 + g) * 128 + t * 4;
#pragma unroll
                for (int nb = 0; nb < 8; nb++) {
                    const uint32_t off = (uint32_t)((nb ^ g) << 4);
                    uint32_t p0 = pack_bf16(phi_f(acc[nb * 4], r0), phi_f(acc[nb * 4 + 1], r0));
                    uint32_t p1 = pack_bf16(phi_f(acc[nb * 4 + 2], r1), phi_f(acc[nb * 4 + 3], r1));
                    uint32_t v0 = pack_bf16(acc[32 + nb * 4] * rho0, acc[32 + nb * 4 + 1] * rho0);
                    uint32_t v1 = pack_bf16(acc[32 + nb * 4 + 2] * rho1, acc[32 + nb * 4 + 3] * rho1);
                    asm volatile("st.shared.u32 [%0], %1;" ::"r"(ra + off), "r"(p0) : "memory");
                    asm volatile("st.shared.u32 [%0], %1;" ::"r"(ra + off + 1024), "r"(p1) : "memory");
                    asm volatile("st.shared.u32 [%0], %1;" ::"r"(ra + off + 8192), "r"(v0) : "memory");
                    asm volatile("st.shared.u32 [%0], %1;" ::"r"(ra + off + 8192 + 1024), "r"(v1) : "memory");
                }
                TS(wg, 25);
                asm volatile("fence.proxy.async.shared::cta;" ::: "memory");
                bar_sync(1 + wg, 128);
                TS(wg, 26);
                const uint64_t da = make_desc(pkb, 8192, 1024, 1);
                const uint64_t db = make_desc(pkb + 8192, 8192, 1024, 1);
                const uint64_t d1 = make_desc(sb + OFF_ONES, 128, 128, 0);
                float kva[32], za[4];
                wg_fence();
#pragma unroll
                for (int ks = 0; ks < 4; ks++) {
                    wgmma_n64_ss_tt(kva, da + ks * 128, db + ks * 128, ks != 0);
                    wgmma_n8_ss_tn(za, da + ks * 128, d1, ks != 0);
                }
                wg_commit();
                wg_wait<0>();
                acc_fence(kva);
                acc_fence(za);
                if (lane < 4) mbar_arrive_cta(sb + BAR_EMPTY + 8 * (SCR0 + (lane >> 1)), lane & 1);
                TS(wg, 27);
                float o[8];
#pragma unroll
                for (int i = 0; i < 8; i++)
                    o[i] = (w == 0) ? kva[i] : (w == 1) ? kva[8 + i] : (w == 2) ? kva[16 + i] : kva[24 + i];
                float4* comb = (float4*)(smem + OFF_COMB) + (tid & 127);
                if (wg == 0) {
                    comb[0] = make_float4(o[0], o[1], o[2], o[3]);
                    comb[128] = make_float4(o[4], o[5], o[6], o[7]);
                    comb[256] = make_float4(za[0], za[2], 0.f, 0.f);
                    bar_arrive(10, 256);
                } else {
                    mbar_wait(sb + BAR_EPOCH, 0);
                    const unsigned epoch = *(volatile unsigned*)(smem + OFF_EPOCH);
                    bar_sync(10, 256);
                    const float4 a = comb[0], b = comb[128], zz = comb[256];
                    uint4* dst = g_kvp + (size_t)(c * 16 + m) * 544 + w * 136;
                    dst[g * 8 + t] = make_uint4(__float_as_uint(o[0] + a.x), epoch, __float_as_uint(o[1] + a.y), epoch);
                    dst[(g + 8) * 8 + t] = make_uint4(__float_as_uint(o[2] + a.z), epoch, __float_as_uint(o[3] + a.w), epoch);
                    dst[g * 8 + 4 + t] = make_uint4(__float_as_uint(o[4] + b.x), epoch, __float_as_uint(o[5] + b.y), epoch);
                    dst[(g + 8) * 8 + 4 + t] = make_uint4(__float_as_uint(o[6] + b.z), epoch, __float_as_uint(o[7] + b.w), epoch);
                    if (t == 0) {
                        uint2* dz = (uint2*)(dst + 128);
                        dz[g] = make_uint2(__float_as_uint(za[0] + zz.x), epoch);
                        dz[g + 8] = make_uint2(__float_as_uint(za[2] + zz.y), epoch);
                    }
                    bar_arrive(11, 160);
                }
            }
            TS(wg, 5);
        }
#pragma unroll
        for (int tile = 1; tile < 4; tile++) {
            mainloop128(acc, xa, 2 + 8 * tile, sb, desc128, lane, wg);
            TS(wg, 4 + 2 * tile);
            {
                uint4* dst = a2w + (size_t)((4 * (tile - 1) + cc) * 4) * 256;
#pragma unroll
                for (int ks = 0; ks < 4; ks++) dst[ks * 256] = swiglu8(&acc[ks * 8], &acc[32 + ks * 8], r0, r1);
            }
            bar_arrive(3 + wg * 2 + (tile & 1), 160);
            TS(wg, 5 + 2 * tile);
        }
        const uint4* a2r = g_A2 + (size_t)((m2 * 2 + rank) * 18) * 4 * 256 + warp * 32 + lane;
        uint4 af[APF + 1][4];
        {
            float qa[32], gu[32];
            mainloop64x2(qa, gu, xa, 34, sb, desc128, lane, wg);
            TS(wg, 12);
#pragma unroll
            for (int b = 0; b < APF; b++) {
                mbar_wait(sb + BAR_AREADY + 8 * b, 0);
#pragma unroll
                for (int ks = 0; ks < 4; ks++) af[b][ks] = __ldcg(a2r + (b * 4 + ks) * 256);
            }
            {
                uint4* dst = a2w + (size_t)((12 + (cc >> 1)) * 4 + 2 * (cc & 1)) * 256;
#pragma unroll
                for (int ks = 0; ks < 2; ks++) dst[ks * 256] = swiglu8(&gu[ks * 8], &gu[16 + ks * 8], r0, r1);
                TS(wg, 13);
                mbar_wait(sb + BAR_KVREADY, 0);
                TS(wg, 14);
                const uint2* kf = (const uint2*)(smem + OFF_KVFRAG);
                dst = a2w + (size_t)((14 + cc) * 4) * 256;
#pragma unroll
                for (int hh = 0; hh < 4; hh++) {
                    const float* q = &qa[hh * 8];
                    uint32_t a[4];
                    a[0] = pack_bf16(phi_f(q[0], r0), phi_f(q[1], r0));
                    a[1] = pack_bf16(phi_f(q[2], r1), phi_f(q[3], r1));
                    a[2] = pack_bf16(phi_f(q[4], r0), phi_f(q[5], r0));
                    a[3] = pack_bf16(phi_f(q[6], r1), phi_f(q[7], r1));
                    float n0[4] = {0.f, 0.f, 0.f, 0.f}, n1[4] = {0.f, 0.f, 0.f, 0.f}, dn[4] = {0.f, 0.f, 0.f, 0.f};
                    const uint2 b0 = kf[(hh * 3 + 0) * 32 + lane], b1 = kf[(hh * 3 + 1) * 32 + lane],
                                bz = kf[(hh * 3 + 2) * 32 + lane];
                    mma16816(n0, a, b0.x, b0.y);
                    mma16816(n1, a, b1.x, b1.y);
                    mma16816(dn, a, bz.x, bz.y);
                    const float i0 = rcp_fast(dn[0] + 1e-6f), i1 = rcp_fast(dn[2] + 1e-6f);
                    uint4 v;
                    v.x = pack_bf16(n0[0] * i0, n0[1] * i0);
                    v.y = pack_bf16(n0[2] * i1, n0[3] * i1);
                    v.z = pack_bf16(n1[0] * i0, n1[1] * i0);
                    v.w = pack_bf16(n1[2] * i1, n1[3] * i1);
                    dst[hh * 256] = v;
                }
            }
            bar_arrive(3 + wg * 2, 160);
            TS(wg, 15);
        }

        {
            TS(wg, 16);
#pragma unroll
            for (int b = 0; b < 18; b++) {
                if (b == 12) TS(wg, 17);
                mbar_wait(sb + BAR_FULL + 8 * ring_slot(42 + b), ring_lap(42 + b) & 1);
                wg_fence();
                const uint32_t d = desc128 + ring_slot(42 + b) * (STAGE_BYTES >> 4);
#pragma unroll
                for (int ks = 0; ks < 4; ks++)
                    wgmma_n128_rs(acc, reinterpret_cast<const uint32_t*>(&af[b % (APF + 1)][ks]), d + ks * 128, (b | ks) != 0);
                wg_commit();
                if (b > 0) {
                    wg_wait<1>();
                    if (lane < 2) mbar_arrive(sb + BAR_EMPTY + 8 * ring_slot(41 + b));
                }
                if (b + APF < 18) {
                    mbar_wait(sb + BAR_AREADY + 8 * (b + APF), 0);
#pragma unroll
                    for (int ks = 0; ks < 4; ks++)
                        af[(b + APF) % (APF + 1)][ks] = __ldcg(a2r + ((b + APF) * 4 + ks) * 256);
                }
            }
            const int row0 = m2 * 128 + wg * 64 + w * 16 + g;
            const int col0 = j2 * 128 + rank * 64 + 2 * t;
            uint32_t xr[16];
#pragma unroll
            for (int nb = 0; nb < 8; nb++) {
                xr[2 * nb] = __ldg((const uint32_t*)(xg + (size_t)row0 * 512 + col0 + nb * 8));
                xr[2 * nb + 1] = __ldg((const uint32_t*)(xg + (size_t)(row0 + 8) * 512 + col0 + nb * 8));
            }
            wg_wait<0>();
            acc_fence(acc);
            TS(wg, 18);
            uint32_t rdst, rbar;
            asm volatile("mapa.shared::cluster.u32 %0, %1, %2;"
                         : "=r"(rdst) : "r"(sb + (SCR0 + wg) * STAGE_BYTES + (tid & 127) * 16), "r"(rank ^ 1));
            mbar_wait(sb + BAR_XRDY, 0);
            asm volatile("mapa.shared::cluster.u32 %0, %1, %2;" : "=r"(rbar) : "r"(sb + BAR_XCHG), "r"(rank ^ 1));
            float keep[32];
#pragma unroll
            for (int i = 0; i < 8; i++) {
                float s0 = rank ? acc[4 * i] : acc[32 + 4 * i], s1 = rank ? acc[4 * i + 1] : acc[33 + 4 * i];
                float s2 = rank ? acc[4 * i + 2] : acc[34 + 4 * i], s3 = rank ? acc[4 * i + 3] : acc[35 + 4 * i];
                asm volatile("st.async.shared::cluster.mbarrier::complete_tx::bytes.v4.f32 [%0], {%1,%2,%3,%4}, [%5];"
                             ::"r"(rdst + i * 2048), "f"(s0), "f"(s1), "f"(s2), "f"(s3), "r"(rbar) : "memory");
#pragma unroll
                for (int e = 0; e < 4; e++) keep[4 * i + e] = rank ? acc[32 + 4 * i + e] : acc[4 * i + e];
            }
            mbar_wait(sb + BAR_XCHG, 0);
            TS(wg, 19);
            const float4* rx = (const float4*)(smem + (SCR0 + wg) * STAGE_BYTES) + (tid & 127);
#pragma unroll
            for (int nb = 0; nb < 8; nb++) {
                const float4 p = rx[nb * 128];
                const uint32_t o0 = pack_bf16(keep[4 * nb] + p.x + bf_lo(xr[2 * nb]), keep[4 * nb + 1] + p.y + bf_hi(xr[2 * nb]));
                const uint32_t o1 = pack_bf16(keep[4 * nb + 2] + p.z + bf_lo(xr[2 * nb + 1]), keep[4 * nb + 3] + p.w + bf_hi(xr[2 * nb + 1]));
                *(uint32_t*)(outg + (size_t)row0 * 512 + col0 + nb * 8) = o0;
                *(uint32_t*)(outg + (size_t)(row0 + 8) * 512 + col0 + nb * 8) = o1;
            }
        }
        TS(wg, 20);
        asm volatile("barrier.cluster.arrive.relaxed.aligned;\nbarrier.cluster.wait.aligned;" ::: "memory");
        TS(wg, 21);
    }
}

typedef CUresult (*EncodeFn)(CUtensorMap*, CUtensorMapDataType, cuuint32_t, void*, const cuuint64_t*, const cuuint64_t*,
                             const cuuint32_t*, const cuuint32_t*, CUtensorMapInterleave, CUtensorMapSwizzle,
                             CUtensorMapL2promotion, CUtensorMapFloatOOBfill);

void make_map(EncodeFn enc, CUtensorMap* tm, const void* ptr, int rows, int cols, int box_rows, int box_cols,
              CUtensorMapSwizzle swz) {
    cuuint64_t dims[2] = {(cuuint64_t)cols, (cuuint64_t)rows};
    cuuint64_t strides[1] = {(cuuint64_t)cols * 2};
    cuuint32_t box[2] = {(cuuint32_t)box_cols, (cuuint32_t)box_rows};
    cuuint32_t es[2] = {1, 1};
    enc(tm, CU_TENSOR_MAP_DATA_TYPE_BFLOAT16, 2, const_cast<void*>(ptr), dims, strides, box, es,
        CU_TENSOR_MAP_INTERLEAVE_NONE, swz, CU_TENSOR_MAP_L2_PROMOTION_L2_256B, CU_TENSOR_MAP_FLOAT_OOB_FILL_NONE);
}

}

extern "C" void kernel_launch(void* const* d_in, const int* in_sizes, int n_in, void* d_out, int out_size) {
    (void)in_sizes; (void)n_in; (void)out_size;
    static EncodeFn enc = nullptr;
    if (!enc) {
        void* fn = nullptr;
        cudaDriverEntryPointQueryResult qr;
        cudaGetDriverEntryPoint("cuTensorMapEncodeTiled", &fn, cudaEnableDefault, &qr);
        enc = (EncodeFn)fn;
        cudaFuncSetAttribute(fused_kernel, cudaFuncAttributeMaxDynamicSharedMemorySize, SMEM_BYTES);
    }
    const void* x = d_in[0];
    const void* wqkv = d_in[1];
    const void* wo = d_in[2];
    const void* w1 = d_in[4];
    const void* w3 = d_in[5];
    const void* w2 = d_in[6];
    CUtensorMap tx, tqkv, t1, t3, t1h, t3h, t2, t2h, two;
    make_map(enc, &tx, x, 2048, 512, 128, 64, CU_TENSOR_MAP_SWIZZLE_128B);
    make_map(enc, &tqkv, wqkv, 512, 1536, 64, 64, CU_TENSOR_MAP_SWIZZLE_128B);
    make_map(enc, &t1, w1, 512, 1792, 64, 64, CU_TENSOR_MAP_SWIZZLE_128B);
    make_map(enc, &t3, w3, 512, 1792, 64, 64, CU_TENSOR_MAP_SWIZZLE_128B);
    make_map(enc, &t1h, w1, 512, 1792, 64, 32, CU_TENSOR_MAP_SWIZZLE_64B);
    make_map(enc, &t3h, w3, 512, 1792, 64, 32, CU_TENSOR_MAP_SWIZZLE_64B);
    make_map(enc, &t2, w2, 1792, 512, 64, 64, CU_TENSOR_MAP_SWIZZLE_128B);
    make_map(enc, &t2h, w2, 1792, 512, 32, 64, CU_TENSOR_MAP_SWIZZLE_128B);
    make_map(enc, &two, wo, 512, 512, 64, 64, CU_TENSOR_MAP_SWIZZLE_128B);
    fused_kernel<<<128, 384, SMEM_BYTES>>>(tx, tqkv, t1, t3, t1h, t3h, t2, t2h, two, (const __nv_bfloat16*)x,
                                           (__nv_bfloat16*)d_out, (const char*)wqkv, (const char*)w1, (const char*)w3,
                                           (const char*)w2, (const char*)wo);
}
```

```cpp
#include <cuda_runtime.h>
#include <cuda_bf16.h>
#include <cuda.h>
#include <stdint.h>

namespace {

constexpr int NST = 13;
constexpr int STAGE_BYTES = 16384;
constexpr int XST0 = 5;
constexpr int SCR0 = 8;
constexpr int OFF_MISC = NST * STAGE_BYTES;
constexpr int OFF_KVFRAG = OFF_MISC;
constexpr int OFF_ONES = OFF_MISC + 3072;
constexpr int OFF_BARS = OFF_MISC + 3328;
constexpr int BAR_FULL = OFF_BARS;
constexpr int BAR_EMPTY = BAR_FULL + 8 * NST;
constexpr int BAR_XFULL = BAR_EMPTY + 8 * NST;
constexpr int BAR_KVREADY = BAR_XFULL + 64;
constexpr int BAR_XCHG = BAR_KVREADY + 8;
constexpr int BAR_AREADY = BAR_XCHG + 8;
constexpr int BAR_EPOCH = BAR_AREADY + 8 * 18;
constexpr int BAR_XRDY = BAR_EPOCH + 8;
constexpr int OFF_EPOCH = BAR_XRDY + 8;
constexpr int SMEM_BYTES = OFF_MISC + 4096;

constexpr int APF = 5;
constexpr unsigned SPIN_LIMIT = 1u << 24;

__device__ uint4 g_A2[16 * 2 * 18 * 4 * 256];
__device__ float4 g_kvacc[2 * 8 * 272];
__device__ unsigned g_kvcnt[8];
__device__ unsigned g_a2flag[16 * 8 * 4 * 2];
__device__ unsigned g_epoch;
__device__ unsigned g_ticket;

#define TS(role, i)
#define TSW(role, i)

__device__ __forceinline__ uint32_t smem_u32(const void* p) { return (uint32_t)__cvta_generic_to_shared(p); }
__device__ __forceinline__ void mbar_init(uint32_t bar, uint32_t cnt) {
    asm volatile("mbarrier.init.shared::cta.b64 [%0], %1;" ::"r"(bar), "r"(cnt) : "memory");
}
__device__ __forceinline__ void mbar_expect_tx(uint32_t bar, uint32_t bytes) {
    asm volatile("mbarrier.arrive.expect_tx.shared::cta.b64 _, [%0], %1;" ::"r"(bar), "r"(bytes) : "memory");
}
__device__ __forceinline__ void mbar_arrive(uint32_t bar) {
    asm volatile("mbarrier.arrive.shared::cta.b64 _, [%0];" ::"r"(bar) : "memory");
}
__device__ __forceinline__ void mbar_arrive_cta(uint32_t bar, uint32_t cta) {
    asm volatile(
        "{\n.reg .b32 ra;\nmapa.shared::cluster.u32 ra, %0, %1;\n"
        "mbarrier.arrive.shared::cluster.b64 _, [ra];\n}" ::"r"(bar), "r"(cta) : "memory");
}
__device__ __forceinline__ void mbar_wait(uint32_t bar, uint32_t parity) {
    asm volatile(
        "{\n.reg .pred p, q;\n.reg .u32 n;\nmov.u32 n, 0;\n"
        "WAIT_%=:\n"
        "mbarrier.try_wait.parity.shared::cta.b64 p, [%0], %1;\n"
        "@p bra.uni DONE_%=;\n"
        "add.u32 n, n, 1;\n"
        "setp.gt.u32 q, n, %2;\n"
        "@q trap;\n"
        "bra.uni WAIT_%=;\n"
        "DONE_%=:\n}"
        ::"r"(bar), "r"(parity), "n"(SPIN_LIMIT) : "memory");
}
__device__ __forceinline__ unsigned ld_acquire(const unsigned* p) {
    unsigned v;
    asm volatile("ld.acquire.gpu.global.u32 %0, [%1];" : "=r"(v) : "l"(p) : "memory");
    return v;
}
__device__ __forceinline__ void st_release(unsigned* p, unsigned v) {
    asm volatile("st.release.gpu.global.u32 [%0], %1;" ::"l"(p), "r"(v) : "memory");
}
__device__ __forceinline__ unsigned read_epoch() {
    return __shfl_sync(0xffffffffu, *(volatile unsigned*)&g_epoch, 0) + 1;
}
__device__ __forceinline__ void tma_load(uint32_t dst, const CUtensorMap* tm, uint32_t bar, int x, int y) {
    asm volatile(
        "cp.async.bulk.tensor.2d.shared::cluster.global.mbarrier::complete_tx::bytes [%0], [%1, {%3, %4}], [%2];"
        ::"r"(dst), "l"(tm), "r"(bar), "r"(x), "r"(y) : "memory");
}
__device__ __forceinline__ void tma_load_mc(uint32_t dst, const CUtensorMap* tm, uint32_t bar, int x, int y) {
    asm volatile(
        "cp.async.bulk.tensor.2d.shared::cluster.global.mbarrier::complete_tx::bytes.multicast::cluster "
        "[%0], [%1, {%3, %4}], [%2], %5;"
        ::"r"(dst), "l"(tm), "r"(bar), "r"(x), "r"(y), "h"((uint16_t)3) : "memory");
}
__device__ __forceinline__ void prefetch_tm(const CUtensorMap* tm) {
    asm volatile("prefetch.tensormap [%0];" ::"l"(tm) : "memory");
}
__device__ __forceinline__ void l2_prefetch(const void* p, uint32_t bytes) {
    asm volatile("cp.async.bulk.prefetch.L2.global [%0], %1;" ::"l"(p), "r"(bytes) : "memory");
}
__device__ __forceinline__ void bar_sync(int id, int n) { asm volatile("bar.sync %0, %1;" ::"r"(id), "r"(n) : "memory"); }
__device__ __forceinline__ void bar_arrive(int id, int n) { asm volatile("bar.arrive %0, %1;" ::"r"(id), "r"(n) : "memory"); }
__device__ __forceinline__ void wg_fence() { asm volatile("wgmma.fence.sync.aligned;" ::: "memory"); }
__device__ __forceinline__ void wg_commit() { asm volatile("wgmma.commit_group.sync.aligned;" ::: "memory"); }
template <int N>
__device__ __forceinline__ void wg_wait() { asm volatile("wgmma.wait_group.sync.aligned %0;" ::"n"(N) : "memory"); }

__device__ __forceinline__ uint64_t make_desc(uint32_t addr, uint32_t lbo, uint32_t sbo, uint64_t swz) {
    return (uint64_t)((addr & 0x3FFFF) >> 4) | ((uint64_t)(lbo >> 4) << 16) | ((uint64_t)(sbo >> 4) << 32) | (swz << 62);
}

#define ACC8(a, o) "+f"(a[o]), "+f"(a[o + 1]), "+f"(a[o + 2]), "+f"(a[o + 3]), "+f"(a[o + 4]), "+f"(a[o + 5]), "+f"(a[o + 6]), "+f"(a[o + 7])
constexpr uint32_t DHI128 = (1024u >> 4) | (1u << 30);
constexpr uint32_t DHI64 = (512u >> 4) | (2u << 30);
__device__ __forceinline__ void wgmma_n128_rs(float (&d)[64], const uint32_t* a, uint32_t db, int scale_d) {
    asm volatile(
        "{\n.reg .pred p;\n.reg .b64 dd;\nsetp.ne.b32 p, %69, 0;\nmov.b64 dd, {%68, %70};\n"
        "wgmma.mma_async.sync.aligned.m64n128k16.f32.bf16.bf16 "
        "{%0,%1,%2,%3,%4,%5,%6,%7,%8,%9,%10,%11,%12,%13,%14,%15,%16,%17,%18,%19,%20,%21,%22,%23,%24,%25,%26,%27,%28,%29,%30,%31,"
        "%32,%33,%34,%35,%36,%37,%38,%39,%40,%41,%42,%43,%44,%45,%46,%47,%48,%49,%50,%51,%52,%53,%54,%55,%56,%57,%58,%59,%60,%61,%62,%63},"
        "{%64,%65,%66,%67}, dd, p, 1, 1, 1;\n}"
        : ACC8(d, 0), ACC8(d, 8), ACC8(d, 16), ACC8(d, 24), ACC8(d, 32), ACC8(d, 40), ACC8(d, 48), ACC8(d, 56)
        : "r"(a[0]), "r"(a[1]), "r"(a[2]), "r"(a[3]), "r"(db), "r"(scale_d), "n"(DHI128));
}
template <uint32_t HI>
__device__ __forceinline__ void wgmma_n64_rs(float (&d)[32], const uint32_t* a, uint32_t db, int scale_d) {
    asm volatile(
        "{\n.reg .pred p;\n.reg .b64 dd;\nsetp.ne.b32 p, %37, 0;\nmov.b64 dd, {%36, %38};\n"
        "wgmma.mma_async.sync.aligned.m64n64k16.f32.bf16.bf16 "
        "{%0,%1,%2,%3,%4,%5,%6,%7,%8,%9,%10,%11,%12,%13,%14,%15,%16,%17,%18,%19,%20,%21,%22,%23,%24,%25,%26,%27,%28,%29,%30,%31},"
        "{%32,%33,%34,%35}, dd, p, 1, 1, 1;\n}"
        : ACC8(d, 0), ACC8(d, 8), ACC8(d, 16), ACC8(d, 24)
        : "r"(a[0]), "r"(a[1]), "r"(a[2]), "r"(a[3]), "r"(db), "r"(scale_d), "n"(HI));
}
__device__ __forceinline__ void wgmma_n64_ss_tt(float (&d)[32], uint64_t da, uint64_t db, int scale_d) {
    asm volatile(
        "{\n.reg .pred p;\nsetp.ne.b32 p, %34, 0;\n"
        "wgmma.mma_async.sync.aligned.m64n64k16.f32.bf16.bf16 "
        "{%0,%1,%2,%3,%4,%5,%6,%7,%8,%9,%10,%11,%12,%13,%14,%15,%16,%17,%18,%19,%20,%21,%22,%23,%24,%25,%26,%27,%28,%29,%30,%31},"
        "%32, %33, p, 1, 1, 1, 1;\n}"
        : ACC8(d, 0), ACC8(d, 8), ACC8(d, 16), ACC8(d, 24)
        : "l"(da), "l"(db), "r"(scale_d));
}
__device__ __forceinline__ void wgmma_n8_ss_tn(float (&d)[4], uint64_t da, uint64_t db, int scale_d) {
    asm volatile(
        "{\n.reg .pred p;\nsetp.ne.b32 p, %6, 0;\n"
        "wgmma.mma_async.sync.aligned.m64n8k16.f32.bf16.bf16 {%0,%1,%2,%3}, %4, %5, p, 1, 1, 1, 0;\n}"
        : "+f"(d[0]), "+f"(d[1]), "+f"(d[2]), "+f"(d[3])
        : "l"(da), "l"(db), "r"(scale_d));
}
template <int N>
__device__ __forceinline__ void acc_fence(float (&d)[N]) {
#pragma unroll
    for (int i = 0; i < N; i++) asm volatile("" : "+f"(d[i])::"memory");
}
__device__ __forceinline__ void mma16816(float (&c)[4], const uint32_t* a, uint32_t b0, uint32_t b1) {
    asm volatile(
        "mma.sync.aligned.m16n8k16.row.col.f32.bf16.bf16.f32 {%0,%1,%2,%3}, {%4,%5,%6,%7}, {%8,%9}, {%0,%1,%2,%3};"
        : "+f"(c[0]), "+f"(c[1]), "+f"(c[2]), "+f"(c[3])
        : "r"(a[0]), "r"(a[1]), "r"(a[2]), "r"(a[3]), "r"(b0), "r"(b1));
}
__device__ __forceinline__ uint32_t pack_bf16(float lo, float hi) {
    uint32_t r;
    asm("cvt.rn.bf16x2.f32 %0, %1, %2;" : "=r"(r) : "f"(hi), "f"(lo));
    return r;
}
__device__ __forceinline__ float bf_lo(uint32_t v) { return __uint_as_float(v << 16); }
__device__ __forceinline__ float bf_hi(uint32_t v) { return __uint_as_float(v & 0xffff0000u); }
__device__ __forceinline__ float bf16_round(float v) { return __bfloat162float(__float2bfloat16_rn(v)); }
__device__ __forceinline__ float sqrt_fast(float v) {
    float r;
    asm("sqrt.approx.ftz.f32 %0, %1;" : "=f"(r) : "f"(v));
    return r;
}
__device__ __forceinline__ float rcp_fast(float v) {
    float r;
    asm("rcp.approx.ftz.f32 %0, %1;" : "=f"(r) : "f"(v));
    return r;
}
__device__ __forceinline__ float ex2_fast(float v) {
    float r;
    asm("ex2.approx.ftz.f32 %0, %1;" : "=f"(r) : "f"(v));
    return r;
}
struct RowScale { float rho, rl, var; };
__device__ __forceinline__ float phi_f(float a, const RowScale& r) {
    return fmaf(fmaxf(a, 0.f), r.rho, ex2_fast(fminf(a, 0.f) * r.rl) + 1e-6f);
}
__device__ __forceinline__ float swiglu_f(float ga, float ua, const RowScale& r) {
    return (ga * ua) * rcp_fast(fmaf(ex2_fast(-ga * r.rl), r.var, r.var));
}
__device__ __forceinline__ uint4 swiglu8(const float* gp, const float* up, const RowScale& r0, const RowScale& r1) {
    uint4 v;
    v.x = pack_bf16(swiglu_f(gp[0], up[0], r0), swiglu_f(gp[1], up[1], r0));
    v.y = pack_bf16(swiglu_f(gp[2], up[2], r1), swiglu_f(gp[3], up[3], r1));
    v.z = pack_bf16(swiglu_f(gp[4], up[4], r0), swiglu_f(gp[5], up[5], r0));
    v.w = pack_bf16(swiglu_f(gp[6], up[6], r1), swiglu_f(gp[7], up[7], r1));
    return v;
}
__device__ __forceinline__ void red_add2(float* p, float a, float b) {
    asm volatile("red.global.add.v2.f32 [%0], {%1, %2};" ::"l"(p), "f"(a), "f"(b) : "memory");
}
__device__ __forceinline__ void cp_async16(uint32_t dst, const void* src) {
    asm volatile("cp.async.cg.shared.global [%0], [%1], 16;" ::"r"(dst), "l"(src) : "memory");
}

__device__ __forceinline__ int ring_lap(int u) { return (u * 79) >> 10; }
__device__ __forceinline__ int ring_slot(int u) { return u - NST * ring_lap(u); }

__device__ __forceinline__ void mainloop128(float (&acc)[64], const uint32_t (&xa)[128], int u0, uint32_t sb,
                                            uint32_t desc128, int lane, int wg) {
    bar_sync(7 + wg, 256);
#pragma unroll
    for (int kb = 0; kb < 8; kb++) {
        const int st = ring_slot(u0 + kb);
        mbar_wait(sb + BAR_FULL + 8 * st, ring_lap(u0 + kb) & 1);
        wg_fence();
        const uint32_t d = desc128 + st * (STAGE_BYTES >> 4);
#pragma unroll
        for (int ks = 0; ks < 4; ks++) wgmma_n128_rs(acc, &xa[(kb * 4 + ks) * 4], d + ks * 128, (kb | ks) != 0);
        wg_commit();
        if (kb == 7) bar_arrive(8 - wg, 256);
        if (kb > 0) {
            wg_wait<1>();
            if (lane < 2) mbar_arrive_cta(sb + BAR_EMPTY + 8 * ring_slot(u0 + kb - 1), lane);
        }
    }
    wg_wait<0>();
    acc_fence(acc);
    if (lane < 2) mbar_arrive_cta(sb + BAR_EMPTY + 8 * ring_slot(u0 + 7), lane);
}
__device__ __forceinline__ void mainloop64x2(float (&a0)[32], float (&a1)[32], const uint32_t (&xa)[128], int u0,
                                             uint32_t sb, uint32_t desc128, int lane, int wg) {
    bar_sync(7 + wg, 256);
#pragma unroll
    for (int kb = 0; kb < 8; kb++) {
        const int st = ring_slot(u0 + kb);
        mbar_wait(sb + BAR_FULL + 8 * st, ring_lap(u0 + kb) & 1);
        wg_fence();
        const uint32_t d = desc128 + st * (STAGE_BYTES >> 4);
        const uint32_t d2 = d + (8192 >> 4) - ((4096u >> 4) << 16);
#pragma unroll
        for (int ks = 0; ks < 4; ks++) {
            wgmma_n64_rs<DHI128>(a0, &xa[(kb * 4 + ks) * 4], d + ks * 128, (kb | ks) != 0);
            wgmma_n64_rs<DHI64>(a1, &xa[(kb * 4 + ks) * 4], d2 + ks * 64, (kb | ks) != 0);
        }
        wg_commit();
        if (kb == 7 && wg == 0) bar_arrive(8, 256);
        if (kb > 0) {
            wg_wait<1>();
            if (lane < 2) mbar_arrive_cta(sb + BAR_EMPTY + 8 * ring_slot(u0 + kb - 1), lane);
        }
    }
    wg_wait<0>();
    acc_fence(a0);
    acc_fence(a1);
    if (lane < 2) mbar_arrive_cta(sb + BAR_EMPTY + 8 * ring_slot(u0 + 7), lane);
}

__global__ void __cluster_dims__(2, 1, 1) __launch_bounds__(384, 1)
fused_kernel(const __grid_constant__ CUtensorMap tm_x, const __grid_constant__ CUtensorMap tm_qkv,
             const __grid_constant__ CUtensorMap tm_w1, const __grid_constant__ CUtensorMap tm_w3,
             const __grid_constant__ CUtensorMap tm_w1h, const __grid_constant__ CUtensorMap tm_w3h,
             const __grid_constant__ CUtensorMap tm_w2, const __grid_constant__ CUtensorMap tm_w2h,
             const __grid_constant__ CUtensorMap tm_wo, const __nv_bfloat16* __restrict__ xg,
             __nv_bfloat16* __restrict__ outg, const char* __restrict__ p_qkv, const char* __restrict__ p_w1,
             const char* __restrict__ p_w3, const char* __restrict__ p_w2, const char* __restrict__ p_wo) {
    extern __shared__ __align__(1024) uint8_t smem[];
    const uint32_t sb = smem_u32(smem);
    const int tid = threadIdx.x;
    const int warp = tid >> 5, lane = tid & 31;
    const int rank = blockIdx.x & 1;
    const int pair = blockIdx.x >> 1;
    const int c = pair & 7;
    const int m = (pair >> 3) * 2 + rank;
    const int m2 = (pair >> 3) * 2 + (c & 1);
    const int j2 = c >> 1;

    TS(tid >> 7, 0);
    if (tid == 256) {
#pragma unroll
        for (int i = 0; i < 8; i++) mbar_init(sb + BAR_XFULL + 8 * i, 1);
        asm volatile("fence.proxy.async.shared::cta;" ::: "memory");
#pragma unroll
        for (int kb = 0; kb < 8; kb++) {
            mbar_expect_tx(sb + BAR_XFULL + 8 * kb, 16384);
            tma_load(sb + (XST0 + kb) * STAGE_BYTES, &tm_x, sb + BAR_XFULL + 8 * kb, kb * 64, m * 128);
        }
        TS(2, 21);
    } else if (tid == 0) {
#pragma unroll
        for (int i = 0; i < NST; i++) mbar_init(sb + BAR_FULL + 8 * i, 1);
        asm volatile("fence.mbarrier_init.release.cluster;" ::: "memory");
    } else if (tid == 32) {
#pragma unroll
        for (int i = 0; i < NST; i++) mbar_init(sb + BAR_EMPTY + 8 * i, 16);
        asm volatile("fence.mbarrier_init.release.cluster;" ::: "memory");
    } else if (tid == 64) {
#pragma unroll
        for (int i = 0; i < 10; i++) mbar_init(sb + BAR_KVREADY + 8 * i, 1);
        mbar_expect_tx(sb + BAR_XCHG, 32768);
        asm volatile("fence.mbarrier_init.release.cluster;" ::: "memory");
    } else if (tid == 96) {
#pragma unroll
        for (int i = 10; i < 22; i++) mbar_init(sb + BAR_KVREADY + 8 * i, 1);
        asm volatile("fence.mbarrier_init.release.cluster;" ::: "memory");
    } else if (tid == 288) {
        prefetch_tm(&tm_qkv);
        prefetch_tm(rank ? &tm_w3 : &tm_w1);
        prefetch_tm(&tm_w1h);
        prefetch_tm(&tm_w3h);
        prefetch_tm(&tm_w2);
        prefetch_tm(&tm_w2h);
        prefetch_tm(&tm_wo);
    } else if (tid >= 320) {
        ((uint32_t*)(smem + OFF_ONES))[tid - 320] = 0x3F803F80u;
        asm volatile("fence.proxy.async.shared::cta;" ::: "memory");
    }
    __syncthreads();
    TS(tid >> 7, 22);
    asm volatile("barrier.cluster.arrive.relaxed.aligned;\nbarrier.cluster.wait.acquire.aligned;" ::: "memory");

    if (warp >= 8) {
        asm volatile("setmaxnreg.dec.sync.aligned.u32 40;");
        if (warp == 8) {
            if (lane == 0) {
                int st = 0;
                uint32_t lap = 0;
                for (int it = 0; it < 40; it++) {
                    const int tile = it >> 3, kb = it & 7;
                    const uint32_t full = sb + BAR_FULL + 8 * st;
                    mbar_wait(sb + BAR_EMPTY + 8 * st, (st >= XST0) ? (lap & 1) : ((lap & 1) ^ 1));
                    mbar_expect_tx(full, STAGE_BYTES);
                    const uint32_t dst = sb + st * STAGE_BYTES;
                    if (tile == 0) {
                        tma_load_mc(dst + rank * 8192, &tm_qkv, full, 512 + 512 * rank + 64 * c, kb * 64);
                    } else if (tile < 4) {
                        tma_load_mc(dst + rank * 8192, rank ? &tm_w3 : &tm_w1, full, 224 * c + 64 * (tile - 1), kb * 64);
                    } else if (rank == 0) {
                        tma_load_mc(dst, &tm_qkv, full, 64 * c, kb * 64);
                    } else {
                        tma_load_mc(dst + 8192, &tm_w1h, full, 224 * c + 192, kb * 64);
                        tma_load_mc(dst + 12288, &tm_w3h, full, 224 * c + 192, kb * 64);
                    }
                    if (++st == NST) { st = 0; lap++; }
                    if (it == 7) {
                        mbar_wait(sb + BAR_EMPTY + 8 * SCR0, 0);
                        mbar_arrive(sb + BAR_FULL + 8 * SCR0);
                        mbar_wait(sb + BAR_EMPTY + 8 * (SCR0 + 1), 0);
                        mbar_arrive(sb + BAR_FULL + 8 * (SCR0 + 1));
                        st += 2;
                    }
                }
                TS(2, 1);
                for (int b = 0; b < 18; b++) {
                    const uint32_t full = sb + BAR_FULL + 8 * st;
                    const uint32_t dst = sb + st * STAGE_BYTES;
                    mbar_wait(sb + BAR_EMPTY + 8 * st, (st >= XST0) ? (lap & 1) : ((lap & 1) ^ 1));
                    mbar_expect_tx(full, STAGE_BYTES);
                    if (b < 12) {
                        const int row = 224 * (4 * rank + (b & 3)) + 64 * (b >> 2);
                        tma_load(dst, &tm_w2, full, 128 * j2, row);
                        tma_load(dst + 8192, &tm_w2, full, 128 * j2 + 64, row);
                    } else if (b < 14) {
                        const int row = 224 * (4 * rank + 2 * (b - 12)) + 192;
                        tma_load(dst, &tm_w2h, full, 128 * j2, row);
                        tma_load(dst + 4096, &tm_w2h, full, 128 * j2, row + 224);
                        tma_load(dst + 8192, &tm_w2h, full, 128 * j2 + 64, row);
                        tma_load(dst + 12288, &tm_w2h, full, 128 * j2 + 64, row + 224);
                    } else {
                        const int row = 64 * (4 * rank + (b - 14));
                        tma_load(dst, &tm_wo, full, 128 * j2, row);
                        tma_load(dst + 8192, &tm_wo, full, 128 * j2 + 64, row);
                    }
                    TS(2, 2 + b);
                    if (++st == NST) { st = 0; lap++; }
                }
                mbar_wait(sb + BAR_EMPTY + 8 * SCR0, lap & 1);
                mbar_wait(sb + BAR_EMPTY + 8 * (SCR0 + 1), lap & 1);
                mbar_arrive_cta(sb + BAR_XRDY, rank ^ 1);
            }
        } else if (warp < 11) {
            const int wg = warp - 9;
            const unsigned epoch = read_epoch();
            bar_arrive(9, 96);
            for (int t = 0; t < 5; t++) {
                bar_sync(3 + wg * 2 + (t & 1), 160);
                if (lane == 0) {
                    if (t == 0) asm volatile("red.release.gpu.global.add.u32 [%0], 1;" ::"l"(&g_kvcnt[c]) : "memory");
                    else st_release(&g_a2flag[((m * 8 + c) * 4 + (t - 1)) * 2 + wg], epoch);
                }
                TSW(3, 2 * t + wg);
            }
        } else {
            const unsigned epoch = read_epoch();
            bar_sync(9, 96);
            if (lane == 0) {
                const unsigned tk = atomicInc(&g_ticket, 127u);
                if (tk == 127u) *(volatile unsigned*)&g_epoch = epoch;
            }
            if (lane == 0) *(volatile unsigned*)(smem + OFF_EPOCH) = epoch;
            __syncwarp();
            if (lane == 0) mbar_arrive(sb + BAR_EPOCH);
            if (lane < 17) g_kvacc[(((epoch & 1) ^ 1) * 8 + c) * 272 + 17 * m + lane] = make_float4(0.f, 0.f, 0.f, 0.f);
            {
                unsigned n = 0;
                while ((int)(ld_acquire(&g_kvcnt[c]) - 32u * epoch) < 0) {
                    __nanosleep(200);
                    if (++n > SPIN_LIMIT) asm volatile("trap;");
                }
            }
            TSW(4, 0);
            const int g = lane >> 2, t = lane & 3;
            const float* ks = (const float*)(g_kvacc + ((epoch & 1) * 8 + c) * 272) + 32 * t + g;
            uint2* kf = (uint2*)(smem + OFF_KVFRAG) + lane;
#pragma unroll 2
            for (int hh = 0; hh < 4; hh++) {
                const float* k = ks + hh * 272;
                const float a0 = __ldcg(k), a1 = __ldcg(k + 16), a2 = __ldcg(k + 128), a3 = __ldcg(k + 144);
                const float b0 = __ldcg(k + 8), b1 = __ldcg(k + 24), b2 = __ldcg(k + 136), b3 = __ldcg(k + 152);
                const float2 z0 = __ldcg((const float2*)(k - g - 30 * t + 256)), z1 = __ldcg((const float2*)(k - g - 30 * t + 264));
                kf[(hh * 3 + 0) * 32] = make_uint2(pack_bf16(a0, a1), pack_bf16(a2, a3));
                kf[(hh * 3 + 1) * 32] = make_uint2(pack_bf16(b0, b1), pack_bf16(b2, b3));
                kf[(hh * 3 + 2) * 32] = make_uint2(pack_bf16(z0.x, z0.y), pack_bf16(z1.x, z1.y));
            }
            __syncwarp();
            if (lane == 0) mbar_arrive(sb + BAR_KVREADY);
            TSW(4, 4);
            const unsigned* fl = g_a2flag + (m2 * 8 + rank * 4) * 8 + lane;
            unsigned ready = 0;
            for (int b = 0; b < 18; b++) {
                const unsigned need = (b < 12) ? (3u << ((b & 3) * 8 + (b >> 2) * 2)) : (b < 14) ? (0xC0C0u << ((b - 12) * 16)) : 0u;
                unsigned n = 0;
                while ((ready & need) != need) {
                    ready = __ballot_sync(0xffffffffu, ld_acquire(fl) == epoch);
                    if (++n > SPIN_LIMIT) asm volatile("trap;");
                }
                if (lane == 0) mbar_arrive(sb + BAR_AREADY + 8 * b);
                TSW(5, b);
            }
        }
    } else {
        asm volatile("setmaxnreg.inc.sync.aligned.u32 232;");
        const int wg = warp >> 2, w = warp & 3;
        const int g = lane >> 2, t = lane & 3;
        float acc[64];
        uint32_t xa[128];
        float rho0, rho1;
        RowScale r0, r1;

        TS(wg, 1);
        {
            const int row = wg * 64 + w * 16 + (lane & 7) + ((lane >> 3) & 1) * 8;
            const uint32_t rbase = sb + XST0 * STAGE_BYTES + row * 128;
            const int hi = lane >> 4, r7 = lane & 7;
            float sm[2][4], c0[2][4], c1[2][4];
#pragma unroll
            for (int i = 0; i < 8; i++) { sm[i >> 2][i & 3] = 0.f; c0[i >> 2][i & 3] = 0.f; c1[i >> 2][i & 3] = 0.f; }
            if (wg == 1) bar_arrive(7, 256);
#pragma unroll
            for (int kb = 0; kb < 8; kb++) {
                mbar_wait(sb + BAR_XFULL + 8 * kb, 0);
#pragma unroll
                for (int ks = 0; ks < 4; ks++) {
                    uint32_t* a = &xa[(kb * 4 + ks) * 4];
                    const uint32_t addr = rbase + kb * STAGE_BYTES + (((2 * ks + hi) ^ r7) << 4);
                    asm volatile("ldmatrix.sync.aligned.m8n8.x4.shared.b16 {%0,%1,%2,%3}, [%4];"
                                 : "=r"(a[0]), "=r"(a[1]), "=r"(a[2]), "=r"(a[3]) : "r"(addr) : "memory");
                    mma16816(sm[ks & 1], a, 0x3F803F80u, 0x3F803F80u);
                    mma16816(c0[ks & 1], a, a[0], a[2]);
                    mma16816(c1[ks & 1], a, a[1], a[3]);
                }
            }
            TS(wg, 2);
            const float mean0 = (sm[0][0] + sm[1][0]) * (1.f / 512.f);
            const float mean1 = (sm[0][2] + sm[1][2]) * (1.f / 512.f);
            __syncwarp();
            if (lane < 16) mbar_arrive_cta(sb + BAR_EMPTY + 8 * (XST0 + (lane >> 1)), lane & 1);
            const __nv_bfloat162 mb0 = __float2bfloat162_rn(mean0), mb1 = __float2bfloat162_rn(mean1);
#pragma unroll
            for (int i = 0; i < 128; i++) {
                __nv_bfloat162 v = *reinterpret_cast<__nv_bfloat162*>(&xa[i]);
                v = __hsub2(v, (i & 1) ? mb1 : mb0);
                xa[i] = *reinterpret_cast<uint32_t*>(&v);
            }
            const float d0 = (g & 1) ? c0[0][1] + c0[1][1] : c0[0][0] + c0[1][0];
            const float d1 = (g & 1) ? c1[0][3] + c1[1][3] : c1[0][2] + c1[1][2];
            const int src = (lane & ~3) | (g >> 1);
            const float var0 = fmaxf(__shfl_sync(0xffffffffu, d0, src) * (1.f / 512.f) - mean0 * mean0, 0.f);
            const float var1 = fmaxf(__shfl_sync(0xffffffffu, d1, src) * (1.f / 512.f) - mean1 * mean1, 0.f);
            const float sd0 = bf16_round(sqrt_fast(bf16_round(bf16_round(var0) + 1e-5f)));
            const float sd1 = bf16_round(sqrt_fast(bf16_round(bf16_round(var1) + 1e-5f)));
            rho0 = rcp_fast(sd0);
            rho1 = rcp_fast(sd1);
            r0.rho = rho0; r0.rl = rho0 * 1.4426950408889634f; r0.var = sd0 * sd0;
            r1.rho = rho1; r1.rl = rho1 * 1.4426950408889634f; r1.var = sd1 * sd1;
        }

        TS(wg, 3);
        const uint32_t desc128 = ((sb & 0x3FFFF) >> 4) | ((8192u >> 4) << 16);
        uint4* a2w = g_A2 + (size_t)((m * 2 + (c >> 2)) * 18) * 4 * 256 + warp * 32 + lane;
        const int cc = c & 3;

        {
            mainloop128(acc, xa, 0, sb, desc128, lane, wg);
            TS(wg, 4);
            {
                TS(wg, 24);
                const uint32_t pkb = sb + (SCR0 + wg) * STAGE_BYTES;
                mbar_wait(sb + BAR_FULL + 8 * (SCR0 + wg), 0);
                const uint32_t ra = pkb + (w * 16 + g) * 128 + t * 4;
#pragma unroll
                for (int nb = 0; nb < 8; nb++) {
                    const uint32_t off = (uint32_t)((nb ^ g) << 4);
                    uint32_t p0 = pack_bf16(phi_f(acc[nb * 4], r0), phi_f(acc[nb * 4 + 1], r0));
                    uint32_t p1 = pack_bf16(phi_f(acc[nb * 4 + 2], r1), phi_f(acc[nb * 4 + 3], r1));
                    uint32_t v0 = pack_bf16(acc[32 + nb * 4] * rho0, acc[32 + nb * 4 + 1] * rho0);
                    uint32_t v1 = pack_bf16(acc[32 + nb * 4 + 2] * rho1, acc[32 + nb * 4 + 3] * rho1);
                    asm volatile("st.shared.u32 [%0], %1;" ::"r"(ra + off), "r"(p0) : "memory");
                    asm volatile("st.shared.u32 [%0], %1;" ::"r"(ra + off + 1024), "r"(p1) : "memory");
                    asm volatile("st.shared.u32 [%0], %1;" ::"r"(ra + off + 8192), "r"(v0) : "memory");
                    asm volatile("st.shared.u32 [%0], %1;" ::"r"(ra + off + 8192 + 1024), "r"(v1) : "memory");
                }
                TS(wg, 25);
                asm volatile("fence.proxy.async.shared::cta;" ::: "memory");
                bar_sync(1 + wg, 128);
                TS(wg, 26);
                const uint64_t da = make_desc(pkb, 8192, 1024, 1);
                const uint64_t db = make_desc(pkb + 8192, 8192, 1024, 1);
                const uint64_t d1 = make_desc(sb + OFF_ONES, 128, 128, 0);
                float kva[32], za[4];
                wg_fence();
#pragma unroll
                for (int ks = 0; ks < 4; ks++) {
                    wgmma_n64_ss_tt(kva, da + ks * 128, db + ks * 128, ks != 0);
                    wgmma_n8_ss_tn(za, da + ks * 128, d1, ks != 0);
                }
                wg_commit();
                wg_wait<0>();
                acc_fence(kva);
                acc_fence(za);
                if (lane < 4) mbar_arrive_cta(sb + BAR_EMPTY + 8 * (SCR0 + (lane >> 1)), lane & 1);
                TS(wg, 27);
                float o[8];
#pragma unroll
                for (int i = 0; i < 8; i++)
                    o[i] = (w == 0) ? kva[i] : (w == 1) ? kva[8 + i] : (w == 2) ? kva[16 + i] : kva[24 + i];
                mbar_wait(sb + BAR_EPOCH, 0);
                const unsigned par = *(volatile unsigned*)(smem + OFF_EPOCH) & 1;
                float* dst = (float*)(g_kvacc + (par * 8 + c) * 272) + w * 272 + g * 16 + 2 * t;
                red_add2(dst, o[0], o[1]);
                red_add2(dst + 128, o[2], o[3]);
                red_add2(dst + 8, o[4], o[5]);
                red_add2(dst + 136, o[6], o[7]);
                if (t == 0) {
                    atomicAdd(dst - g * 15 + 256, za[0]);
                    atomicAdd(dst - g * 15 + 264, za[2]);
                }
            }
            bar_arrive(3 + wg * 2, 160);
            TS(wg, 5);
        }
#pragma unroll
        for (int tile = 1; tile < 4; tile++) {
            mainloop128(acc, xa, 2 + 8 * tile, sb, desc128, lane, wg);
            TS(wg, 4 + 2 * tile);
            {
                uint4* dst = a2w + (size_t)((4 * (tile - 1) + cc) * 4) * 256;
#pragma unroll
                for (int ks = 0; ks < 4; ks++) dst[ks * 256] = swiglu8(&acc[ks * 8], &acc[32 + ks * 8], r0, r1);
            }
            bar_arrive(3 + wg * 2 + (tile & 1), 160);
            TS(wg, 5 + 2 * tile);
        }
        const uint4* a2r = g_A2 + (size_t)((m2 * 2 + rank) * 18) * 4 * 256 + warp * 32 + lane;
        uint4 af[APF + 1][4];
        {
            float qa[32], gu[32];
            mainloop64x2(qa, gu, xa, 34, sb, desc128, lane, wg);
            TS(wg, 12);
#pragma unroll
            for (int b = 0; b < APF; b++) {
                mbar_wait(sb + BAR_AREADY + 8 * b, 0);
#pragma unroll
                for (int ks = 0; ks < 4; ks++) af[b][ks] = __ldcg(a2r + (b * 4 + ks) * 256);
            }
            {
                uint4* dst = a2w + (size_t)((12 + (cc >> 1)) * 4 + 2 * (cc & 1)) * 256;
#pragma unroll
                for (int ks = 0; ks < 2; ks++) dst[ks * 256] = swiglu8(&gu[ks * 8], &gu[16 + ks * 8], r0, r1);
                TS(wg, 13);
                mbar_wait(sb + BAR_KVREADY, 0);
                TS(wg, 14);
                const uint2* kf = (const uint2*)(smem + OFF_KVFRAG);
                dst = a2w + (size_t)((14 + cc) * 4) * 256;
#pragma unroll
                for (int hh = 0; hh < 4; hh++) {
                    const float* q = &qa[hh * 8];
                    uint32_t a[4];
                    a[0] = pack_bf16(phi_f(q[0], r0), phi_f(q[1], r0));
                    a[1] = pack_bf16(phi_f(q[2], r1), phi_f(q[3], r1));
                    a[2] = pack_bf16(phi_f(q[4], r0), phi_f(q[5], r0));
                    a[3] = pack_bf16(phi_f(q[6], r1), phi_f(q[7], r1));
                    float n0[4] = {0.f, 0.f, 0.f, 0.f}, n1[4] = {0.f, 0.f, 0.f, 0.f}, dn[4] = {0.f, 0.f, 0.f, 0.f};
                    const uint2 b0 = kf[(hh * 3 + 0) * 32 + lane], b1 = kf[(hh * 3 + 1) * 32 + lane],
                                bz = kf[(hh * 3 + 2) * 32 + lane];
                    mma16816(n0, a, b0.x, b0.y);
                    mma16816(n1, a, b1.x, b1.y);
                    mma16816(dn, a, bz.x, bz.y);
                    const float i0 = rcp_fast(dn[0] + 1e-6f), i1 = rcp_fast(dn[2] + 1e-6f);
                    uint4 v;
                    v.x = pack_bf16(n0[0] * i0, n0[1] * i0);
                    v.y = pack_bf16(n0[2] * i1, n0[3] * i1);
                    v.z = pack_bf16(n1[0] * i0, n1[1] * i0);
                    v.w = pack_bf16(n1[2] * i1, n1[3] * i1);
                    dst[hh * 256] = v;
                }
            }
            bar_arrive(3 + wg * 2, 160);
            TS(wg, 15);
        }

        {
            TS(wg, 16);
#pragma unroll
            for (int b = 0; b < 18; b++) {
                if (b == 12) TS(wg, 17);
                mbar_wait(sb + BAR_FULL + 8 * ring_slot(42 + b), ring_lap(42 + b) & 1);
                wg_fence();
                const uint32_t d = desc128 + ring_slot(42 + b) * (STAGE_BYTES >> 4);
#pragma unroll
                for (int ks = 0; ks < 4; ks++)
                    wgmma_n128_rs(acc, reinterpret_cast<const uint32_t*>(&af[b % (APF + 1)][ks]), d + ks * 128, (b | ks) != 0);
                wg_commit();
                if (b > 0) {
                    wg_wait<1>();
                    if (lane < 2) mbar_arrive(sb + BAR_EMPTY + 8 * ring_slot(41 + b));
                }
                if (b + APF < 18) {
                    mbar_wait(sb + BAR_AREADY + 8 * (b + APF), 0);
#pragma unroll
                    for (int ks = 0; ks < 4; ks++)
                        af[(b + APF) % (APF + 1)][ks] = __ldcg(a2r + ((b + APF) * 4 + ks) * 256);
                }
            }
            const int row0 = m2 * 128 + wg * 64 + w * 16 + g;
            const int col0 = j2 * 128 + rank * 64 + 2 * t;
            uint32_t xr[16];
#pragma unroll
            for (int nb = 0; nb < 8; nb++) {
                xr[2 * nb] = __ldg((const uint32_t*)(xg + (size_t)row0 * 512 + col0 + nb * 8));
                xr[2 * nb + 1] = __ldg((const uint32_t*)(xg + (size_t)(row0 + 8) * 512 + col0 + nb * 8));
            }
            wg_wait<0>();
            acc_fence(acc);
            TS(wg, 18);
            uint32_t rdst, rbar;
            asm volatile("mapa.shared::cluster.u32 %0, %1, %2;"
                         : "=r"(rdst) : "r"(sb + (SCR0 + wg) * STAGE_BYTES + (tid & 127) * 16), "r"(rank ^ 1));
            mbar_wait(sb + BAR_XRDY, 0);
            asm volatile("mapa.shared::cluster.u32 %0, %1, %2;" : "=r"(rbar) : "r"(sb + BAR_XCHG), "r"(rank ^ 1));
            float keep[32];
#pragma unroll
            for (int i = 0; i < 8; i++) {
                float s0 = rank ? acc[4 * i] : acc[32 + 4 * i], s1 = rank ? acc[4 * i + 1] : acc[33 + 4 * i];
                float s2 = rank ? acc[4 * i + 2] : acc[34 + 4 * i], s3 = rank ? acc[4 * i + 3] : acc[35 + 4 * i];
                asm volatile("st.async.shared::cluster.mbarrier::complete_tx::bytes.v4.f32 [%0], {%1,%2,%3,%4}, [%5];"
                             ::"r"(rdst + i * 2048), "f"(s0), "f"(s1), "f"(s2), "f"(s3), "r"(rbar) : "memory");
#pragma unroll
                for (int e = 0; e < 4; e++) keep[4 * i + e] = rank ? acc[32 + 4 * i + e] : acc[4 * i + e];
            }
            mbar_wait(sb + BAR_XCHG, 0);
            TS(wg, 19);
            const float4* rx = (const float4*)(smem + (SCR0 + wg) * STAGE_BYTES) + (tid & 127);
#pragma unroll
            for (int nb = 0; nb < 8; nb++) {
                const float4 p = rx[nb * 128];
                const uint32_t o0 = pack_bf16(keep[4 * nb] + p.x + bf_lo(xr[2 * nb]), keep[4 * nb + 1] + p.y + bf_hi(xr[2 * nb]));
                const uint32_t o1 = pack_bf16(keep[4 * nb + 2] + p.z + bf_lo(xr[2 * nb + 1]), keep[4 * nb + 3] + p.w + bf_hi(xr[2 * nb + 1]));
                *(uint32_t*)(outg + (size_t)row0 * 512 + col0 + nb * 8) = o0;
                *(uint32_t*)(outg + (size_t)(row0 + 8) * 512 + col0 + nb * 8) = o1;
            }
        }
        TS(wg, 20);
        asm volatile("barrier.cluster.arrive.relaxed.aligned;\nbarrier.cluster.wait.aligned;" ::: "memory");
        TS(wg, 21);
    }
}

typedef CUresult (*EncodeFn)(CUtensorMap*, CUtensorMapDataType, cuuint32_t, void*, const cuuint64_t*, const cuuint64_t*,
                             const cuuint32_t*, const cuuint32_t*, CUtensorMapInterleave, CUtensorMapSwizzle,
                             CUtensorMapL2promotion, CUtensorMapFloatOOBfill);

void make_map(EncodeFn enc, CUtensorMap* tm, const void* ptr, int rows, int cols, int box_rows, int box_cols,
              CUtensorMapSwizzle swz) {
    cuuint64_t dims[2] = {(cuuint64_t)cols, (cuuint64_t)rows};
    cuuint64_t strides[1] = {(cuuint64_t)cols * 2};
    cuuint32_t box[2] = {(cuuint32_t)box_cols, (cuuint32_t)box_rows};
    cuuint32_t es[2] = {1, 1};
    enc(tm, CU_TENSOR_MAP_DATA_TYPE_BFLOAT16, 2, const_cast<void*>(ptr), dims, strides, box, es,
        CU_TENSOR_MAP_INTERLEAVE_NONE, swz, CU_TENSOR_MAP_L2_PROMOTION_L2_256B, CU_TENSOR_MAP_FLOAT_OOB_FILL_NONE);
}

}

extern "C" void kernel_launch(void* const* d_in, const int* in_sizes, int n_in, void* d_out, int out_size) {
    (void)in_sizes; (void)n_in; (void)out_size;
    static EncodeFn enc = nullptr;
    if (!enc) {
        void* fn = nullptr;
        cudaDriverEntryPointQueryResult qr;
        cudaGetDriverEntryPoint("cuTensorMapEncodeTiled", &fn, cudaEnableDefault, &qr);
        enc = (EncodeFn)fn;
        cudaFuncSetAttribute(fused_kernel, cudaFuncAttributeMaxDynamicSharedMemorySize, SMEM_BYTES);
    }
    const void* x = d_in[0];
    const void* wqkv = d_in[1];
    const void* wo = d_in[2];
    const void* w1 = d_in[4];
    const void* w3 = d_in[5];
    const void* w2 = d_in[6];
    CUtensorMap tx, tqkv, t1, t3, t1h, t3h, t2, t2h, two;
    make_map(enc, &tx, x, 2048, 512, 128, 64, CU_TENSOR_MAP_SWIZZLE_128B);
    make_map(enc, &tqkv, wqkv, 512, 1536, 64, 64, CU_TENSOR_MAP_SWIZZLE_128B);
    make_map(enc, &t1, w1, 512, 1792, 64, 64, CU_TENSOR_MAP_SWIZZLE_128B);
    make_map(enc, &t3, w3, 512, 1792, 64, 64, CU_TENSOR_MAP_SWIZZLE_128B);
    make_map(enc, &t1h, w1, 512, 1792, 64, 32, CU_TENSOR_MAP_SWIZZLE_64B);
    make_map(enc, &t3h, w3, 512, 1792, 64, 32, CU_TENSOR_MAP_SWIZZLE_64B);
    make_map(enc, &t2, w2, 1792, 512, 64, 64, CU_TENSOR_MAP_SWIZZLE_128B);
    make_map(enc, &t2h, w2, 1792, 512, 32, 64, CU_TENSOR_MAP_SWIZZLE_128B);
    make_map(enc, &two, wo, 512, 512, 64, 64, CU_TENSOR_MAP_SWIZZLE_128B);
    fused_kernel<<<128, 384, SMEM_BYTES>>>(tx, tqkv, t1, t3, t1h, t3h, t2, t2h, two, (const __nv_bfloat16*)x,
                                           (__nv_bfloat16*)d_out, (const char*)wqkv, (const char*)w1, (const char*)w3,
                                           (const char*)w2, (const char*)wo);
}
```

```cpp
#include <cuda_runtime.h>
#include <cuda_bf16.h>
#include <cuda.h>
#include <stdint.h>

namespace {

constexpr int NST = 13;
constexpr int STAGE_BYTES = 16384;
constexpr int XST0 = 5;
constexpr int SCR0 = 8;
constexpr int OFF_MISC = NST * STAGE_BYTES;
constexpr int OFF_KVFRAG = OFF_MISC;
constexpr int OFF_ONES = OFF_MISC + 3072;
constexpr int OFF_BARS = OFF_MISC + 3328;
constexpr int BAR_FULL = OFF_BARS;
constexpr int BAR_EMPTY = BAR_FULL + 8 * NST;
constexpr int BAR_XFULL = BAR_EMPTY + 8 * NST;
constexpr int BAR_KVREADY = BAR_XFULL + 64;
constexpr int BAR_XCHG = BAR_KVREADY + 8;
constexpr int BAR_AREADY = BAR_XCHG + 8;
constexpr int BAR_EPOCH = BAR_AREADY + 8 * 18;
constexpr int BAR_XRDY = BAR_EPOCH + 8;
constexpr int OFF_EPOCH = BAR_XRDY + 8;
constexpr int SMEM_BYTES = OFF_MISC + 4096;

constexpr int APF = 5;
constexpr unsigned SPIN_LIMIT = 1u << 24;

__device__ uint4 g_A2[16 * 2 * 18 * 4 * 256];
__device__ float4 g_kvacc[2 * 8 * 272];
__device__ unsigned g_kvcnt[8];
__device__ unsigned g_a2flag[16 * 8 * 4 * 2];
__device__ unsigned g_epoch;
__device__ unsigned g_ticket;

#define TS(role, i)
#define TSW(role, i)

__device__ __forceinline__ uint32_t smem_u32(const void* p) { return (uint32_t)__cvta_generic_to_shared(p); }
__device__ __forceinline__ void mbar_init(uint32_t bar, uint32_t cnt) {
    asm volatile("mbarrier.init.shared::cta.b64 [%0], %1;" ::"r"(bar), "r"(cnt) : "memory");
}
__device__ __forceinline__ void mbar_expect_tx(uint32_t bar, uint32_t bytes) {
    asm volatile("mbarrier.arrive.expect_tx.shared::cta.b64 _, [%0], %1;" ::"r"(bar), "r"(bytes) : "memory");
}
__device__ __forceinline__ void mbar_arrive(uint32_t bar) {
    asm volatile("mbarrier.arrive.shared::cta.b64 _, [%0];" ::"r"(bar) : "memory");
}
__device__ __forceinline__ void mbar_arrive_cta(uint32_t bar, uint32_t cta) {
    asm volatile(
        "{\n.reg .b32 ra;\nmapa.shared::cluster.u32 ra, %0, %1;\n"
        "mbarrier.arrive.shared::cluster.b64 _, [ra];\n}" ::"r"(bar), "r"(cta) : "memory");
}
__device__ __forceinline__ void mbar_wait(uint32_t bar, uint32_t parity) {
    asm volatile(
        "{\n.reg .pred p, q;\n.reg .u32 n;\nmov.u32 n, 0;\n"
        "WAIT_%=:\n"
        "mbarrier.try_wait.parity.shared::cta.b64 p, [%0], %1;\n"
        "@p bra.uni DONE_%=;\n"
        "add.u32 n, n, 1;\n"
        "setp.gt.u32 q, n, %2;\n"
        "@q trap;\n"
        "bra.uni WAIT_%=;\n"
        "DONE_%=:\n}"
        ::"r"(bar), "r"(parity), "n"(SPIN_LIMIT) : "memory");
}
__device__ __forceinline__ unsigned ld_acquire(const unsigned* p) {
    unsigned v;
    asm volatile("ld.acquire.gpu.global.u32 %0, [%1];" : "=r"(v) : "l"(p) : "memory");
    return v;
}
__device__ __forceinline__ void st_release(unsigned* p, unsigned v) {
    asm volatile("st.release.gpu.global.u32 [%0], %1;" ::"l"(p), "r"(v) : "memory");
}
__device__ __forceinline__ unsigned read_epoch() {
    return __shfl_sync(0xffffffffu, *(volatile unsigned*)&g_epoch, 0) + 1;
}
__device__ __forceinline__ void tma_load(uint32_t dst, const CUtensorMap* tm, uint32_t bar, int x, int y) {
    asm volatile(
        "cp.async.bulk.tensor.2d.shared::cluster.global.mbarrier::complete_tx::bytes [%0], [%1, {%3, %4}], [%2];"
        ::"r"(dst), "l"(tm), "r"(bar), "r"(x), "r"(y) : "memory");
}
__device__ __forceinline__ void tma_load_mc(uint32_t dst, const CUtensorMap* tm, uint32_t bar, int x, int y) {
    asm volatile(
        "cp.async.bulk.tensor.2d.shared::cluster.global.mbarrier::complete_tx::bytes.multicast::cluster "
        "[%0], [%1, {%3, %4}], [%2], %5;"
        ::"r"(dst), "l"(tm), "r"(bar), "r"(x), "r"(y), "h"((uint16_t)3) : "memory");
}
__device__ __forceinline__ void prefetch_tm(const CUtensorMap* tm) {
    asm volatile("prefetch.tensormap [%0];" ::"l"(tm) : "memory");
}
__device__ __forceinline__ void l2_prefetch(const void* p, uint32_t bytes) {
    asm volatile("cp.async.bulk.prefetch.L2.global [%0], %1;" ::"l"(p), "r"(bytes) : "memory");
}
__device__ __forceinline__ void bar_sync(int id, int n) { asm volatile("bar.sync %0, %1;" ::"r"(id), "r"(n) : "memory"); }
__device__ __forceinline__ void bar_arrive(int id, int n) { asm volatile("bar.arrive %0, %1;" ::"r"(id), "r"(n) : "memory"); }
__device__ __forceinline__ void wg_fence() { asm volatile("wgmma.fence.sync.aligned;" ::: "memory"); }
__device__ __forceinline__ void wg_commit() { asm volatile("wgmma.commit_group.sync.aligned;" ::: "memory"); }
template <int N>
__device__ __forceinline__ void wg_wait() { asm volatile("wgmma.wait_group.sync.aligned %0;" ::"n"(N) : "memory"); }

__device__ __forceinline__ uint64_t make_desc(uint32_t addr, uint32_t lbo, uint32_t sbo, uint64_t swz) {
    return (uint64_t)((addr & 0x3FFFF) >> 4) | ((uint64_t)(lbo >> 4) << 16) | ((uint64_t)(sbo >> 4) << 32) | (swz << 62);
}

#define ACC8(a, o) "+f"(a[o]), "+f"(a[o + 1]), "+f"(a[o + 2]), "+f"(a[o + 3]), "+f"(a[o + 4]), "+f"(a[o + 5]), "+f"(a[o + 6]), "+f"(a[o + 7])
constexpr uint32_t DHI128 = (1024u >> 4) | (1u << 30);
constexpr uint32_t DHI64 = (512u >> 4) | (2u << 30);
__device__ __forceinline__ void wgmma_n128_rs(float (&d)[64], const uint32_t* a, uint32_t db, int scale_d) {
    asm volatile(
        "{\n.reg .pred p;\n.reg .b64 dd;\nsetp.ne.b32 p, %69, 0;\nmov.b64 dd, {%68, %70};\n"
        "wgmma.mma_async.sync.aligned.m64n128k16.f32.bf16.bf16 "
        "{%0,%1,%2,%3,%4,%5,%6,%7,%8,%9,%10,%11,%12,%13,%14,%15,%16,%17,%18,%19,%20,%21,%22,%23,%24,%25,%26,%27,%28,%29,%30,%31,"
        "%32,%33,%34,%35,%36,%37,%38,%39,%40,%41,%42,%43,%44,%45,%46,%47,%48,%49,%50,%51,%52,%53,%54,%55,%56,%57,%58,%59,%60,%61,%62,%63},"
        "{%64,%65,%66,%67}, dd, p, 1, 1, 1;\n}"
        : ACC8(d, 0), ACC8(d, 8), ACC8(d, 16), ACC8(d, 24), ACC8(d, 32), ACC8(d, 40), ACC8(d, 48), ACC8(d, 56)
        : "r"(a[0]), "r"(a[1]), "r"(a[2]), "r"(a[3]), "r"(db), "r"(scale_d), "n"(DHI128));
}
template <uint32_t HI>
__device__ __forceinline__ void wgmma_n64_rs(float (&d)[32], const uint32_t* a, uint32_t db, int scale_d) {
    asm volatile(
        "{\n.reg .pred p;\n.reg .b64 dd;\nsetp.ne.b32 p, %37, 0;\nmov.b64 dd, {%36, %38};\n"
        "wgmma.mma_async.sync.aligned.m64n64k16.f32.bf16.bf16 "
        "{%0,%1,%2,%3,%4,%5,%6,%7,%8,%9,%10,%11,%12,%13,%14,%15,%16,%17,%18,%19,%20,%21,%22,%23,%24,%25,%26,%27,%28,%29,%30,%31},"
        "{%32,%33,%34,%35}, dd, p, 1, 1, 1;\n}"
        : ACC8(d, 0), ACC8(d, 8), ACC8(d, 16), ACC8(d, 24)
        : "r"(a[0]), "r"(a[1]), "r"(a[2]), "r"(a[3]), "r"(db), "r"(scale_d), "n"(HI));
}
__device__ __forceinline__ void wgmma_n64_ss_tt(float (&d)[32], uint64_t da, uint64_t db, int scale_d) {
    asm volatile(
        "{\n.reg .pred p;\nsetp.ne.b32 p, %34, 0;\n"
        "wgmma.mma_async.sync.aligned.m64n64k16.f32.bf16.bf16 "
        "{%0,%1,%2,%3,%4,%5,%6,%7,%8,%9,%10,%11,%12,%13,%14,%15,%16,%17,%18,%19,%20,%21,%22,%23,%24,%25,%26,%27,%28,%29,%30,%31},"
        "%32, %33, p, 1, 1, 1, 1;\n}"
        : ACC8(d, 0), ACC8(d, 8), ACC8(d, 16), ACC8(d, 24)
        : "l"(da), "l"(db), "r"(scale_d));
}
__device__ __forceinline__ void wgmma_n8_ss_tn(float (&d)[4], uint64_t da, uint64_t db, int scale_d) {
    asm volatile(
        "{\n.reg .pred p;\nsetp.ne.b32 p, %6, 0;\n"
        "wgmma.mma_async.sync.aligned.m64n8k16.f32.bf16.bf16 {%0,%1,%2,%3}, %4, %5, p, 1, 1, 1, 0;\n}"
        : "+f"(d[0]), "+f"(d[1]), "+f"(d[2]), "+f"(d[3])
        : "l"(da), "l"(db), "r"(scale_d));
}
template <int N>
__device__ __forceinline__ void acc_fence(float (&d)[N]) {
#pragma unroll
    for (int i = 0; i < N; i++) asm volatile("" : "+f"(d[i])::"memory");
}
__device__ __forceinline__ void mma16816(float (&c)[4], const uint32_t* a, uint32_t b0, uint32_t b1) {
    asm volatile(
        "mma.sync.aligned.m16n8k16.row.col.f32.bf16.bf16.f32 {%0,%1,%2,%3}, {%4,%5,%6,%7}, {%8,%9}, {%0,%1,%2,%3};"
        : "+f"(c[0]), "+f"(c[1]), "+f"(c[2]), "+f"(c[3])
        : "r"(a[0]), "r"(a[1]), "r"(a[2]), "r"(a[3]), "r"(b0), "r"(b1));
}
__device__ __forceinline__ uint32_t pack_bf16(float lo, float hi) {
    uint32_t r;
    asm("cvt.rn.bf16x2.f32 %0, %1, %2;" : "=r"(r) : "f"(hi), "f"(lo));
    return r;
}
__device__ __forceinline__ float bf_lo(uint32_t v) { return __uint_as_float(v << 16); }
__device__ __forceinline__ float bf_hi(uint32_t v) { return __uint_as_float(v & 0xffff0000u); }
__device__ __forceinline__ float bf16_round(float v) { return __bfloat162float(__float2bfloat16_rn(v)); }
__device__ __forceinline__ float sqrt_fast(float v) {
    float r;
    asm("sqrt.approx.ftz.f32 %0, %1;" : "=f"(r) : "f"(v));
    return r;
}
__device__ __forceinline__ float rcp_fast(float v) {
    float r;
    asm("rcp.approx.ftz.f32 %0, %1;" : "=f"(r) : "f"(v));
    return r;
}
__device__ __forceinline__ float ex2_fast(float v) {
    float r;
    asm("ex2.approx.ftz.f32 %0, %1;" : "=f"(r) : "f"(v));
    return r;
}
struct RowScale { float rho, rl, var; };
__device__ __forceinline__ float phi_f(float a, const RowScale& r) {
    return fmaf(fmaxf(a, 0.f), r.rho, ex2_fast(fminf(a, 0.f) * r.rl) + 1e-6f);
}
__device__ __forceinline__ float swiglu_f(float ga, float ua, const RowScale& r) {
    return (ga * ua) * rcp_fast(fmaf(ex2_fast(-ga * r.rl), r.var, r.var));
}
__device__ __forceinline__ uint4 swiglu8(const float* gp, const float* up, const RowScale& r0, const RowScale& r1) {
    uint4 v;
    v.x = pack_bf16(swiglu_f(gp[0], up[0], r0), swiglu_f(gp[1], up[1], r0));
    v.y = pack_bf16(swiglu_f(gp[2], up[2], r1), swiglu_f(gp[3], up[3], r1));
    v.z = pack_bf16(swiglu_f(gp[4], up[4], r0), swiglu_f(gp[5], up[5], r0));
    v.w = pack_bf16(swiglu_f(gp[6], up[6], r1), swiglu_f(gp[7], up[7], r1));
    return v;
}
__device__ __forceinline__ void red_add2(float* p, float a, float b) {
    asm volatile("red.global.add.v2.f32 [%0], {%1, %2};" ::"l"(p), "f"(a), "f"(b) : "memory");
}
__device__ __forceinline__ void cp_async16(uint32_t dst, const void* src) {
    asm volatile("cp.async.cg.shared.global [%0], [%1], 16;" ::"r"(dst), "l"(src) : "memory");
}

__device__ __forceinline__ int ring_lap(int u) { return (u * 79) >> 10; }
__device__ __forceinline__ int ring_slot(int u) { return u - NST * ring_lap(u); }

__device__ __forceinline__ void mainloop128(float (&acc)[64], const uint32_t (&xa)[128], int u0, uint32_t sb,
                                            uint32_t desc128, int lane, int wg, bool last = false) {
    bar_sync(7 + wg, 256);
#pragma unroll
    for (int kb = 0; kb < 8; kb++) {
        const int st = ring_slot(u0 + kb);
        mbar_wait(sb + BAR_FULL + 8 * st, ring_lap(u0 + kb) & 1);
        wg_fence();
        const uint32_t d = desc128 + st * (STAGE_BYTES >> 4);
#pragma unroll
        for (int ks = 0; ks < 4; ks++) wgmma_n128_rs(acc, &xa[(kb * 4 + ks) * 4], d + ks * 128, (kb | ks) != 0);
        wg_commit();
        if (kb == 7 && !(last && wg == 1)) bar_arrive(8 - wg, 256);
        if (kb > 0) {
            wg_wait<1>();
            if (lane < 2) mbar_arrive_cta(sb + BAR_EMPTY + 8 * ring_slot(u0 + kb - 1), lane);
        }
    }
    wg_wait<0>();
    acc_fence(acc);
    if (lane < 2) mbar_arrive_cta(sb + BAR_EMPTY + 8 * ring_slot(u0 + 7), lane);
}
__device__ __forceinline__ void mainloop64x2(float (&a0)[32], float (&a1)[32], const uint32_t (&xa)[128], int u0,
                                             uint32_t sb, uint32_t desc128, int lane, int wg) {
    bar_sync(7 + wg, 256);
#pragma unroll
    for (int kb = 0; kb < 8; kb++) {
        const int st = ring_slot(u0 + kb);
        mbar_wait(sb + BAR_FULL + 8 * st, ring_lap(u0 + kb) & 1);
        wg_fence();
        const uint32_t d = desc128 + st * (STAGE_BYTES >> 4);
        const uint32_t d2 = d + (8192 >> 4) - ((4096u >> 4) << 16);
#pragma unroll
        for (int ks = 0; ks < 4; ks++) {
            wgmma_n64_rs<DHI128>(a0, &xa[(kb * 4 + ks) * 4], d + ks * 128, (kb | ks) != 0);
            wgmma_n64_rs<DHI64>(a1, &xa[(kb * 4 + ks) * 4], d2 + ks * 64, (kb | ks) != 0);
        }
        wg_commit();
        if (kb == 7) bar_arrive(8 - wg, 256);
        if (kb > 0) {
            wg_wait<1>();
            if (lane < 2) mbar_arrive_cta(sb + BAR_EMPTY + 8 * ring_slot(u0 + kb - 1), lane);
        }
    }
    wg_wait<0>();
    acc_fence(a0);
    acc_fence(a1);
    if (lane < 2) mbar_arrive_cta(sb + BAR_EMPTY + 8 * ring_slot(u0 + 7), lane);
}

__global__ void __cluster_dims__(2, 1, 1) __launch_bounds__(384, 1)
fused_kernel(const __grid_constant__ CUtensorMap tm_x, const __grid_constant__ CUtensorMap tm_qkv,
             const __grid_constant__ CUtensorMap tm_w1, const __grid_constant__ CUtensorMap tm_w3,
             const __grid_constant__ CUtensorMap tm_w1h, const __grid_constant__ CUtensorMap tm_w3h,
             const __grid_constant__ CUtensorMap tm_w2, const __grid_constant__ CUtensorMap tm_w2h,
             const __grid_constant__ CUtensorMap tm_wo, const __nv_bfloat16* __restrict__ xg,
             __nv_bfloat16* __restrict__ outg, const char* __restrict__ p_qkv, const char* __restrict__ p_w1,
             const char* __restrict__ p_w3, const char* __restrict__ p_w2, const char* __restrict__ p_wo) {
    extern __shared__ __align__(1024) uint8_t smem[];
    const uint32_t sb = smem_u32(smem);
    const int tid = threadIdx.x;
    const int warp = tid >> 5, lane = tid & 31;
    const int rank = blockIdx.x & 1;
    const int pair = blockIdx.x >> 1;
    const int c = pair & 7;
    const int m = (pair >> 3) * 2 + rank;
    const int m2 = (pair >> 3) * 2 + (c & 1);
    const int j2 = c >> 1;

    TS(tid >> 7, 0);
    if (tid == 256) {
#pragma unroll
        for (int i = 0; i < 8; i++) mbar_init(sb + BAR_XFULL + 8 * i, 1);
        asm volatile("fence.proxy.async.shared::cta;" ::: "memory");
#pragma unroll
        for (int kb = 0; kb < 8; kb++) {
            mbar_expect_tx(sb + BAR_XFULL + 8 * kb, 16384);
            tma_load(sb + (XST0 + kb) * STAGE_BYTES, &tm_x, sb + BAR_XFULL + 8 * kb, kb * 64, m * 128);
        }
        TS(2, 21);
    } else if (tid == 0) {
#pragma unroll
        for (int i = 0; i < NST; i++) mbar_init(sb + BAR_FULL + 8 * i, 1);
        asm volatile("fence.mbarrier_init.release.cluster;" ::: "memory");
    } else if (tid == 32) {
#pragma unroll
        for (int i = 0; i < NST; i++) mbar_init(sb + BAR_EMPTY + 8 * i, 16);
        asm volatile("fence.mbarrier_init.release.cluster;" ::: "memory");
    } else if (tid == 64) {
#pragma unroll
        for (int i = 0; i < 10; i++) mbar_init(sb + BAR_KVREADY + 8 * i, 1);
        mbar_expect_tx(sb + BAR_XCHG, 32768);
        asm volatile("fence.mbarrier_init.release.cluster;" ::: "memory");
    } else if (tid == 96) {
#pragma unroll
        for (int i = 10; i < 22; i++) mbar_init(sb + BAR_KVREADY + 8 * i, 1);
        asm volatile("fence.mbarrier_init.release.cluster;" ::: "memory");
    } else if (tid == 288) {
        prefetch_tm(&tm_qkv);
        prefetch_tm(rank ? &tm_w3 : &tm_w1);
        prefetch_tm(&tm_w1h);
        prefetch_tm(&tm_w3h);
        prefetch_tm(&tm_w2);
        prefetch_tm(&tm_w2h);
        prefetch_tm(&tm_wo);
    } else if (tid >= 320) {
        ((uint32_t*)(smem + OFF_ONES))[tid - 320] = 0x3F803F80u;
        asm volatile("fence.proxy.async.shared::cta;" ::: "memory");
    }
    __syncthreads();
    TS(tid >> 7, 22);
    asm volatile("barrier.cluster.arrive.relaxed.aligned;\nbarrier.cluster.wait.acquire.aligned;" ::: "memory");

    if (warp >= 8) {
        asm volatile("setmaxnreg.dec.sync.aligned.u32 40;");
        if (warp == 8) {
            if (lane == 0) {
                int st = 0;
                uint32_t lap = 0;
                for (int it = 0; it < 40; it++) {
                    const int tile = it >> 3, kb = it & 7;
                    const uint32_t full = sb + BAR_FULL + 8 * st;
                    mbar_wait(sb + BAR_EMPTY + 8 * st, (st >= XST0) ? (lap & 1) : ((lap & 1) ^ 1));
                    mbar_expect_tx(full, STAGE_BYTES);
                    const uint32_t dst = sb + st * STAGE_BYTES;
                    if (tile == 0) {
                        tma_load_mc(dst + rank * 8192, &tm_qkv, full, 512 + 512 * rank + 64 * c, kb * 64);
                    } else if (tile != 3) {
                        tma_load_mc(dst + rank * 8192, rank ? &tm_w3 : &tm_w1, full, 224 * c + 64 * (tile == 4 ? 2 : tile - 1), kb * 64);
                    } else if (rank == 0) {
                        tma_load_mc(dst, &tm_qkv, full, 64 * c, kb * 64);
                    } else {
                        tma_load_mc(dst + 8192, &tm_w1h, full, 224 * c + 192, kb * 64);
                        tma_load_mc(dst + 12288, &tm_w3h, full, 224 * c + 192, kb * 64);
                    }
                    if (++st == NST) { st = 0; lap++; }
                    if (it == 7) {
                        mbar_wait(sb + BAR_EMPTY + 8 * SCR0, 0);
                        mbar_arrive(sb + BAR_FULL + 8 * SCR0);
                        mbar_wait(sb + BAR_EMPTY + 8 * (SCR0 + 1), 0);
                        mbar_arrive(sb + BAR_FULL + 8 * (SCR0 + 1));
                        st += 2;
                    }
                }
                TS(2, 1);
                for (int b = 0; b < 18; b++) {
                    const uint32_t full = sb + BAR_FULL + 8 * st;
                    const uint32_t dst = sb + st * STAGE_BYTES;
                    mbar_wait(sb + BAR_EMPTY + 8 * st, (st >= XST0) ? (lap & 1) : ((lap & 1) ^ 1));
                    mbar_expect_tx(full, STAGE_BYTES);
                    if (b < 8 || b >= 14) {
                        const int row = (b < 8) ? 224 * (4 * rank + (b & 3)) + 64 * (b >> 2) : 224 * (4 * rank + b - 14) + 128;
                        tma_load(dst, &tm_w2, full, 128 * j2, row);
                        tma_load(dst + 8192, &tm_w2, full, 128 * j2 + 64, row);
                    } else if (b < 10) {
                        const int row = 224 * (4 * rank + 2 * (b - 8)) + 192;
                        tma_load(dst, &tm_w2h, full, 128 * j2, row);
                        tma_load(dst + 4096, &tm_w2h, full, 128 * j2, row + 224);
                        tma_load(dst + 8192, &tm_w2h, full, 128 * j2 + 64, row);
                        tma_load(dst + 12288, &tm_w2h, full, 128 * j2 + 64, row + 224);
                    } else {
                        const int row = 64 * (4 * rank + (b - 10));
                        tma_load(dst, &tm_wo, full, 128 * j2, row);
                        tma_load(dst + 8192, &tm_wo, full, 128 * j2 + 64, row);
                    }
                    TS(2, 2 + b);
                    if (++st == NST) { st = 0; lap++; }
                }
                mbar_wait(sb + BAR_EMPTY + 8 * SCR0, lap & 1);
                mbar_wait(sb + BAR_EMPTY + 8 * (SCR0 + 1), lap & 1);
                mbar_arrive_cta(sb + BAR_XRDY, rank ^ 1);
            }
        } else if (warp < 11) {
            const int wg = warp - 9;
            const unsigned epoch = read_epoch();
            bar_arrive(9, 96);
            for (int t = 0; t < 5; t++) {
                bar_sync(3 + wg * 2 + (t & 1), 160);
                if (lane == 0) {
                    if (t == 0) asm volatile("red.release.gpu.global.add.u32 [%0], 1;" ::"l"(&g_kvcnt[c]) : "memory");
                    else st_release(&g_a2flag[((m * 8 + c) * 4 + (t - 1)) * 2 + wg], epoch);
                }
                TSW(3, 2 * t + wg);
            }
        } else {
            const unsigned epoch = read_epoch();
            bar_sync(9, 96);
            if (lane == 0) {
                const unsigned tk = atomicInc(&g_ticket, 127u);
                if (tk == 127u) *(volatile unsigned*)&g_epoch = epoch;
            }
            if (lane == 0) *(volatile unsigned*)(smem + OFF_EPOCH) = epoch;
            __syncwarp();
            if (lane == 0) mbar_arrive(sb + BAR_EPOCH);
            if (lane < 17) g_kvacc[(((epoch & 1) ^ 1) * 8 + c) * 272 + 17 * m + lane] = make_float4(0.f, 0.f, 0.f, 0.f);
            {
                unsigned n = 0;
                while ((int)(ld_acquire(&g_kvcnt[c]) - 32u * epoch) < 0) {
                    __nanosleep(200);
                    if (++n > SPIN_LIMIT) asm volatile("trap;");
                }
            }
            TSW(4, 0);
            const int g = lane >> 2, t = lane & 3;
            const float* ks = (const float*)(g_kvacc + ((epoch & 1) * 8 + c) * 272) + 32 * t + g;
            uint2* kf = (uint2*)(smem + OFF_KVFRAG) + lane;
#pragma unroll 2
            for (int hh = 0; hh < 4; hh++) {
                const float* k = ks + hh * 272;
                const float a0 = __ldcg(k), a1 = __ldcg(k + 16), a2 = __ldcg(k + 128), a3 = __ldcg(k + 144);
                const float b0 = __ldcg(k + 8), b1 = __ldcg(k + 24), b2 = __ldcg(k + 136), b3 = __ldcg(k + 152);
                const float2 z0 = __ldcg((const float2*)(k - g - 30 * t + 256)), z1 = __ldcg((const float2*)(k - g - 30 * t + 264));
                kf[(hh * 3 + 0) * 32] = make_uint2(pack_bf16(a0, a1), pack_bf16(a2, a3));
                kf[(hh * 3 + 1) * 32] = make_uint2(pack_bf16(b0, b1), pack_bf16(b2, b3));
                kf[(hh * 3 + 2) * 32] = make_uint2(pack_bf16(z0.x, z0.y), pack_bf16(z1.x, z1.y));
            }
            __syncwarp();
            if (lane == 0) mbar_arrive(sb + BAR_KVREADY);
            TSW(4, 4);
            const unsigned* fl = g_a2flag + (m2 * 8 + rank * 4) * 8 + lane;
            unsigned ready = 0;
            for (int b = 0; b < 18; b++) {
                const unsigned need = (b < 8) ? (3u << ((b & 3) * 8 + (b >> 2) * 2)) : (b < 10) ? (0x3030u << ((b - 8) * 16))
                                      : (b < 14) ? 0u : (0xC0u << ((b - 14) * 8));
                unsigned n = 0;
                while ((ready & need) != need) {
                    ready = __ballot_sync(0xffffffffu, ld_acquire(fl) == epoch);
                    if (++n > SPIN_LIMIT) asm volatile("trap;");
                }
                if (lane == 0) mbar_arrive(sb + BAR_AREADY + 8 * b);
                TSW(5, b);
            }
        }
    } else {
        asm volatile("setmaxnreg.inc.sync.aligned.u32 232;");
        const int wg = warp >> 2, w = warp & 3;
        const int g = lane >> 2, t = lane & 3;
        float acc[64];
        uint32_t xa[128];
        float rho0, rho1;
        RowScale r0, r1;

        TS(wg, 1);
        {
            const int row = wg * 64 + w * 16 + (lane & 7) + ((lane >> 3) & 1) * 8;
            const uint32_t rbase = sb + XST0 * STAGE_BYTES + row * 128;
            const int hi = lane >> 4, r7 = lane & 7;
            float sm[2][4], c0[2][4], c1[2][4];
#pragma unroll
            for (int i = 0; i < 8; i++) { sm[i >> 2][i & 3] = 0.f; c0[i >> 2][i & 3] = 0.f; c1[i >> 2][i & 3] = 0.f; }
            if (wg == 1) bar_arrive(7, 256);
#pragma unroll
            for (int kb = 0; kb < 8; kb++) {
                mbar_wait(sb + BAR_XFULL + 8 * kb, 0);
#pragma unroll
                for (int ks = 0; ks < 4; ks++) {
                    uint32_t* a = &xa[(kb * 4 + ks) * 4];
                    const uint32_t addr = rbase + kb * STAGE_BYTES + (((2 * ks + hi) ^ r7) << 4);
                    asm volatile("ldmatrix.sync.aligned.m8n8.x4.shared.b16 {%0,%1,%2,%3}, [%4];"
                                 : "=r"(a[0]), "=r"(a[1]), "=r"(a[2]), "=r"(a[3]) : "r"(addr) : "memory");
                    mma16816(sm[ks & 1], a, 0x3F803F80u, 0x3F803F80u);
                    mma16816(c0[ks & 1], a, a[0], a[2]);
                    mma16816(c1[ks & 1], a, a[1], a[3]);
                }
            }
            TS(wg, 2);
            const float mean0 = (sm[0][0] + sm[1][0]) * (1.f / 512.f);
            const float mean1 = (sm[0][2] + sm[1][2]) * (1.f / 512.f);
            __syncwarp();
            if (lane < 16) mbar_arrive_cta(sb + BAR_EMPTY + 8 * (XST0 + (lane >> 1)), lane & 1);
            const __nv_bfloat162 mb0 = __float2bfloat162_rn(mean0), mb1 = __float2bfloat162_rn(mean1);
#pragma unroll
            for (int i = 0; i < 128; i++) {
                __nv_bfloat162 v = *reinterpret_cast<__nv_bfloat162*>(&xa[i]);
                v = __hsub2(v, (i & 1) ? mb1 : mb0);
                xa[i] = *reinterpret_cast<uint32_t*>(&v);
            }
            const float d0 = (g & 1) ? c0[0][1] + c0[1][1] : c0[0][0] + c0[1][0];
            const float d1 = (g & 1) ? c1[0][3] + c1[1][3] : c1[0][2] + c1[1][2];
            const int src = (lane & ~3) | (g >> 1);
            const float var0 = fmaxf(__shfl_sync(0xffffffffu, d0, src) * (1.f / 512.f) - mean0 * mean0, 0.f);
            const float var1 = fmaxf(__shfl_sync(0xffffffffu, d1, src) * (1.f / 512.f) - mean1 * mean1, 0.f);
            const float sd0 = bf16_round(sqrt_fast(bf16_round(bf16_round(var0) + 1e-5f)));
            const float sd1 = bf16_round(sqrt_fast(bf16_round(bf16_round(var1) + 1e-5f)));
            rho0 = rcp_fast(sd0);
            rho1 = rcp_fast(sd1);
            r0.rho = rho0; r0.rl = rho0 * 1.4426950408889634f; r0.var = sd0 * sd0;
            r1.rho = rho1; r1.rl = rho1 * 1.4426950408889634f; r1.var = sd1 * sd1;
        }

        TS(wg, 3);
        const uint32_t desc128 = ((sb & 0x3FFFF) >> 4) | ((8192u >> 4) << 16);
        uint4* a2w = g_A2 + (size_t)((m * 2 + (c >> 2)) * 18) * 4 * 256 + warp * 32 + lane;
        const int cc = c & 3;

        {
            mainloop128(acc, xa, 0, sb, desc128, lane, wg);
            TS(wg, 4);
            {
                TS(wg, 24);
                const uint32_t pkb = sb + (SCR0 + wg) * STAGE_BYTES;
                mbar_wait(sb + BAR_FULL + 8 * (SCR0 + wg), 0);
                const uint32_t ra = pkb + (w * 16 + g) * 128 + t * 4;
#pragma unroll
                for (int nb = 0; nb < 8; nb++) {
                    const uint32_t off = (uint32_t)((nb ^ g) << 4);
                    uint32_t p0 = pack_bf16(phi_f(acc[nb * 4], r0), phi_f(acc[nb * 4 + 1], r0));
                    uint32_t p1 = pack_bf16(phi_f(acc[nb * 4 + 2], r1), phi_f(acc[nb * 4 + 3], r1));
                    uint32_t v0 = pack_bf16(acc[32 + nb * 4] * rho0, acc[32 + nb * 4 + 1] * rho0);
                    uint32_t v1 = pack_bf16(acc[32 + nb * 4 + 2] * rho1, acc[32 + nb * 4 + 3] * rho1);
                    asm volatile("st.shared.u32 [%0], %1;" ::"r"(ra + off), "r"(p0) : "memory");
                    asm volatile("st.shared.u32 [%0], %1;" ::"r"(ra + off + 1024), "r"(p1) : "memory");
                    asm volatile("st.shared.u32 [%0], %1;" ::"r"(ra + off + 8192), "r"(v0) : "memory");
                    asm volatile("st.shared.u32 [%0], %1;" ::"r"(ra + off + 8192 + 1024), "r"(v1) : "memory");
                }
                TS(wg, 25);
                asm volatile("fence.proxy.async.shared::cta;" ::: "memory");
                bar_sync(1 + wg, 128);
                TS(wg, 26);
                const uint64_t da = make_desc(pkb, 8192, 1024, 1);
                const uint64_t db = make_desc(pkb + 8192, 8192, 1024, 1);
                const uint64_t d1 = make_desc(sb + OFF_ONES, 128, 128, 0);
                float kva[32], za[4];
                wg_fence();
#pragma unroll
                for (int ks = 0; ks < 4; ks++) {
                    wgmma_n64_ss_tt(kva, da + ks * 128, db + ks * 128, ks != 0);
                    wgmma_n8_ss_tn(za, da + ks * 128, d1, ks != 0);
                }
                wg_commit();
                wg_wait<0>();
                acc_fence(kva);
                acc_fence(za);
                if (lane < 4) mbar_arrive_cta(sb + BAR_EMPTY + 8 * (SCR0 + (lane >> 1)), lane & 1);
                TS(wg, 27);
                float o[8];
#pragma unroll
                for (int i = 0; i < 8; i++)
                    o[i] = (w == 0) ? kva[i] : (w == 1) ? kva[8 + i] : (w == 2) ? kva[16 + i] : kva[24 + i];
                mbar_wait(sb + BAR_EPOCH, 0);
                const unsigned par = *(volatile unsigned*)(smem + OFF_EPOCH) & 1;
                float* dst = (float*)(g_kvacc + (par * 8 + c) * 272) + w * 272 + g * 16 + 2 * t;
                red_add2(dst, o[0], o[1]);
                red_add2(dst + 128, o[2], o[3]);
                red_add2(dst + 8, o[4], o[5]);
                red_add2(dst + 136, o[6], o[7]);
                if (t == 0) {
                    atomicAdd(dst - g * 15 + 256, za[0]);
                    atomicAdd(dst - g * 15 + 264, za[2]);
                }
            }
            bar_arrive(3 + wg * 2, 160);
            TS(wg, 5);
        }
#pragma unroll
        for (int tile = 1; tile < 3; tile++) {
            mainloop128(acc, xa, 2 + 8 * tile, sb, desc128, lane, wg);
            TS(wg, 4 + 2 * tile);
            uint4* dst = a2w + (size_t)((4 * (tile - 1) + cc) * 4) * 256;
#pragma unroll
            for (int ks = 0; ks < 4; ks++) dst[ks * 256] = swiglu8(&acc[ks * 8], &acc[32 + ks * 8], r0, r1);
            bar_arrive(3 + wg * 2 + (tile & 1), 160);
            TS(wg, 5 + 2 * tile);
        }
        {
            float qa[32], gu[32];
            mainloop64x2(qa, gu, xa, 26, sb, desc128, lane, wg);
            TS(wg, 10);
            uint4* dst = a2w + (size_t)((8 + (cc >> 1)) * 4 + 2 * (cc & 1)) * 256;
#pragma unroll
            for (int ks = 0; ks < 2; ks++) dst[ks * 256] = swiglu8(&gu[ks * 8], &gu[16 + ks * 8], r0, r1);
            TS(wg, 13);
            mbar_wait(sb + BAR_KVREADY, 0);
            TS(wg, 14);
            const uint2* kf = (const uint2*)(smem + OFF_KVFRAG);
            dst = a2w + (size_t)((10 + cc) * 4) * 256;
#pragma unroll
            for (int hh = 0; hh < 4; hh++) {
                const float* q = &qa[hh * 8];
                uint32_t a[4];
                a[0] = pack_bf16(phi_f(q[0], r0), phi_f(q[1], r0));
                a[1] = pack_bf16(phi_f(q[2], r1), phi_f(q[3], r1));
                a[2] = pack_bf16(phi_f(q[4], r0), phi_f(q[5], r0));
                a[3] = pack_bf16(phi_f(q[6], r1), phi_f(q[7], r1));
                float n0[4] = {0.f, 0.f, 0.f, 0.f}, n1[4] = {0.f, 0.f, 0.f, 0.f}, dn[4] = {0.f, 0.f, 0.f, 0.f};
                const uint2 b0 = kf[(hh * 3 + 0) * 32 + lane], b1 = kf[(hh * 3 + 1) * 32 + lane],
                            bz = kf[(hh * 3 + 2) * 32 + lane];
                mma16816(n0, a, b0.x, b0.y);
                mma16816(n1, a, b1.x, b1.y);
                mma16816(dn, a, bz.x, bz.y);
                const float i0 = rcp_fast(dn[0] + 1e-6f), i1 = rcp_fast(dn[2] + 1e-6f);
                uint4 v;
                v.x = pack_bf16(n0[0] * i0, n0[1] * i0);
                v.y = pack_bf16(n0[2] * i1, n0[3] * i1);
                v.z = pack_bf16(n1[0] * i0, n1[1] * i0);
                v.w = pack_bf16(n1[2] * i1, n1[3] * i1);
                dst[hh * 256] = v;
            }
            bar_arrive(3 + wg * 2 + 1, 160);
            TS(wg, 11);
        }
        const uint4* a2r = g_A2 + (size_t)((m2 * 2 + rank) * 18) * 4 * 256 + warp * 32 + lane;
        uint4 af[APF + 1][4];
        {
            mainloop128(acc, xa, 34, sb, desc128, lane, wg, true);
            TS(wg, 12);
#pragma unroll
            for (int b = 0; b < APF; b++) {
                mbar_wait(sb + BAR_AREADY + 8 * b, 0);
#pragma unroll
                for (int ks = 0; ks < 4; ks++) af[b][ks] = __ldcg(a2r + (b * 4 + ks) * 256);
            }
            uint4* dst = a2w + (size_t)((14 + cc) * 4) * 256;
#pragma unroll
            for (int ks = 0; ks < 4; ks++) dst[ks * 256] = swiglu8(&acc[ks * 8], &acc[32 + ks * 8], r0, r1);
            bar_arrive(3 + wg * 2, 160);
            TS(wg, 15);
        }

        {
            float ao[32], ap[32];
            const uint32_t dso = desc128 + rank * 512, dsp = desc128 + (rank ^ 1) * 512;
            TS(wg, 16);
#pragma unroll
            for (int b = 0; b < 18; b++) {
                if (b == 14) TS(wg, 17);
                mbar_wait(sb + BAR_FULL + 8 * ring_slot(42 + b), ring_lap(42 + b) & 1);
                wg_fence();
                const uint32_t so = ring_slot(42 + b) * (STAGE_BYTES >> 4);
#pragma unroll
                for (int ks = 0; ks < 4; ks++) {
                    const uint32_t* a = reinterpret_cast<const uint32_t*>(&af[b % (APF + 1)][ks]);
                    wgmma_n64_rs<DHI128>(ap, a, dsp + so + ks * 128, (b | ks) != 0);
                    if (b < 14) wgmma_n64_rs<DHI128>(ao, a, dso + so + ks * 128, (b | ks) != 0);
                }
                wg_commit();
                if (b > 0 && b < 14) {
                    wg_wait<1>();
                    if (lane < 2) mbar_arrive(sb + BAR_EMPTY + 8 * ring_slot(41 + b));
                }
                if (b + APF < 18) {
                    mbar_wait(sb + BAR_AREADY + 8 * (b + APF), 0);
#pragma unroll
                    for (int ks = 0; ks < 4; ks++)
                        af[(b + APF) % (APF + 1)][ks] = __ldcg(a2r + ((b + APF) * 4 + ks) * 256);
                }
            }
#pragma unroll
            for (int b = 14; b < 18; b++) {
                const uint32_t so = ring_slot(42 + b) * (STAGE_BYTES >> 4);
#pragma unroll
                for (int ks = 0; ks < 4; ks++)
                    wgmma_n64_rs<DHI128>(ao, reinterpret_cast<const uint32_t*>(&af[b % (APF + 1)][ks]), dso + so + ks * 128, 1);
            }
            wg_commit();
            const int row0 = m2 * 128 + wg * 64 + w * 16 + g;
            const int col0 = j2 * 128 + rank * 64 + 2 * t;
            uint32_t xr[16];
#pragma unroll
            for (int nb = 0; nb < 8; nb++) {
                xr[2 * nb] = __ldg((const uint32_t*)(xg + (size_t)row0 * 512 + col0 + nb * 8));
                xr[2 * nb + 1] = __ldg((const uint32_t*)(xg + (size_t)(row0 + 8) * 512 + col0 + nb * 8));
            }
            uint32_t rdst, rbar;
            asm volatile("mapa.shared::cluster.u32 %0, %1, %2;"
                         : "=r"(rdst) : "r"(sb + (SCR0 + wg) * STAGE_BYTES + (tid & 127) * 16), "r"(rank ^ 1));
            asm volatile("mapa.shared::cluster.u32 %0, %1, %2;" : "=r"(rbar) : "r"(sb + BAR_XCHG), "r"(rank ^ 1));
            mbar_wait(sb + BAR_XRDY, 0);
            wg_wait<1>();
            acc_fence(ap);
            TS(wg, 18);
#pragma unroll
            for (int i = 0; i < 8; i++)
                asm volatile("st.async.shared::cluster.mbarrier::complete_tx::bytes.v4.f32 [%0], {%1,%2,%3,%4}, [%5];"
                             ::"r"(rdst + i * 2048), "f"(ap[4 * i]), "f"(ap[4 * i + 1]), "f"(ap[4 * i + 2]), "f"(ap[4 * i + 3]),
                             "r"(rbar) : "memory");
            wg_wait<0>();
            acc_fence(ao);
            mbar_wait(sb + BAR_XCHG, 0);
            TS(wg, 19);
            const float4* rx = (const float4*)(smem + (SCR0 + wg) * STAGE_BYTES) + (tid & 127);
#pragma unroll
            for (int nb = 0; nb < 8; nb++) {
                const float4 p = rx[nb * 128];
                const uint32_t o0 = pack_bf16(ao[4 * nb] + p.x + bf_lo(xr[2 * nb]), ao[4 * nb + 1] + p.y + bf_hi(xr[2 * nb]));
                const uint32_t o1 = pack_bf16(ao[4 * nb + 2] + p.z + bf_lo(xr[2 * nb + 1]), ao[4 * nb + 3] + p.w + bf_hi(xr[2 * nb + 1]));
                *(uint32_t*)(outg + (size_t)row0 * 512 + col0 + nb * 8) = o0;
                *(uint32_t*)(outg + (size_t)(row0 + 8) * 512 + col0 + nb * 8) = o1;
            }
        }
        TS(wg, 20);
    }
}

typedef CUresult (*EncodeFn)(CUtensorMap*, CUtensorMapDataType, cuuint32_t, void*, const cuuint64_t*, const cuuint64_t*,
                             const cuuint32_t*, const cuuint32_t*, CUtensorMapInterleave, CUtensorMapSwizzle,
                             CUtensorMapL2promotion, CUtensorMapFloatOOBfill);

void make_map(EncodeFn enc, CUtensorMap* tm, const void* ptr, int rows, int cols, int box_rows, int box_cols,
              CUtensorMapSwizzle swz) {
    cuuint64_t dims[2] = {(cuuint64_t)cols, (cuuint64_t)rows};
    cuuint64_t strides[1] = {(cuuint64_t)cols * 2};
    cuuint32_t box[2] = {(cuuint32_t)box_cols, (cuuint32_t)box_rows};
    cuuint32_t es[2] = {1, 1};
    enc(tm, CU_TENSOR_MAP_DATA_TYPE_BFLOAT16, 2, const_cast<void*>(ptr), dims, strides, box, es,
        CU_TENSOR_MAP_INTERLEAVE_NONE, swz, CU_TENSOR_MAP_L2_PROMOTION_L2_256B, CU_TENSOR_MAP_FLOAT_OOB_FILL_NONE);
}

}

extern "C" void kernel_launch(void* const* d_in, const int* in_sizes, int n_in, void* d_out, int out_size) {
    (void)in_sizes; (void)n_in; (void)out_size;
    static EncodeFn enc = nullptr;
    if (!enc) {
        void* fn = nullptr;
        cudaDriverEntryPointQueryResult qr;
        cudaGetDriverEntryPoint("cuTensorMapEncodeTiled", &fn, cudaEnableDefault, &qr);
        enc = (EncodeFn)fn;
        cudaFuncSetAttribute(fused_kernel, cudaFuncAttributeMaxDynamicSharedMemorySize, SMEM_BYTES);
    }
    const void* x = d_in[0];
    const void* wqkv = d_in[1];
    const void* wo = d_in[2];
    const void* w1 = d_in[4];
    const void* w3 = d_in[5];
    const void* w2 = d_in[6];
    CUtensorMap tx, tqkv, t1, t3, t1h, t3h, t2, t2h, two;
    make_map(enc, &tx, x, 2048, 512, 128, 64, CU_TENSOR_MAP_SWIZZLE_128B);
    make_map(enc, &tqkv, wqkv, 512, 1536, 64, 64, CU_TENSOR_MAP_SWIZZLE_128B);
    make_map(enc, &t1, w1, 512, 1792, 64, 64, CU_TENSOR_MAP_SWIZZLE_128B);
    make_map(enc, &t3, w3, 512, 1792, 64, 64, CU_TENSOR_MAP_SWIZZLE_128B);
    make_map(enc, &t1h, w1, 512, 1792, 64, 32, CU_TENSOR_MAP_SWIZZLE_64B);
    make_map(enc, &t3h, w3, 512, 1792, 64, 32, CU_TENSOR_MAP_SWIZZLE_64B);
    make_map(enc, &t2, w2, 1792, 512, 64, 64, CU_TENSOR_MAP_SWIZZLE_128B);
    make_map(enc, &t2h, w2, 1792, 512, 32, 64, CU_TENSOR_MAP_SWIZZLE_128B);
    make_map(enc, &two, wo, 512, 512, 64, 64, CU_TENSOR_MAP_SWIZZLE_128B);
    fused_kernel<<<128, 384, SMEM_BYTES>>>(tx, tqkv, t1, t3, t1h, t3h, t2, t2h, two, (const __nv_bfloat16*)x,
                                           (__nv_bfloat16*)d_out, (const char*)wqkv, (const char*)w1, (const char*)w3,
                                           (const char*)w2, (const char*)wo);
}
```

```cpp
#include <cuda_runtime.h>
#include <cuda_bf16.h>
#include <cuda.h>
#include <stdint.h>

namespace {

constexpr int NST = 13;
constexpr int STAGE_BYTES = 16384;
constexpr int XST0 = 5;
constexpr int SCR0 = 8;
constexpr int OFF_MISC = NST * STAGE_BYTES;
constexpr int OFF_KVFRAG = OFF_MISC;
constexpr int OFF_ONES = OFF_MISC + 3072;
constexpr int OFF_BARS = OFF_MISC + 3328;
constexpr int BAR_FULL = OFF_BARS;
constexpr int BAR_EMPTY = BAR_FULL + 8 * NST;
constexpr int BAR_XFULL = BAR_EMPTY + 8 * NST;
constexpr int BAR_KVREADY = BAR_XFULL + 64;
constexpr int BAR_XCHG = BAR_KVREADY + 8;
constexpr int BAR_EPOCH = BAR_XCHG + 8;
constexpr int BAR_XRDY = BAR_EPOCH + 8;
constexpr int OFF_EPOCH = BAR_XRDY + 8;
constexpr int OFF_ZERO = OFF_MISC + 4096;
constexpr int SMEM_BYTES = OFF_MISC + 8192;

constexpr int APF = 5;
constexpr unsigned SPIN_LIMIT = 1u << 24;

constexpr int A2_N = 16 * 2 * 18 * 4 * 256;
__device__ uint4 g_A2[2 * A2_N];
__device__ float4 g_kvacc[2 * 8 * 272];
__device__ unsigned g_kvcnt[8];
__device__ unsigned g_epoch;
__device__ unsigned g_ticket;

#define TS(role, i)
#define TSW(role, i)

__device__ __forceinline__ uint32_t smem_u32(const void* p) { return (uint32_t)__cvta_generic_to_shared(p); }
__device__ __forceinline__ void mbar_init(uint32_t bar, uint32_t cnt) {
    asm volatile("mbarrier.init.shared::cta.b64 [%0], %1;" ::"r"(bar), "r"(cnt) : "memory");
}
__device__ __forceinline__ void mbar_expect_tx(uint32_t bar, uint32_t bytes) {
    asm volatile("mbarrier.arrive.expect_tx.shared::cta.b64 _, [%0], %1;" ::"r"(bar), "r"(bytes) : "memory");
}
__device__ __forceinline__ void mbar_arrive(uint32_t bar) {
    asm volatile("mbarrier.arrive.shared::cta.b64 _, [%0];" ::"r"(bar) : "memory");
}
__device__ __forceinline__ void mbar_arrive_cta(uint32_t bar, uint32_t cta) {
    asm volatile(
        "{\n.reg .b32 ra;\nmapa.shared::cluster.u32 ra, %0, %1;\n"
        "mbarrier.arrive.shared::cluster.b64 _, [ra];\n}" ::"r"(bar), "r"(cta) : "memory");
}
__device__ __forceinline__ void mbar_wait(uint32_t bar, uint32_t parity) {
    asm volatile(
        "{\n.reg .pred p, q;\n.reg .u32 n;\nmov.u32 n, 0;\n"
        "WAIT_%=:\n"
        "mbarrier.try_wait.parity.shared::cta.b64 p, [%0], %1;\n"
        "@p bra.uni DONE_%=;\n"
        "add.u32 n, n, 1;\n"
        "setp.gt.u32 q, n, %2;\n"
        "@q trap;\n"
        "bra.uni WAIT_%=;\n"
        "DONE_%=:\n}"
        ::"r"(bar), "r"(parity), "n"(SPIN_LIMIT) : "memory");
}
__device__ __forceinline__ unsigned ld_acquire(const unsigned* p) {
    unsigned v;
    asm volatile("ld.acquire.gpu.global.u32 %0, [%1];" : "=r"(v) : "l"(p) : "memory");
    return v;
}
__device__ __forceinline__ void st_release(unsigned* p, unsigned v) {
    asm volatile("st.release.gpu.global.u32 [%0], %1;" ::"l"(p), "r"(v) : "memory");
}
__device__ __forceinline__ unsigned read_epoch() {
    return __shfl_sync(0xffffffffu, *(volatile unsigned*)&g_epoch, 0) + 1;
}
__device__ __forceinline__ void tma_load(uint32_t dst, const CUtensorMap* tm, uint32_t bar, int x, int y) {
    asm volatile(
        "cp.async.bulk.tensor.2d.shared::cluster.global.mbarrier::complete_tx::bytes [%0], [%1, {%3, %4}], [%2];"
        ::"r"(dst), "l"(tm), "r"(bar), "r"(x), "r"(y) : "memory");
}
__device__ __forceinline__ void tma_load_mc(uint32_t dst, const CUtensorMap* tm, uint32_t bar, int x, int y) {
    asm volatile(
        "cp.async.bulk.tensor.2d.shared::cluster.global.mbarrier::complete_tx::bytes.multicast::cluster "
        "[%0], [%1, {%3, %4}], [%2], %5;"
        ::"r"(dst), "l"(tm), "r"(bar), "r"(x), "r"(y), "h"((uint16_t)3) : "memory");
}
__device__ __forceinline__ void prefetch_tm(const CUtensorMap* tm) {
    asm volatile("prefetch.tensormap [%0];" ::"l"(tm) : "memory");
}
__device__ __forceinline__ void l2_prefetch(const void* p, uint32_t bytes) {
    asm volatile("cp.async.bulk.prefetch.L2.global [%0], %1;" ::"l"(p), "r"(bytes) : "memory");
}
__device__ __forceinline__ void bar_sync(int id, int n) { asm volatile("bar.sync %0, %1;" ::"r"(id), "r"(n) : "memory"); }
__device__ __forceinline__ void bar_arrive(int id, int n) { asm volatile("bar.arrive %0, %1;" ::"r"(id), "r"(n) : "memory"); }
__device__ __forceinline__ void wg_fence() { asm volatile("wgmma.fence.sync.aligned;" ::: "memory"); }
__device__ __forceinline__ void wg_commit() { asm volatile("wgmma.commit_group.sync.aligned;" ::: "memory"); }
template <int N>
__device__ __forceinline__ void wg_wait() { asm volatile("wgmma.wait_group.sync.aligned %0;" ::"n"(N) : "memory"); }

__device__ __forceinline__ uint64_t make_desc(uint32_t addr, uint32_t lbo, uint32_t sbo, uint64_t swz) {
    return (uint64_t)((addr & 0x3FFFF) >> 4) | ((uint64_t)(lbo >> 4) << 16) | ((uint64_t)(sbo >> 4) << 32) | (swz << 62);
}

#define ACC8(a, o) "+f"(a[o]), "+f"(a[o + 1]), "+f"(a[o + 2]), "+f"(a[o + 3]), "+f"(a[o + 4]), "+f"(a[o + 5]), "+f"(a[o + 6]), "+f"(a[o + 7])
constexpr uint32_t DHI128 = (1024u >> 4) | (1u << 30);
constexpr uint32_t DHI64 = (512u >> 4) | (2u << 30);
__device__ __forceinline__ void wgmma_n128_rs(float (&d)[64], const uint32_t* a, uint32_t db, int scale_d) {
    asm volatile(
        "{\n.reg .pred p;\n.reg .b64 dd;\nsetp.ne.b32 p, %69, 0;\nmov.b64 dd, {%68, %70};\n"
        "wgmma.mma_async.sync.aligned.m64n128k16.f32.bf16.bf16 "
        "{%0,%1,%2,%3,%4,%5,%6,%7,%8,%9,%10,%11,%12,%13,%14,%15,%16,%17,%18,%19,%20,%21,%22,%23,%24,%25,%26,%27,%28,%29,%30,%31,"
        "%32,%33,%34,%35,%36,%37,%38,%39,%40,%41,%42,%43,%44,%45,%46,%47,%48,%49,%50,%51,%52,%53,%54,%55,%56,%57,%58,%59,%60,%61,%62,%63},"
        "{%64,%65,%66,%67}, dd, p, 1, 1, 1;\n}"
        : ACC8(d, 0), ACC8(d, 8), ACC8(d, 16), ACC8(d, 24), ACC8(d, 32), ACC8(d, 40), ACC8(d, 48), ACC8(d, 56)
        : "r"(a[0]), "r"(a[1]), "r"(a[2]), "r"(a[3]), "r"(db), "r"(scale_d), "n"(DHI128));
}
template <uint32_t HI>
__device__ __forceinline__ void wgmma_n64_rs(float (&d)[32], const uint32_t* a, uint32_t db, int scale_d) {
    asm volatile(
        "{\n.reg .pred p;\n.reg .b64 dd;\nsetp.ne.b32 p, %37, 0;\nmov.b64 dd, {%36, %38};\n"
        "wgmma.mma_async.sync.aligned.m64n64k16.f32.bf16.bf16 "
        "{%0,%1,%2,%3,%4,%5,%6,%7,%8,%9,%10,%11,%12,%13,%14,%15,%16,%17,%18,%19,%20,%21,%22,%23,%24,%25,%26,%27,%28,%29,%30,%31},"
        "{%32,%33,%34,%35}, dd, p, 1, 1, 1;\n}"
        : ACC8(d, 0), ACC8(d, 8), ACC8(d, 16), ACC8(d, 24)
        : "r"(a[0]), "r"(a[1]), "r"(a[2]), "r"(a[3]), "r"(db), "r"(scale_d), "n"(HI));
}
__device__ __forceinline__ void wgmma_n64_ss_tt(float (&d)[32], uint64_t da, uint64_t db, int scale_d) {
    asm volatile(
        "{\n.reg .pred p;\nsetp.ne.b32 p, %34, 0;\n"
        "wgmma.mma_async.sync.aligned.m64n64k16.f32.bf16.bf16 "
        "{%0,%1,%2,%3,%4,%5,%6,%7,%8,%9,%10,%11,%12,%13,%14,%15,%16,%17,%18,%19,%20,%21,%22,%23,%24,%25,%26,%27,%28,%29,%30,%31},"
        "%32, %33, p, 1, 1, 1, 1;\n}"
        : ACC8(d, 0), ACC8(d, 8), ACC8(d, 16), ACC8(d, 24)
        : "l"(da), "l"(db), "r"(scale_d));
}
__device__ __forceinline__ void wgmma_n8_ss_tn(float (&d)[4], uint64_t da, uint64_t db, int scale_d) {
    asm volatile(
        "{\n.reg .pred p;\nsetp.ne.b32 p, %6, 0;\n"
        "wgmma.mma_async.sync.aligned.m64n8k16.f32.bf16.bf16 {%0,%1,%2,%3}, %4, %5, p, 1, 1, 1, 0;\n}"
        : "+f"(d[0]), "+f"(d[1]), "+f"(d[2]), "+f"(d[3])
        : "l"(da), "l"(db), "r"(scale_d));
}
template <int N>
__device__ __forceinline__ void acc_fence(float (&d)[N]) {
#pragma unroll
    for (int i = 0; i < N; i++) asm volatile("" : "+f"(d[i])::"memory");
}
__device__ __forceinline__ void mma16816(float (&c)[4], const uint32_t* a, uint32_t b0, uint32_t b1) {
    asm volatile(
        "mma.sync.aligned.m16n8k16.row.col.f32.bf16.bf16.f32 {%0,%1,%2,%3}, {%4,%5,%6,%7}, {%8,%9}, {%0,%1,%2,%3};"
        : "+f"(c[0]), "+f"(c[1]), "+f"(c[2]), "+f"(c[3])
        : "r"(a[0]), "r"(a[1]), "r"(a[2]), "r"(a[3]), "r"(b0), "r"(b1));
}
__device__ __forceinline__ uint32_t pack_bf16(float lo, float hi) {
    uint32_t r;
    asm("cvt.rn.bf16x2.f32 %0, %1, %2;" : "=r"(r) : "f"(hi), "f"(lo));
    return r;
}
__device__ __forceinline__ float bf_lo(uint32_t v) { return __uint_as_float(v << 16); }
__device__ __forceinline__ float bf_hi(uint32_t v) { return __uint_as_float(v & 0xffff0000u); }
__device__ __forceinline__ float bf16_round(float v) { return __bfloat162float(__float2bfloat16_rn(v)); }
__device__ __forceinline__ float sqrt_fast(float v) {
    float r;
    asm("sqrt.approx.ftz.f32 %0, %1;" : "=f"(r) : "f"(v));
    return r;
}
__device__ __forceinline__ float rcp_fast(float v) {
    float r;
    asm("rcp.approx.ftz.f32 %0, %1;" : "=f"(r) : "f"(v));
    return r;
}
__device__ __forceinline__ float ex2_fast(float v) {
    float r;
    asm("ex2.approx.ftz.f32 %0, %1;" : "=f"(r) : "f"(v));
    return r;
}
struct RowScale { float rho, rl, var; };
__device__ __forceinline__ float phi_f(float a, const RowScale& r) {
    return fmaf(fmaxf(a, 0.f), r.rho, ex2_fast(fminf(a, 0.f) * r.rl) + 1e-6f);
}
__device__ __forceinline__ float swiglu_f(float ga, float ua, const RowScale& r) {
    return (ga * ua) * rcp_fast(fmaf(ex2_fast(-ga * r.rl), r.var, r.var));
}
__device__ __forceinline__ uint4 swiglu8(const float* gp, const float* up, const RowScale& r0, const RowScale& r1) {
    uint4 v;
    v.x = pack_bf16(swiglu_f(gp[0], up[0], r0), swiglu_f(gp[1], up[1], r0));
    v.y = pack_bf16(swiglu_f(gp[2], up[2], r1), swiglu_f(gp[3], up[3], r1));
    v.z = pack_bf16(swiglu_f(gp[4], up[4], r0), swiglu_f(gp[5], up[5], r0));
    v.w = pack_bf16(swiglu_f(gp[6], up[6], r1), swiglu_f(gp[7], up[7], r1));
    v.y = v.y ? v.y : 0x8000u;
    v.w = v.w ? v.w : 0x8000u;
    return v;
}
__device__ __forceinline__ void st_frag(uint4* p, uint4 v) {
    asm volatile("st.relaxed.gpu.global.v4.u32 [%0], {%1,%2,%3,%4};" ::"l"(p), "r"(v.x), "r"(v.y), "r"(v.z), "r"(v.w) : "memory");
}
__device__ __forceinline__ uint4 ld_frag(const uint4* p) {
    uint4 v;
    asm volatile("ld.relaxed.gpu.global.v4.u32 {%0,%1,%2,%3}, [%4];" : "=r"(v.x), "=r"(v.y), "=r"(v.z), "=r"(v.w) : "l"(p) : "memory");
    return v;
}
__device__ __forceinline__ void red_add2(float* p, float a, float b) {
    asm volatile("red.global.add.v2.f32 [%0], {%1, %2};" ::"l"(p), "f"(a), "f"(b) : "memory");
}
__device__ __forceinline__ void cp_async16(uint32_t dst, const void* src) {
    asm volatile("cp.async.cg.shared.global [%0], [%1], 16;" ::"r"(dst), "l"(src) : "memory");
}

__device__ __forceinline__ int ring_lap(int u) { return (u * 79) >> 10; }
__device__ __forceinline__ int ring_slot(int u) { return u - NST * ring_lap(u); }

__device__ __forceinline__ void mainloop128(float (&acc)[64], const uint32_t (&xa)[128], int u0, uint32_t sb,
                                            uint32_t desc128, int lane, int wg, bool last = false) {
    bar_sync(7 + wg, 256);
#pragma unroll
    for (int kb = 0; kb < 8; kb++) {
        const int st = ring_slot(u0 + kb);
        mbar_wait(sb + BAR_FULL + 8 * st, ring_lap(u0 + kb) & 1);
        wg_fence();
        const uint32_t d = desc128 + st * (STAGE_BYTES >> 4);
#pragma unroll
        for (int ks = 0; ks < 4; ks++) wgmma_n128_rs(acc, &xa[(kb * 4 + ks) * 4], d + ks * 128, (kb | ks) != 0);
        wg_commit();
        if (kb == 7 && !(last && wg == 1)) bar_arrive(8 - wg, 256);
        if (kb > 0) {
            wg_wait<1>();
            if (lane < 2) mbar_arrive_cta(sb + BAR_EMPTY + 8 * ring_slot(u0 + kb - 1), lane);
        }
    }
    wg_wait<0>();
    acc_fence(acc);
    if (lane < 2) mbar_arrive_cta(sb + BAR_EMPTY + 8 * ring_slot(u0 + 7), lane);
}
__device__ __forceinline__ void mainloop64x2(float (&a0)[32], float (&a1)[32], const uint32_t (&xa)[128], int u0,
                                             uint32_t sb, uint32_t desc128, int lane, int wg) {
    bar_sync(7 + wg, 256);
#pragma unroll
    for (int kb = 0; kb < 8; kb++) {
        const int st = ring_slot(u0 + kb);
        mbar_wait(sb + BAR_FULL + 8 * st, ring_lap(u0 + kb) & 1);
        wg_fence();
        const uint32_t d = desc128 + st * (STAGE_BYTES >> 4);
        const uint32_t d2 = d + (8192 >> 4) - ((4096u >> 4) << 16);
#pragma unroll
        for (int ks = 0; ks < 4; ks++) {
            wgmma_n64_rs<DHI128>(a0, &xa[(kb * 4 + ks) * 4], d + ks * 128, (kb | ks) != 0);
            wgmma_n64_rs<DHI64>(a1, &xa[(kb * 4 + ks) * 4], d2 + ks * 64, (kb | ks) != 0);
        }
        wg_commit();
        if (kb == 7) bar_arrive(8 - wg, 256);
        if (kb > 0) {
            wg_wait<1>();
            if (lane < 2) mbar_arrive_cta(sb + BAR_EMPTY + 8 * ring_slot(u0 + kb - 1), lane);
        }
    }
    wg_wait<0>();
    acc_fence(a0);
    acc_fence(a1);
    if (lane < 2) mbar_arrive_cta(sb + BAR_EMPTY + 8 * ring_slot(u0 + 7), lane);
}

__global__ void __cluster_dims__(2, 1, 1) __launch_bounds__(384, 1)
fused_kernel(const __grid_constant__ CUtensorMap tm_x, const __grid_constant__ CUtensorMap tm_qkv,
             const __grid_constant__ CUtensorMap tm_w1, const __grid_constant__ CUtensorMap tm_w3,
             const __grid_constant__ CUtensorMap tm_w1h, const __grid_constant__ CUtensorMap tm_w3h,
             const __grid_constant__ CUtensorMap tm_w2, const __grid_constant__ CUtensorMap tm_w2h,
             const __grid_constant__ CUtensorMap tm_wo, const __nv_bfloat16* __restrict__ xg,
             __nv_bfloat16* __restrict__ outg, const char* __restrict__ p_qkv, const char* __restrict__ p_w1,
             const char* __restrict__ p_w3, const char* __restrict__ p_w2, const char* __restrict__ p_wo) {
    extern __shared__ __align__(1024) uint8_t smem[];
    const uint32_t sb = smem_u32(smem);
    const int tid = threadIdx.x;
    const int warp = tid >> 5, lane = tid & 31;
    const int rank = blockIdx.x & 1;
    const int pair = blockIdx.x >> 1;
    const int c = pair & 7;
    const int m = (pair >> 3) * 2 + rank;
    const int m2 = (pair >> 3) * 2 + (c & 1);
    const int j2 = c >> 1;

    TS(tid >> 7, 0);
    if (tid == 256) {
#pragma unroll
        for (int i = 0; i < 8; i++) mbar_init(sb + BAR_XFULL + 8 * i, 1);
        asm volatile("fence.proxy.async.shared::cta;" ::: "memory");
#pragma unroll
        for (int kb = 0; kb < 8; kb++) {
            mbar_expect_tx(sb + BAR_XFULL + 8 * kb, 16384);
            tma_load(sb + (XST0 + kb) * STAGE_BYTES, &tm_x, sb + BAR_XFULL + 8 * kb, kb * 64, m * 128);
        }
        TS(2, 21);
    } else if (tid == 0) {
#pragma unroll
        for (int i = 0; i < NST; i++) mbar_init(sb + BAR_FULL + 8 * i, 1);
        asm volatile("fence.mbarrier_init.release.cluster;" ::: "memory");
    } else if (tid == 32) {
#pragma unroll
        for (int i = 0; i < NST; i++) mbar_init(sb + BAR_EMPTY + 8 * i, 16);
        asm volatile("fence.mbarrier_init.release.cluster;" ::: "memory");
    } else if (tid == 64) {
#pragma unroll
        for (int i = 0; i < 4; i++) mbar_init(sb + BAR_KVREADY + 8 * i, 1);
        mbar_expect_tx(sb + BAR_XCHG, 32768);
        asm volatile("fence.mbarrier_init.release.cluster;" ::: "memory");
    } else if (tid >= 128 && tid < 256) {
        ((uint4*)(smem + OFF_ZERO))[tid - 128] = make_uint4(0, 0, 0, 0);
        ((uint4*)(smem + OFF_ZERO))[tid] = make_uint4(0, 0, 0, 0);
        asm volatile("fence.proxy.async.shared::cta;" ::: "memory");
    } else if (tid == 288) {
        prefetch_tm(&tm_qkv);
        prefetch_tm(rank ? &tm_w3 : &tm_w1);
        prefetch_tm(&tm_w1h);
        prefetch_tm(&tm_w3h);
        prefetch_tm(&tm_w2);
        prefetch_tm(&tm_w2h);
        prefetch_tm(&tm_wo);
    } else if (tid >= 320) {
        ((uint32_t*)(smem + OFF_ONES))[tid - 320] = 0x3F803F80u;
        asm volatile("fence.proxy.async.shared::cta;" ::: "memory");
    }
    __syncthreads();
    TS(tid >> 7, 22);
    asm volatile("barrier.cluster.arrive.relaxed.aligned;\nbarrier.cluster.wait.acquire.aligned;" ::: "memory");

    if (warp >= 8) {
        asm volatile("setmaxnreg.dec.sync.aligned.u32 40;");
        if (warp == 8) {
            if (lane == 0) {
                int st = 0;
                uint32_t lap = 0;
                for (int it = 0; it < 40; it++) {
                    const int tile = it >> 3, kb = it & 7;
                    const uint32_t full = sb + BAR_FULL + 8 * st;
                    mbar_wait(sb + BAR_EMPTY + 8 * st, (st >= XST0) ? (lap & 1) : ((lap & 1) ^ 1));
                    mbar_expect_tx(full, STAGE_BYTES);
                    const uint32_t dst = sb + st * STAGE_BYTES;
                    if (tile == 0) {
                        tma_load_mc(dst + rank * 8192, &tm_qkv, full, 512 + 512 * rank + 64 * c, kb * 64);
                    } else if (tile != 3) {
                        tma_load_mc(dst + rank * 8192, rank ? &tm_w3 : &tm_w1, full, 224 * c + 64 * (tile == 4 ? 2 : tile - 1), kb * 64);
                    } else if (rank == 0) {
                        tma_load_mc(dst, &tm_qkv, full, 64 * c, kb * 64);
                    } else {
                        tma_load_mc(dst + 8192, &tm_w1h, full, 224 * c + 192, kb * 64);
                        tma_load_mc(dst + 12288, &tm_w3h, full, 224 * c + 192, kb * 64);
                    }
                    if (++st == NST) { st = 0; lap++; }
                    if (it == 7) {
                        mbar_wait(sb + BAR_EMPTY + 8 * SCR0, 0);
                        mbar_arrive(sb + BAR_FULL + 8 * SCR0);
                        mbar_wait(sb + BAR_EMPTY + 8 * (SCR0 + 1), 0);
                        mbar_arrive(sb + BAR_FULL + 8 * (SCR0 + 1));
                        st += 2;
                    }
                }
                TS(2, 1);
                for (int b = 0; b < 18; b++) {
                    const uint32_t full = sb + BAR_FULL + 8 * st;
                    const uint32_t dst = sb + st * STAGE_BYTES;
                    mbar_wait(sb + BAR_EMPTY + 8 * st, (st >= XST0) ? (lap & 1) : ((lap & 1) ^ 1));
                    mbar_expect_tx(full, STAGE_BYTES);
                    if (b < 8 || b >= 14) {
                        const int row = (b < 8) ? 224 * (4 * rank + (b & 3)) + 64 * (b >> 2) : 224 * (4 * rank + b - 14) + 128;
                        tma_load(dst, &tm_w2, full, 128 * j2, row);
                        tma_load(dst + 8192, &tm_w2, full, 128 * j2 + 64, row);
                    } else if (b < 10) {
                        const int row = 224 * (4 * rank + 2 * (b - 8)) + 192;
                        tma_load(dst, &tm_w2h, full, 128 * j2, row);
                        tma_load(dst + 4096, &tm_w2h, full, 128 * j2, row + 224);
                        tma_load(dst + 8192, &tm_w2h, full, 128 * j2 + 64, row);
                        tma_load(dst + 12288, &tm_w2h, full, 128 * j2 + 64, row + 224);
                    } else {
                        const int row = 64 * (4 * rank + (b - 10));
                        tma_load(dst, &tm_wo, full, 128 * j2, row);
                        tma_load(dst + 8192, &tm_wo, full, 128 * j2 + 64, row);
                    }
                    TS(2, 2 + b);
                    if (++st == NST) { st = 0; lap++; }
                }
                mbar_wait(sb + BAR_EMPTY + 8 * SCR0, lap & 1);
                mbar_wait(sb + BAR_EMPTY + 8 * (SCR0 + 1), lap & 1);
                mbar_arrive_cta(sb + BAR_XRDY, rank ^ 1);
            }
        } else if (warp < 11) {
            const int wg = warp - 9;
            bar_sync(3 + wg, 160);
            if (lane == 0) asm volatile("red.release.gpu.global.add.u32 [%0], 1;" ::"l"(&g_kvcnt[c]) : "memory");
            TSW(3, wg);
        } else {
            const unsigned epoch = read_epoch();
            if (lane == 0) {
                const unsigned tk = atomicInc(&g_ticket, 127u);
                if (tk == 127u) *(volatile unsigned*)&g_epoch = epoch;
            }
            if (lane == 0) *(volatile unsigned*)(smem + OFF_EPOCH) = epoch;
            __syncwarp();
            if (lane == 0) mbar_arrive(sb + BAR_EPOCH);
            if (lane == 0) {
                char* z = (char*)(g_A2 + (size_t)((epoch & 1) ^ 1) * A2_N + (size_t)((m * 2 + (c >> 2)) * 18) * 4 * 256);
                const int cc = c & 3;
#pragma unroll 1
                for (int i = 0; i < 18; i++) {
                    const int blk = (i < 8) ? ((i >> 2) * 4 + cc) * 4 + (i & 3)
                                  : (i < 10) ? (8 + (cc >> 1)) * 4 + 2 * (cc & 1) + (i - 8)
                                  : (i < 14) ? (10 + cc) * 4 + (i - 10) : (14 + cc) * 4 + (i - 14);
                    asm volatile("cp.async.bulk.global.shared::cta.bulk_group [%0], [%1], 4096;"
                                 ::"l"(z + (size_t)blk * 4096), "r"(sb + OFF_ZERO) : "memory");
                }
                asm volatile("cp.async.bulk.commit_group;" ::: "memory");
            }
            if (lane < 17) g_kvacc[(((epoch & 1) ^ 1) * 8 + c) * 272 + 17 * m + lane] = make_float4(0.f, 0.f, 0.f, 0.f);
            {
                unsigned n = 0;
                while ((int)(ld_acquire(&g_kvcnt[c]) - 32u * epoch) < 0) {
                    __nanosleep(200);
                    if (++n > SPIN_LIMIT) asm volatile("trap;");
                }
            }
            TSW(4, 0);
            const int g = lane >> 2, t = lane & 3;
            const float* ks = (const float*)(g_kvacc + ((epoch & 1) * 8 + c) * 272) + 32 * t + g;
            uint2* kf = (uint2*)(smem + OFF_KVFRAG) + lane;
#pragma unroll 2
            for (int hh = 0; hh < 4; hh++) {
                const float* k = ks + hh * 272;
                const float a0 = __ldcg(k), a1 = __ldcg(k + 16), a2 = __ldcg(k + 128), a3 = __ldcg(k + 144);
                const float b0 = __ldcg(k + 8), b1 = __ldcg(k + 24), b2 = __ldcg(k + 136), b3 = __ldcg(k + 152);
                const float2 z0 = __ldcg((const float2*)(k - g - 30 * t + 256)), z1 = __ldcg((const float2*)(k - g - 30 * t + 264));
                kf[(hh * 3 + 0) * 32] = make_uint2(pack_bf16(a0, a1), pack_bf16(a2, a3));
                kf[(hh * 3 + 1) * 32] = make_uint2(pack_bf16(b0, b1), pack_bf16(b2, b3));
                kf[(hh * 3 + 2) * 32] = make_uint2(pack_bf16(z0.x, z0.y), pack_bf16(z1.x, z1.y));
            }
            __syncwarp();
            if (lane == 0) mbar_arrive(sb + BAR_KVREADY);
            TSW(4, 4);
            if (lane == 0) asm volatile("cp.async.bulk.wait_group 0;" ::: "memory");
        }
    } else {
        asm volatile("setmaxnreg.inc.sync.aligned.u32 232;");
        const int wg = warp >> 2, w = warp & 3;
        const int g = lane >> 2, t = lane & 3;
        float acc[64];
        uint32_t xa[128];
        float rho0, rho1;
        RowScale r0, r1;
        unsigned par;

        TS(wg, 1);
        {
            const int row = wg * 64 + w * 16 + (lane & 7) + ((lane >> 3) & 1) * 8;
            const uint32_t rbase = sb + XST0 * STAGE_BYTES + row * 128;
            const int hi = lane >> 4, r7 = lane & 7;
            float sm[2][4], c0[2][4], c1[2][4];
#pragma unroll
            for (int i = 0; i < 8; i++) { sm[i >> 2][i & 3] = 0.f; c0[i >> 2][i & 3] = 0.f; c1[i >> 2][i & 3] = 0.f; }
            if (wg == 1) bar_arrive(7, 256);
#pragma unroll
            for (int kb = 0; kb < 8; kb++) {
                mbar_wait(sb + BAR_XFULL + 8 * kb, 0);
#pragma unroll
                for (int ks = 0; ks < 4; ks++) {
                    uint32_t* a = &xa[(kb * 4 + ks) * 4];
                    const uint32_t addr = rbase + kb * STAGE_BYTES + (((2 * ks + hi) ^ r7) << 4);
                    asm volatile("ldmatrix.sync.aligned.m8n8.x4.shared.b16 {%0,%1,%2,%3}, [%4];"
                                 : "=r"(a[0]), "=r"(a[1]), "=r"(a[2]), "=r"(a[3]) : "r"(addr) : "memory");
                    mma16816(sm[ks & 1], a, 0x3F803F80u, 0x3F803F80u);
                    mma16816(c0[ks & 1], a, a[0], a[2]);
                    mma16816(c1[ks & 1], a, a[1], a[3]);
                }
            }
            TS(wg, 2);
            const float mean0 = (sm[0][0] + sm[1][0]) * (1.f / 512.f);
            const float mean1 = (sm[0][2] + sm[1][2]) * (1.f / 512.f);
            __syncwarp();
            if (lane < 16) mbar_arrive_cta(sb + BAR_EMPTY + 8 * (XST0 + (lane >> 1)), lane & 1);
            const __nv_bfloat162 mb0 = __float2bfloat162_rn(mean0), mb1 = __float2bfloat162_rn(mean1);
#pragma unroll
            for (int i = 0; i < 128; i++) {
                __nv_bfloat162 v = *reinterpret_cast<__nv_bfloat162*>(&xa[i]);
                v = __hsub2(v, (i & 1) ? mb1 : mb0);
                xa[i] = *reinterpret_cast<uint32_t*>(&v);
            }
            const float d0 = (g & 1) ? c0[0][1] + c0[1][1] : c0[0][0] + c0[1][0];
            const float d1 = (g & 1) ? c1[0][3] + c1[1][3] : c1[0][2] + c1[1][2];
            const int src = (lane & ~3) | (g >> 1);
            const float var0 = fmaxf(__shfl_sync(0xffffffffu, d0, src) * (1.f / 512.f) - mean0 * mean0, 0.f);
            const float var1 = fmaxf(__shfl_sync(0xffffffffu, d1, src) * (1.f / 512.f) - mean1 * mean1, 0.f);
            const float sd0 = bf16_round(sqrt_fast(bf16_round(bf16_round(var0) + 1e-5f)));
            const float sd1 = bf16_round(sqrt_fast(bf16_round(bf16_round(var1) + 1e-5f)));
            rho0 = rcp_fast(sd0);
            rho1 = rcp_fast(sd1);
            r0.rho = rho0; r0.rl = rho0 * 1.4426950408889634f; r0.var = sd0 * sd0;
            r1.rho = rho1; r1.rl = rho1 * 1.4426950408889634f; r1.var = sd1 * sd1;
        }

        TS(wg, 3);
        const uint32_t desc128 = ((sb & 0x3FFFF) >> 4) | ((8192u >> 4) << 16);
        const int cc = c & 3;

        {
            mainloop128(acc, xa, 0, sb, desc128, lane, wg);
            TS(wg, 4);
            {
                TS(wg, 24);
                const uint32_t pkb = sb + (SCR0 + wg) * STAGE_BYTES;
                mbar_wait(sb + BAR_FULL + 8 * (SCR0 + wg), 0);
                const uint32_t ra = pkb + (w * 16 + g) * 128 + t * 4;
#pragma unroll
                for (int nb = 0; nb < 8; nb++) {
                    const uint32_t off = (uint32_t)((nb ^ g) << 4);
                    uint32_t p0 = pack_bf16(phi_f(acc[nb * 4], r0), phi_f(acc[nb * 4 + 1], r0));
                    uint32_t p1 = pack_bf16(phi_f(acc[nb * 4 + 2], r1), phi_f(acc[nb * 4 + 3], r1));
                    uint32_t v0 = pack_bf16(acc[32 + nb * 4] * rho0, acc[32 + nb * 4 + 1] * rho0);
                    uint32_t v1 = pack_bf16(acc[32 + nb * 4 + 2] * rho1, acc[32 + nb * 4 + 3] * rho1);
                    asm volatile("st.shared.u32 [%0], %1;" ::"r"(ra + off), "r"(p0) : "memory");
                    asm volatile("st.shared.u32 [%0], %1;" ::"r"(ra + off + 1024), "r"(p1) : "memory");
                    asm volatile("st.shared.u32 [%0], %1;" ::"r"(ra + off + 8192), "r"(v0) : "memory");
                    asm volatile("st.shared.u32 [%0], %1;" ::"r"(ra + off + 8192 + 1024), "r"(v1) : "memory");
                }
                TS(wg, 25);
                asm volatile("fence.proxy.async.shared::cta;" ::: "memory");
                bar_sync(1 + wg, 128);
                TS(wg, 26);
                const uint64_t da = make_desc(pkb, 8192, 1024, 1);
                const uint64_t db = make_desc(pkb + 8192, 8192, 1024, 1);
                const uint64_t d1 = make_desc(sb + OFF_ONES, 128, 128, 0);
                float kva[32], za[4];
                wg_fence();
#pragma unroll
                for (int ks = 0; ks < 4; ks++) {
                    wgmma_n64_ss_tt(kva, da + ks * 128, db + ks * 128, ks != 0);
                    wgmma_n8_ss_tn(za, da + ks * 128, d1, ks != 0);
                }
                wg_commit();
                wg_wait<0>();
                acc_fence(kva);
                acc_fence(za);
                if (lane < 4) mbar_arrive_cta(sb + BAR_EMPTY + 8 * (SCR0 + (lane >> 1)), lane & 1);
                TS(wg, 27);
                float o[8];
#pragma unroll
                for (int i = 0; i < 8; i++)
                    o[i] = (w == 0) ? kva[i] : (w == 1) ? kva[8 + i] : (w == 2) ? kva[16 + i] : kva[24 + i];
                mbar_wait(sb + BAR_EPOCH, 0);
                par = *(volatile unsigned*)(smem + OFF_EPOCH) & 1;
                float* dst = (float*)(g_kvacc + (par * 8 + c) * 272) + w * 272 + g * 16 + 2 * t;
                red_add2(dst, o[0], o[1]);
                red_add2(dst + 128, o[2], o[3]);
                red_add2(dst + 8, o[4], o[5]);
                red_add2(dst + 136, o[6], o[7]);
                if (t == 0) {
                    atomicAdd(dst - g * 15 + 256, za[0]);
                    atomicAdd(dst - g * 15 + 264, za[2]);
                }
            }
            bar_arrive(3 + wg, 160);
            TS(wg, 5);
        }
        uint4* a2w = g_A2 + (size_t)par * A2_N + (size_t)((m * 2 + (c >> 2)) * 18) * 4 * 256 + warp * 32 + lane;
#pragma unroll
        for (int tile = 1; tile < 3; tile++) {
            mainloop128(acc, xa, 2 + 8 * tile, sb, desc128, lane, wg);
            TS(wg, 4 + 2 * tile);
            uint4* dst = a2w + (size_t)((4 * (tile - 1) + cc) * 4) * 256;
#pragma unroll
            for (int ks = 0; ks < 4; ks++) st_frag(dst + ks * 256, swiglu8(&acc[ks * 8], &acc[32 + ks * 8], r0, r1));
            TS(wg, 5 + 2 * tile);
        }
        {
            float qa[32], gu[32];
            mainloop64x2(qa, gu, xa, 26, sb, desc128, lane, wg);
            TS(wg, 10);
            uint4* dst = a2w + (size_t)((8 + (cc >> 1)) * 4 + 2 * (cc & 1)) * 256;
#pragma unroll
            for (int ks = 0; ks < 2; ks++) st_frag(dst + ks * 256, swiglu8(&gu[ks * 8], &gu[16 + ks * 8], r0, r1));
            TS(wg, 13);
            mbar_wait(sb + BAR_KVREADY, 0);
            TS(wg, 14);
            const uint2* kf = (const uint2*)(smem + OFF_KVFRAG);
            dst = a2w + (size_t)((10 + cc) * 4) * 256;
#pragma unroll
            for (int hh = 0; hh < 4; hh++) {
                const float* q = &qa[hh * 8];
                uint32_t a[4];
                a[0] = pack_bf16(phi_f(q[0], r0), phi_f(q[1], r0));
                a[1] = pack_bf16(phi_f(q[2], r1), phi_f(q[3], r1));
                a[2] = pack_bf16(phi_f(q[4], r0), phi_f(q[5], r0));
                a[3] = pack_bf16(phi_f(q[6], r1), phi_f(q[7], r1));
                float n0[4] = {0.f, 0.f, 0.f, 0.f}, n1[4] = {0.f, 0.f, 0.f, 0.f}, dn[4] = {0.f, 0.f, 0.f, 0.f};
                const uint2 b0 = kf[(hh * 3 + 0) * 32 + lane], b1 = kf[(hh * 3 + 1) * 32 + lane],
                            bz = kf[(hh * 3 + 2) * 32 + lane];
                mma16816(n0, a, b0.x, b0.y);
                mma16816(n1, a, b1.x, b1.y);
                mma16816(dn, a, bz.x, bz.y);
                const float i0 = rcp_fast(dn[0] + 1e-6f), i1 = rcp_fast(dn[2] + 1e-6f);
                uint4 v;
                v.x = pack_bf16(n0[0] * i0, n0[1] * i0);
                v.y = pack_bf16(n0[2] * i1, n0[3] * i1);
                v.z = pack_bf16(n1[0] * i0, n1[1] * i0);
                v.w = pack_bf16(n1[2] * i1, n1[3] * i1);
                v.y = v.y ? v.y : 0x8000u;
                v.w = v.w ? v.w : 0x8000u;
                st_frag(dst + hh * 256, v);
            }
            TS(wg, 11);
        }
        const uint4* a2r = g_A2 + (size_t)par * A2_N + (size_t)((m2 * 2 + rank) * 18) * 4 * 256 + warp * 32 + lane;
        uint4 af[APF + 1][4];
        {
            mainloop128(acc, xa, 34, sb, desc128, lane, wg, true);
            TS(wg, 12);
#pragma unroll
            for (int b = 0; b < APF; b++) {
#pragma unroll
                for (int ks = 0; ks < 4; ks++) af[b][ks] = ld_frag(a2r + (b * 4 + ks) * 256);
            }
            uint4* dst = a2w + (size_t)((14 + cc) * 4) * 256;
#pragma unroll
            for (int ks = 0; ks < 4; ks++) st_frag(dst + ks * 256, swiglu8(&acc[ks * 8], &acc[32 + ks * 8], r0, r1));
            TS(wg, 15);
        }

        {
            float ao[32], ap[32];
            const uint32_t dso = desc128 + rank * 512, dsp = desc128 + (rank ^ 1) * 512;
            TS(wg, 16);
#pragma unroll
            for (int b = 0; b < 18; b++) {
                if (b == 14) TS(wg, 17);
                mbar_wait(sb + BAR_FULL + 8 * ring_slot(42 + b), ring_lap(42 + b) & 1);
                {
                    uint4(&f)[4] = af[b % (APF + 1)];
                    unsigned n = 0;
                    while (__any_sync(0xffffffffu, min(min(min(f[0].y, f[0].w), min(f[1].y, f[1].w)),
                                                       min(min(f[2].y, f[2].w), min(f[3].y, f[3].w))) == 0u)) {
#pragma unroll
                        for (int ks = 0; ks < 4; ks++) f[ks] = ld_frag(a2r + (b * 4 + ks) * 256);
                        if (++n > SPIN_LIMIT) asm volatile("trap;");
                    }
                }
                wg_fence();
                const uint32_t so = ring_slot(42 + b) * (STAGE_BYTES >> 4);
#pragma unroll
                for (int ks = 0; ks < 4; ks++) {
                    const uint32_t* a = reinterpret_cast<const uint32_t*>(&af[b % (APF + 1)][ks]);
                    wgmma_n64_rs<DHI128>(ap, a, dsp + so + ks * 128, (b | ks) != 0);
                    if (b < 14) wgmma_n64_rs<DHI128>(ao, a, dso + so + ks * 128, (b | ks) != 0);
                }
                wg_commit();
                if (b > 0 && b < 14) {
                    wg_wait<1>();
                    if (lane < 2) mbar_arrive(sb + BAR_EMPTY + 8 * ring_slot(41 + b));
                }
                if (b + APF < 18) {
#pragma unroll
                    for (int ks = 0; ks < 4; ks++)
                        af[(b + APF) % (APF + 1)][ks] = ld_frag(a2r + ((b + APF) * 4 + ks) * 256);
                }
            }
#pragma unroll
            for (int b = 14; b < 18; b++) {
                const uint32_t so = ring_slot(42 + b) * (STAGE_BYTES >> 4);
#pragma unroll
                for (int ks = 0; ks < 4; ks++)
                    wgmma_n64_rs<DHI128>(ao, reinterpret_cast<const uint32_t*>(&af[b % (APF + 1)][ks]), dso + so + ks * 128, 1);
            }
            wg_commit();
            const int row0 = m2 * 128 + wg * 64 + w * 16 + g;
            const int col0 = j2 * 128 + rank * 64 + 2 * t;
            uint32_t xr[16];
#pragma unroll
            for (int nb = 0; nb < 8; nb++) {
                xr[2 * nb] = __ldg((const uint32_t*)(xg + (size_t)row0 * 512 + col0 + nb * 8));
                xr[2 * nb + 1] = __ldg((const uint32_t*)(xg + (size_t)(row0 + 8) * 512 + col0 + nb * 8));
            }
            uint32_t rdst, rbar;
            asm volatile("mapa.shared::cluster.u32 %0, %1, %2;"
                         : "=r"(rdst) : "r"(sb + (SCR0 + wg) * STAGE_BYTES + (tid & 127) * 16), "r"(rank ^ 1));
            asm volatile("mapa.shared::cluster.u32 %0, %1, %2;" : "=r"(rbar) : "r"(sb + BAR_XCHG), "r"(rank ^ 1));
            mbar_wait(sb + BAR_XRDY, 0);
            wg_wait<1>();
            acc_fence(ap);
            TS(wg, 18);
#pragma unroll
            for (int i = 0; i < 8; i++)
                asm volatile("st.async.shared::cluster.mbarrier::complete_tx::bytes.v4.f32 [%0], {%1,%2,%3,%4}, [%5];"
                             ::"r"(rdst + i * 2048), "f"(ap[4 * i]), "f"(ap[4 * i + 1]), "f"(ap[4 * i + 2]), "f"(ap[4 * i + 3]),
                             "r"(rbar) : "memory");
            wg_wait<0>();
            acc_fence(ao);
            mbar_wait(sb + BAR_XCHG, 0);
            TS(wg, 19);
            const float4* rx = (const float4*)(smem + (SCR0 + wg) * STAGE_BYTES) + (tid & 127);
#pragma unroll
            for (int nb = 0; nb < 8; nb++) {
                const float4 p = rx[nb * 128];
                const uint32_t o0 = pack_bf16(ao[4 * nb] + p.x + bf_lo(xr[2 * nb]), ao[4 * nb + 1] + p.y + bf_hi(xr[2 * nb]));
                const uint32_t o1 = pack_bf16(ao[4 * nb + 2] + p.z + bf_lo(xr[2 * nb + 1]), ao[4 * nb + 3] + p.w + bf_hi(xr[2 * nb + 1]));
                *(uint32_t*)(outg + (size_t)row0 * 512 + col0 + nb * 8) = o0;
                *(uint32_t*)(outg + (size_t)(row0 + 8) * 512 + col0 + nb * 8) = o1;
            }
        }
        TS(wg, 20);
    }
}

typedef CUresult (*EncodeFn)(CUtensorMap*, CUtensorMapDataType, cuuint32_t, void*, const cuuint64_t*, const cuuint64_t*,
                             const cuuint32_t*, const cuuint32_t*, CUtensorMapInterleave, CUtensorMapSwizzle,
                             CUtensorMapL2promotion, CUtensorMapFloatOOBfill);

void make_map(EncodeFn enc, CUtensorMap* tm, const void* ptr, int rows, int cols, int box_rows, int box_cols,
              CUtensorMapSwizzle swz) {
    cuuint64_t dims[2] = {(cuuint64_t)cols, (cuuint64_t)rows};
    cuuint64_t strides[1] = {(cuuint64_t)cols * 2};
    cuuint32_t box[2] = {(cuuint32_t)box_cols, (cuuint32_t)box_rows};
    cuuint32_t es[2] = {1, 1};
    enc(tm, CU_TENSOR_MAP_DATA_TYPE_BFLOAT16, 2, const_cast<void*>(ptr), dims, strides, box, es,
        CU_TENSOR_MAP_INTERLEAVE_NONE, swz, CU_TENSOR_MAP_L2_PROMOTION_L2_256B, CU_TENSOR_MAP_FLOAT_OOB_FILL_NONE);
}

}

extern "C" void kernel_launch(void* const* d_in, const int* in_sizes, int n_in, void* d_out, int out_size) {
    (void)in_sizes; (void)n_in; (void)out_size;
    static EncodeFn enc = nullptr;
    if (!enc) {
        void* fn = nullptr;
        cudaDriverEntryPointQueryResult qr;
        cudaGetDriverEntryPoint("cuTensorMapEncodeTiled", &fn, cudaEnableDefault, &qr);
        enc = (EncodeFn)fn;
        cudaFuncSetAttribute(fused_kernel, cudaFuncAttributeMaxDynamicSharedMemorySize, SMEM_BYTES);
    }
    const void* x = d_in[0];
    const void* wqkv = d_in[1];
    const void* wo = d_in[2];
    const void* w1 = d_in[4];
    const void* w3 = d_in[5];
    const void* w2 = d_in[6];
    CUtensorMap tx, tqkv, t1, t3, t1h, t3h, t2, t2h, two;
    make_map(enc, &tx, x, 2048, 512, 128, 64, CU_TENSOR_MAP_SWIZZLE_128B);
    make_map(enc, &tqkv, wqkv, 512, 1536, 64, 64, CU_TENSOR_MAP_SWIZZLE_128B);
    make_map(enc, &t1, w1, 512, 1792, 64, 64, CU_TENSOR_MAP_SWIZZLE_128B);
    make_map(enc, &t3, w3, 512, 1792, 64, 64, CU_TENSOR_MAP_SWIZZLE_128B);
    make_map(enc, &t1h, w1, 512, 1792, 64, 32, CU_TENSOR_MAP_SWIZZLE_64B);
    make_map(enc, &t3h, w3, 512, 1792, 64, 32, CU_TENSOR_MAP_SWIZZLE_64B);
    make_map(enc, &t2, w2, 1792, 512, 64, 64, CU_TENSOR_MAP_SWIZZLE_128B);
    make_map(enc, &t2h, w2, 1792, 512, 32, 64, CU_TENSOR_MAP_SWIZZLE_128B);
    make_map(enc, &two, wo, 512, 512, 64, 64, CU_TENSOR_MAP_SWIZZLE_128B);
    fused_kernel<<<128, 384, SMEM_BYTES>>>(tx, tqkv, t1, t3, t1h, t3h, t2, t2h, two, (const __nv_bfloat16*)x,
                                           (__nv_bfloat16*)d_out, (const char*)wqkv, (const char*)w1, (const char*)w3,
                                           (const char*)w2, (const char*)wo);
}
```

```cpp
#include <cuda_runtime.h>
#include <cuda_bf16.h>
#include <cuda.h>
#include <stdint.h>

namespace {

constexpr int NST = 13;
constexpr int STAGE_BYTES = 16384;
constexpr int XST0 = 5;
constexpr int SCR0 = 8;
constexpr int OFF_MISC = NST * STAGE_BYTES;
constexpr int OFF_KVFRAG = OFF_MISC;
constexpr int OFF_ONES = OFF_MISC + 3072;
constexpr int OFF_BARS = OFF_MISC + 3328;
constexpr int BAR_FULL = OFF_BARS;
constexpr int BAR_EMPTY = BAR_FULL + 8 * NST;
constexpr int BAR_XFULL = BAR_EMPTY + 8 * NST;
constexpr int BAR_KVREADY = BAR_XFULL + 64;
constexpr int BAR_XCHG = BAR_KVREADY + 8;
constexpr int BAR_EPOCH = BAR_XCHG + 8;
constexpr int BAR_XRDY = BAR_EPOCH + 8;
constexpr int OFF_EPOCH = BAR_XRDY + 8;
constexpr int OFF_ZERO = OFF_MISC + 4096;
constexpr int SMEM_BYTES = OFF_MISC + 8192;

constexpr unsigned SPIN_LIMIT = 1u << 24;

constexpr int A2_N = 16 * 2 * 18 * 4 * 256;
__device__ uint4 g_A2[2 * A2_N];
__device__ float4 g_kvacc[2 * 8 * 272];
__device__ unsigned g_kvcnt[8];
__device__ unsigned g_epoch;
__device__ unsigned g_ticket;

#define TS(role, i)
#define TSW(role, i)

__device__ __forceinline__ uint32_t smem_u32(const void* p) { return (uint32_t)__cvta_generic_to_shared(p); }
__device__ __forceinline__ void mbar_init(uint32_t bar, uint32_t cnt) {
    asm volatile("mbarrier.init.shared::cta.b64 [%0], %1;" ::"r"(bar), "r"(cnt) : "memory");
}
__device__ __forceinline__ void mbar_expect_tx(uint32_t bar, uint32_t bytes) {
    asm volatile("mbarrier.arrive.expect_tx.shared::cta.b64 _, [%0], %1;" ::"r"(bar), "r"(bytes) : "memory");
}
__device__ __forceinline__ void mbar_arrive(uint32_t bar) {
    asm volatile("mbarrier.arrive.shared::cta.b64 _, [%0];" ::"r"(bar) : "memory");
}
__device__ __forceinline__ void mbar_arrive_cta(uint32_t bar, uint32_t cta) {
    asm volatile(
        "{\n.reg .b32 ra;\nmapa.shared::cluster.u32 ra, %0, %1;\n"
        "mbarrier.arrive.shared::cluster.b64 _, [ra];\n}" ::"r"(bar), "r"(cta) : "memory");
}
__device__ __forceinline__ void mbar_wait(uint32_t bar, uint32_t parity) {
    asm volatile(
        "{\n.reg .pred p, q;\n.reg .u32 n;\nmov.u32 n, 0;\n"
        "WAIT_%=:\n"
        "mbarrier.try_wait.parity.shared::cta.b64 p, [%0], %1;\n"
        "@p bra.uni DONE_%=;\n"
        "add.u32 n, n, 1;\n"
        "setp.gt.u32 q, n, %2;\n"
        "@q trap;\n"
        "bra.uni WAIT_%=;\n"
        "DONE_%=:\n}"
        ::"r"(bar), "r"(parity), "n"(SPIN_LIMIT) : "memory");
}
__device__ __forceinline__ unsigned ld_acquire(const unsigned* p) {
    unsigned v;
    asm volatile("ld.acquire.gpu.global.u32 %0, [%1];" : "=r"(v) : "l"(p) : "memory");
    return v;
}
__device__ __forceinline__ void st_release(unsigned* p, unsigned v) {
    asm volatile("st.release.gpu.global.u32 [%0], %1;" ::"l"(p), "r"(v) : "memory");
}
__device__ __forceinline__ unsigned read_epoch() {
    return __shfl_sync(0xffffffffu, *(volatile unsigned*)&g_epoch, 0) + 1;
}
__device__ __forceinline__ void tma_load(uint32_t dst, const CUtensorMap* tm, uint32_t bar, int x, int y) {
    asm volatile(
        "cp.async.bulk.tensor.2d.shared::cluster.global.mbarrier::complete_tx::bytes [%0], [%1, {%3, %4}], [%2];"
        ::"r"(dst), "l"(tm), "r"(bar), "r"(x), "r"(y) : "memory");
}
__device__ __forceinline__ void tma_load_mc(uint32_t dst, const CUtensorMap* tm, uint32_t bar, int x, int y) {
    asm volatile(
        "cp.async.bulk.tensor.2d.shared::cluster.global.mbarrier::complete_tx::bytes.multicast::cluster "
        "[%0], [%1, {%3, %4}], [%2], %5;"
        ::"r"(dst), "l"(tm), "r"(bar), "r"(x), "r"(y), "h"((uint16_t)3) : "memory");
}
__device__ __forceinline__ void prefetch_tm(const CUtensorMap* tm) {
    asm volatile("prefetch.tensormap [%0];" ::"l"(tm) : "memory");
}
__device__ __forceinline__ void l2_prefetch(const void* p, uint32_t bytes) {
    asm volatile("cp.async.bulk.prefetch.L2.global [%0], %1;" ::"l"(p), "r"(bytes) : "memory");
}
__device__ __forceinline__ void bar_sync(int id, int n) { asm volatile("bar.sync %0, %1;" ::"r"(id), "r"(n) : "memory"); }
__device__ __forceinline__ void bar_arrive(int id, int n) { asm volatile("bar.arrive %0, %1;" ::"r"(id), "r"(n) : "memory"); }
__device__ __forceinline__ void wg_fence() { asm volatile("wgmma.fence.sync.aligned;" ::: "memory"); }
__device__ __forceinline__ void wg_commit() { asm volatile("wgmma.commit_group.sync.aligned;" ::: "memory"); }
template <int N>
__device__ __forceinline__ void wg_wait() { asm volatile("wgmma.wait_group.sync.aligned %0;" ::"n"(N) : "memory"); }

__device__ __forceinline__ uint64_t make_desc(uint32_t addr, uint32_t lbo, uint32_t sbo, uint64_t swz) {
    return (uint64_t)((addr & 0x3FFFF) >> 4) | ((uint64_t)(lbo >> 4) << 16) | ((uint64_t)(sbo >> 4) << 32) | (swz << 62);
}

#define ACC8(a, o) "+f"(a[o]), "+f"(a[o + 1]), "+f"(a[o + 2]), "+f"(a[o + 3]), "+f"(a[o + 4]), "+f"(a[o + 5]), "+f"(a[o + 6]), "+f"(a[o + 7])
constexpr uint32_t DHI128 = (1024u >> 4) | (1u << 30);
constexpr uint32_t DHI64 = (512u >> 4) | (2u << 30);
__device__ __forceinline__ void wgmma_n128_rs(float (&d)[64], const uint32_t* a, uint32_t db, int scale_d) {
    asm volatile(
        "{\n.reg .pred p;\n.reg .b64 dd;\nsetp.ne.b32 p, %69, 0;\nmov.b64 dd, {%68, %70};\n"
        "wgmma.mma_async.sync.aligned.m64n128k16.f32.bf16.bf16 "
        "{%0,%1,%2,%3,%4,%5,%6,%7,%8,%9,%10,%11,%12,%13,%14,%15,%16,%17,%18,%19,%20,%21,%22,%23,%24,%25,%26,%27,%28,%29,%30,%31,"
        "%32,%33,%34,%35,%36,%37,%38,%39,%40,%41,%42,%43,%44,%45,%46,%47,%48,%49,%50,%51,%52,%53,%54,%55,%56,%57,%58,%59,%60,%61,%62,%63},"
        "{%64,%65,%66,%67}, dd, p, 1, 1, 1;\n}"
        : ACC8(d, 0), ACC8(d, 8), ACC8(d, 16), ACC8(d, 24), ACC8(d, 32), ACC8(d, 40), ACC8(d, 48), ACC8(d, 56)
        : "r"(a[0]), "r"(a[1]), "r"(a[2]), "r"(a[3]), "r"(db), "r"(scale_d), "n"(DHI128));
}
template <uint32_t HI>
__device__ __forceinline__ void wgmma_n64_rs(float (&d)[32], const uint32_t* a, uint32_t db, int scale_d) {
    asm volatile(
        "{\n.reg .pred p;\n.reg .b64 dd;\nsetp.ne.b32 p, %37, 0;\nmov.b64 dd, {%36, %38};\n"
        "wgmma.mma_async.sync.aligned.m64n64k16.f32.bf16.bf16 "
        "{%0,%1,%2,%3,%4,%5,%6,%7,%8,%9,%10,%11,%12,%13,%14,%15,%16,%17,%18,%19,%20,%21,%22,%23,%24,%25,%26,%27,%28,%29,%30,%31},"
        "{%32,%33,%34,%35}, dd, p, 1, 1, 1;\n}"
        : ACC8(d, 0), ACC8(d, 8), ACC8(d, 16), ACC8(d, 24)
        : "r"(a[0]), "r"(a[1]), "r"(a[2]), "r"(a[3]), "r"(db), "r"(scale_d), "n"(HI));
}
__device__ __forceinline__ void wgmma_n64_ss_tt(float (&d)[32], uint64_t da, uint64_t db, int scale_d) {
    asm volatile(
        "{\n.reg .pred p;\nsetp.ne.b32 p, %34, 0;\n"
        "wgmma.mma_async.sync.aligned.m64n64k16.f32.bf16.bf16 "
        "{%0,%1,%2,%3,%4,%5,%6,%7,%8,%9,%10,%11,%12,%13,%14,%15,%16,%17,%18,%19,%20,%21,%22,%23,%24,%25,%26,%27,%28,%29,%30,%31},"
        "%32, %33, p, 1, 1, 1, 1;\n}"
        : ACC8(d, 0), ACC8(d, 8), ACC8(d, 16), ACC8(d, 24)
        : "l"(da), "l"(db), "r"(scale_d));
}
__device__ __forceinline__ void wgmma_n8_ss_tn(float (&d)[4], uint64_t da, uint64_t db, int scale_d) {
    asm volatile(
        "{\n.reg .pred p;\nsetp.ne.b32 p, %6, 0;\n"
        "wgmma.mma_async.sync.aligned.m64n8k16.f32.bf16.bf16 {%0,%1,%2,%3}, %4, %5, p, 1, 1, 1, 0;\n}"
        : "+f"(d[0]), "+f"(d[1]), "+f"(d[2]), "+f"(d[3])
        : "l"(da), "l"(db), "r"(scale_d));
}
template <int N>
__device__ __forceinline__ void acc_fence(float (&d)[N]) {
#pragma unroll
    for (int i = 0; i < N; i++) asm volatile("" : "+f"(d[i])::"memory");
}
__device__ __forceinline__ void mma16816(float (&c)[4], const uint32_t* a, uint32_t b0, uint32_t b1) {
    asm volatile(
        "mma.sync.aligned.m16n8k16.row.col.f32.bf16.bf16.f32 {%0,%1,%2,%3}, {%4,%5,%6,%7}, {%8,%9}, {%0,%1,%2,%3};"
        : "+f"(c[0]), "+f"(c[1]), "+f"(c[2]), "+f"(c[3])
        : "r"(a[0]), "r"(a[1]), "r"(a[2]), "r"(a[3]), "r"(b0), "r"(b1));
}
__device__ __forceinline__ uint32_t pack_bf16(float lo, float hi) {
    uint32_t r;
    asm("cvt.rn.bf16x2.f32 %0, %1, %2;" : "=r"(r) : "f"(hi), "f"(lo));
    return r;
}
__device__ __forceinline__ float bf_lo(uint32_t v) { return __uint_as_float(v << 16); }
__device__ __forceinline__ float bf_hi(uint32_t v) { return __uint_as_float(v & 0xffff0000u); }
__device__ __forceinline__ float bf16_round(float v) { return __bfloat162float(__float2bfloat16_rn(v)); }
__device__ __forceinline__ float sqrt_fast(float v) {
    float r;
    asm("sqrt.approx.ftz.f32 %0, %1;" : "=f"(r) : "f"(v));
    return r;
}
__device__ __forceinline__ float rcp_fast(float v) {
    float r;
    asm("rcp.approx.ftz.f32 %0, %1;" : "=f"(r) : "f"(v));
    return r;
}
__device__ __forceinline__ float ex2_fast(float v) {
    float r;
    asm("ex2.approx.ftz.f32 %0, %1;" : "=f"(r) : "f"(v));
    return r;
}
struct RowScale { float rho, rl, var; };
__device__ __forceinline__ float phi_f(float a, const RowScale& r) {
    return fmaf(fmaxf(a, 0.f), r.rho, ex2_fast(fminf(a, 0.f) * r.rl) + 1e-6f);
}
__device__ __forceinline__ float swiglu_f(float ga, float ua, const RowScale& r) {
    return (ga * ua) * rcp_fast(fmaf(ex2_fast(-ga * r.rl), r.var, r.var));
}
__device__ __forceinline__ uint4 swiglu8(const float* gp, const float* up, const RowScale& r0, const RowScale& r1) {
    uint4 v;
    v.x = pack_bf16(swiglu_f(gp[0], up[0], r0), swiglu_f(gp[1], up[1], r0));
    v.y = pack_bf16(swiglu_f(gp[2], up[2], r1), swiglu_f(gp[3], up[3], r1));
    v.z = pack_bf16(swiglu_f(gp[4], up[4], r0), swiglu_f(gp[5], up[5], r0));
    v.w = pack_bf16(swiglu_f(gp[6], up[6], r1), swiglu_f(gp[7], up[7], r1));
    v.y = v.y ? v.y : 0x8000u;
    v.w = v.w ? v.w : 0x8000u;
    return v;
}
__device__ __forceinline__ bool frag_stale(const uint4 (&f)[12]) {
    unsigned v = min(f[0].y, f[0].w);
#pragma unroll
    for (int i = 1; i < 12; i++) v = min(v, min(f[i].y, f[i].w));
    return __any_sync(0xffffffffu, v == 0u);
}
__device__ __forceinline__ void st_frag(uint4* p, uint4 v) {
    asm volatile("st.relaxed.gpu.global.v4.u32 [%0], {%1,%2,%3,%4};" ::"l"(p), "r"(v.x), "r"(v.y), "r"(v.z), "r"(v.w) : "memory");
}
__device__ __forceinline__ uint4 ld_frag(const uint4* p) {
    uint4 v;
    asm volatile("ld.relaxed.gpu.global.v4.u32 {%0,%1,%2,%3}, [%4];" : "=r"(v.x), "=r"(v.y), "=r"(v.z), "=r"(v.w) : "l"(p) : "memory");
    return v;
}
__device__ __forceinline__ void red_add2(float* p, float a, float b) {
    asm volatile("red.global.add.v2.f32 [%0], {%1, %2};" ::"l"(p), "f"(a), "f"(b) : "memory");
}
__device__ __forceinline__ void cp_async16(uint32_t dst, const void* src) {
    asm volatile("cp.async.cg.shared.global [%0], [%1], 16;" ::"r"(dst), "l"(src) : "memory");
}

__device__ __forceinline__ int ring_lap(int u) { return (u * 79) >> 10; }
__device__ __forceinline__ int ring_slot(int u) { return u - NST * ring_lap(u); }

__device__ __forceinline__ void mainloop128(float (&acc)[64], const uint32_t (&xa)[128], int u0, uint32_t sb,
                                            uint32_t desc128, int lane, int wg, bool last = false) {
    bar_sync(7 + wg, 256);
#pragma unroll
    for (int kb = 0; kb < 8; kb++) {
        const int st = ring_slot(u0 + kb);
        mbar_wait(sb + BAR_FULL + 8 * st, ring_lap(u0 + kb) & 1);
        wg_fence();
        const uint32_t d = desc128 + st * (STAGE_BYTES >> 4);
#pragma unroll
        for (int ks = 0; ks < 4; ks++) wgmma_n128_rs(acc, &xa[(kb * 4 + ks) * 4], d + ks * 128, (kb | ks) != 0);
        wg_commit();
        if (kb == 7 && !(last && wg == 1)) bar_arrive(8 - wg, 256);
        if (kb > 0) {
            wg_wait<1>();
            if (lane < 2) mbar_arrive_cta(sb + BAR_EMPTY + 8 * ring_slot(u0 + kb - 1), lane);
        }
    }
    wg_wait<0>();
    acc_fence(acc);
    if (lane < 2) mbar_arrive_cta(sb + BAR_EMPTY + 8 * ring_slot(u0 + 7), lane);
}
__device__ __forceinline__ void mainloop64x2(float (&a0)[32], float (&a1)[32], const uint32_t (&xa)[128], int u0,
                                             uint32_t sb, uint32_t desc128, int lane, int wg) {
    bar_sync(7 + wg, 256);
#pragma unroll
    for (int kb = 0; kb < 8; kb++) {
        const int st = ring_slot(u0 + kb);
        mbar_wait(sb + BAR_FULL + 8 * st, ring_lap(u0 + kb) & 1);
        wg_fence();
        const uint32_t d = desc128 + st * (STAGE_BYTES >> 4);
        const uint32_t d2 = d + (8192 >> 4) - ((4096u >> 4) << 16);
#pragma unroll
        for (int ks = 0; ks < 4; ks++) {
            wgmma_n64_rs<DHI128>(a0, &xa[(kb * 4 + ks) * 4], d + ks * 128, (kb | ks) != 0);
            wgmma_n64_rs<DHI64>(a1, &xa[(kb * 4 + ks) * 4], d2 + ks * 64, (kb | ks) != 0);
        }
        wg_commit();
        if (kb == 7) bar_arrive(8 - wg, 256);
        if (kb > 0) {
            wg_wait<1>();
            if (lane < 2) mbar_arrive_cta(sb + BAR_EMPTY + 8 * ring_slot(u0 + kb - 1), lane);
        }
    }
    wg_wait<0>();
    acc_fence(a0);
    acc_fence(a1);
    if (lane < 2) mbar_arrive_cta(sb + BAR_EMPTY + 8 * ring_slot(u0 + 7), lane);
}

__global__ void __cluster_dims__(2, 1, 1) __launch_bounds__(384, 1)
fused_kernel(const __grid_constant__ CUtensorMap tm_x, const __grid_constant__ CUtensorMap tm_qkv,
             const __grid_constant__ CUtensorMap tm_w1, const __grid_constant__ CUtensorMap tm_w3,
             const __grid_constant__ CUtensorMap tm_w1h, const __grid_constant__ CUtensorMap tm_w3h,
             const __grid_constant__ CUtensorMap tm_w2, const __grid_constant__ CUtensorMap tm_w2h,
             const __grid_constant__ CUtensorMap tm_wo, const __nv_bfloat16* __restrict__ xg,
             __nv_bfloat16* __restrict__ outg, const char* __restrict__ p_qkv, const char* __restrict__ p_w1,
             const char* __restrict__ p_w3, const char* __restrict__ p_w2, const char* __restrict__ p_wo) {
    extern __shared__ __align__(1024) uint8_t smem[];
    const uint32_t sb = smem_u32(smem);
    const int tid = threadIdx.x;
    const int warp = tid >> 5, lane = tid & 31;
    const int rank = blockIdx.x & 1;
    const int pair = blockIdx.x >> 1;
    const int c = pair & 7;
    const int m = (pair >> 3) * 2 + rank;
    const int m2 = (pair >> 3) * 2 + (c & 1);
    const int j2 = c >> 1;

    TS(tid >> 7, 0);
    if (tid == 256) {
#pragma unroll
        for (int i = 0; i < 8; i++) mbar_init(sb + BAR_XFULL + 8 * i, 1);
        asm volatile("fence.proxy.async.shared::cta;" ::: "memory");
#pragma unroll
        for (int kb = 0; kb < 8; kb++) {
            mbar_expect_tx(sb + BAR_XFULL + 8 * kb, 16384);
            tma_load(sb + (XST0 + kb) * STAGE_BYTES, &tm_x, sb + BAR_XFULL + 8 * kb, kb * 64, m * 128);
        }
        TS(2, 21);
    } else if (tid == 0) {
#pragma unroll
        for (int i = 0; i < NST; i++) mbar_init(sb + BAR_FULL + 8 * i, 1);
        asm volatile("fence.mbarrier_init.release.cluster;" ::: "memory");
    } else if (tid == 32) {
#pragma unroll
        for (int i = 0; i < NST; i++) mbar_init(sb + BAR_EMPTY + 8 * i, 16);
        asm volatile("fence.mbarrier_init.release.cluster;" ::: "memory");
    } else if (tid == 64) {
#pragma unroll
        for (int i = 0; i < 4; i++) mbar_init(sb + BAR_KVREADY + 8 * i, 1);
        mbar_expect_tx(sb + BAR_XCHG, 32768);
        asm volatile("fence.mbarrier_init.release.cluster;" ::: "memory");
    } else if (tid >= 128 && tid < 256) {
        ((uint4*)(smem + OFF_ZERO))[tid - 128] = make_uint4(0, 0, 0, 0);
        ((uint4*)(smem + OFF_ZERO))[tid] = make_uint4(0, 0, 0, 0);
        asm volatile("fence.proxy.async.shared::cta;" ::: "memory");
    } else if (tid == 288) {
        prefetch_tm(&tm_qkv);
        prefetch_tm(rank ? &tm_w3 : &tm_w1);
        prefetch_tm(&tm_w1h);
        prefetch_tm(&tm_w3h);
        prefetch_tm(&tm_w2);
        prefetch_tm(&tm_w2h);
        prefetch_tm(&tm_wo);
    } else if (tid >= 320) {
        ((uint32_t*)(smem + OFF_ONES))[tid - 320] = 0x3F803F80u;
        asm volatile("fence.proxy.async.shared::cta;" ::: "memory");
    }
    __syncthreads();
    TS(tid >> 7, 22);
    asm volatile("barrier.cluster.arrive.relaxed.aligned;\nbarrier.cluster.wait.acquire.aligned;" ::: "memory");

    if (warp >= 8) {
        asm volatile("setmaxnreg.dec.sync.aligned.u32 40;");
        if (warp == 8) {
            if (lane == 0) {
                int st = 0;
                uint32_t lap = 0;
                for (int it = 0; it < 40; it++) {
                    const int tile = it >> 3, kb = it & 7;
                    const uint32_t full = sb + BAR_FULL + 8 * st;
                    mbar_wait(sb + BAR_EMPTY + 8 * st, (st >= XST0) ? (lap & 1) : ((lap & 1) ^ 1));
                    mbar_expect_tx(full, STAGE_BYTES);
                    const uint32_t dst = sb + st * STAGE_BYTES;
                    if (tile == 0) {
                        tma_load_mc(dst + rank * 8192, &tm_qkv, full, 512 + 512 * rank + 64 * c, kb * 64);
                    } else if (tile != 3) {
                        tma_load_mc(dst + rank * 8192, rank ? &tm_w3 : &tm_w1, full, 224 * c + 64 * (tile == 4 ? 2 : tile - 1), kb * 64);
                    } else if (rank == 0) {
                        tma_load_mc(dst, &tm_qkv, full, 64 * c, kb * 64);
                    } else {
                        tma_load_mc(dst + 8192, &tm_w1h, full, 224 * c + 192, kb * 64);
                        tma_load_mc(dst + 12288, &tm_w3h, full, 224 * c + 192, kb * 64);
                    }
                    if (++st == NST) { st = 0; lap++; }
                    if (it == 7) {
                        mbar_wait(sb + BAR_EMPTY + 8 * SCR0, 0);
                        mbar_arrive(sb + BAR_FULL + 8 * SCR0);
                        mbar_wait(sb + BAR_EMPTY + 8 * (SCR0 + 1), 0);
                        mbar_arrive(sb + BAR_FULL + 8 * (SCR0 + 1));
                        st += 2;
                    }
                }
                TS(2, 1);
                for (int b = 0; b < 18; b++) {
                    const uint32_t full = sb + BAR_FULL + 8 * st;
                    const uint32_t dst = sb + st * STAGE_BYTES;
                    mbar_wait(sb + BAR_EMPTY + 8 * st, (st >= XST0) ? (lap & 1) : ((lap & 1) ^ 1));
                    mbar_expect_tx(full, STAGE_BYTES);
                    if (b < 8 || b >= 14) {
                        const int row = (b < 8) ? 224 * (4 * rank + (b & 3)) + 64 * (b >> 2) : 224 * (4 * rank + b - 14) + 128;
                        tma_load(dst, &tm_w2, full, 128 * j2, row);
                        tma_load(dst + 8192, &tm_w2, full, 128 * j2 + 64, row);
                    } else if (b < 10) {
                        const int row = 224 * (4 * rank + 2 * (b - 8)) + 192;
                        tma_load(dst, &tm_w2h, full, 128 * j2, row);
                        tma_load(dst + 4096, &tm_w2h, full, 128 * j2, row + 224);
                        tma_load(dst + 8192, &tm_w2h, full, 128 * j2 + 64, row);
                        tma_load(dst + 12288, &tm_w2h, full, 128 * j2 + 64, row + 224);
                    } else {
                        const int row = 64 * (4 * rank + (b - 10));
                        tma_load(dst, &tm_wo, full, 128 * j2, row);
                        tma_load(dst + 8192, &tm_wo, full, 128 * j2 + 64, row);
                    }
                    TS(2, 2 + b);
                    if (++st == NST) { st = 0; lap++; }
                }
                mbar_wait(sb + BAR_EMPTY + 8 * SCR0, lap & 1);
                mbar_wait(sb + BAR_EMPTY + 8 * (SCR0 + 1), lap & 1);
                mbar_arrive_cta(sb + BAR_XRDY, rank ^ 1);
            }
        } else if (warp < 11) {
            const int wg = warp - 9;
            bar_sync(3 + wg, 160);
            if (lane == 0) asm volatile("red.release.gpu.global.add.u32 [%0], 1;" ::"l"(&g_kvcnt[c]) : "memory");
            TSW(3, wg);
        } else {
            const unsigned epoch = read_epoch();
            if (lane == 0) {
                const unsigned tk = atomicInc(&g_ticket, 127u);
                if (tk == 127u) *(volatile unsigned*)&g_epoch = epoch;
            }
            if (lane == 0) *(volatile unsigned*)(smem + OFF_EPOCH) = epoch;
            __syncwarp();
            if (lane == 0) mbar_arrive(sb + BAR_EPOCH);
            if (lane < 17) g_kvacc[(((epoch & 1) ^ 1) * 8 + c) * 272 + 17 * m + lane] = make_float4(0.f, 0.f, 0.f, 0.f);
            {
                unsigned n = 0;
                while ((int)(ld_acquire(&g_kvcnt[c]) - 32u * epoch) < 0) {
                    __nanosleep(200);
                    if (++n > SPIN_LIMIT) asm volatile("trap;");
                }
            }
            TSW(4, 0);
            const int g = lane >> 2, t = lane & 3;
            const float* ks = (const float*)(g_kvacc + ((epoch & 1) * 8 + c) * 272) + 32 * t + g;
            uint2* kf = (uint2*)(smem + OFF_KVFRAG) + lane;
#pragma unroll 2
            for (int hh = 0; hh < 4; hh++) {
                const float* k = ks + hh * 272;
                const float a0 = __ldcg(k), a1 = __ldcg(k + 16), a2 = __ldcg(k + 128), a3 = __ldcg(k + 144);
                const float b0 = __ldcg(k + 8), b1 = __ldcg(k + 24), b2 = __ldcg(k + 136), b3 = __ldcg(k + 152);
                const float2 z0 = __ldcg((const float2*)(k - g - 30 * t + 256)), z1 = __ldcg((const float2*)(k - g - 30 * t + 264));
                kf[(hh * 3 + 0) * 32] = make_uint2(pack_bf16(a0, a1), pack_bf16(a2, a3));
                kf[(hh * 3 + 1) * 32] = make_uint2(pack_bf16(b0, b1), pack_bf16(b2, b3));
                kf[(hh * 3 + 2) * 32] = make_uint2(pack_bf16(z0.x, z0.y), pack_bf16(z1.x, z1.y));
            }
            __syncwarp();
            if (lane == 0) mbar_arrive(sb + BAR_KVREADY);
            TSW(4, 4);
            if (lane == 0) {
                char* z = (char*)(g_A2 + (size_t)((epoch & 1) ^ 1) * A2_N + (size_t)((m * 2 + (c >> 2)) * 18) * 4 * 256);
                const int cc = c & 3;
#pragma unroll 1
                for (int i = 0; i < 18; i++) {
                    const int blk = (i < 8) ? ((i >> 2) * 4 + cc) * 4 + (i & 3)
                                  : (i < 10) ? (8 + (cc >> 1)) * 4 + 2 * (cc & 1) + (i - 8)
                                  : (i < 14) ? (10 + cc) * 4 + (i - 10) : (14 + cc) * 4 + (i - 14);
                    asm volatile("cp.async.bulk.global.shared::cta.bulk_group [%0], [%1], 4096;"
                                 ::"l"(z + (size_t)blk * 4096), "r"(sb + OFF_ZERO) : "memory");
                }
                asm volatile("cp.async.bulk.commit_group;" ::: "memory");
            }
            if (lane == 0) asm volatile("cp.async.bulk.wait_group 0;" ::: "memory");
        }
    } else {
        asm volatile("setmaxnreg.inc.sync.aligned.u32 232;");
        const int wg = warp >> 2, w = warp & 3;
        const int g = lane >> 2, t = lane & 3;
        float acc[64];
        uint32_t xa[128];
        float rho0, rho1;
        RowScale r0, r1;
        unsigned par;

        TS(wg, 1);
        {
            const int row = wg * 64 + w * 16 + (lane & 7) + ((lane >> 3) & 1) * 8;
            const uint32_t rbase = sb + XST0 * STAGE_BYTES + row * 128;
            const int hi = lane >> 4, r7 = lane & 7;
            float sm[2][4], c0[2][4], c1[2][4];
#pragma unroll
            for (int i = 0; i < 8; i++) { sm[i >> 2][i & 3] = 0.f; c0[i >> 2][i & 3] = 0.f; c1[i >> 2][i & 3] = 0.f; }
            if (wg == 1) bar_arrive(7, 256);
#pragma unroll
            for (int kb = 0; kb < 8; kb++) {
                mbar_wait(sb + BAR_XFULL + 8 * kb, 0);
#pragma unroll
                for (int ks = 0; ks < 4; ks++) {
                    uint32_t* a = &xa[(kb * 4 + ks) * 4];
                    const uint32_t addr = rbase + kb * STAGE_BYTES + (((2 * ks + hi) ^ r7) << 4);
                    asm volatile("ldmatrix.sync.aligned.m8n8.x4.shared.b16 {%0,%1,%2,%3}, [%4];"
                                 : "=r"(a[0]), "=r"(a[1]), "=r"(a[2]), "=r"(a[3]) : "r"(addr) : "memory");
                    mma16816(sm[ks & 1], a, 0x3F803F80u, 0x3F803F80u);
                    mma16816(c0[ks & 1], a, a[0], a[2]);
                    mma16816(c1[ks & 1], a, a[1], a[3]);
                }
            }
            TS(wg, 2);
            const float mean0 = (sm[0][0] + sm[1][0]) * (1.f / 512.f);
            const float mean1 = (sm[0][2] + sm[1][2]) * (1.f / 512.f);
            __syncwarp();
            if (lane < 16) mbar_arrive_cta(sb + BAR_EMPTY + 8 * (XST0 + (lane >> 1)), lane & 1);
            const __nv_bfloat162 mb0 = __float2bfloat162_rn(mean0), mb1 = __float2bfloat162_rn(mean1);
#pragma unroll
            for (int i = 0; i < 128; i++) {
                __nv_bfloat162 v = *reinterpret_cast<__nv_bfloat162*>(&xa[i]);
                v = __hsub2(v, (i & 1) ? mb1 : mb0);
                xa[i] = *reinterpret_cast<uint32_t*>(&v);
            }
            const float d0 = (g & 1) ? c0[0][1] + c0[1][1] : c0[0][0] + c0[1][0];
            const float d1 = (g & 1) ? c1[0][3] + c1[1][3] : c1[0][2] + c1[1][2];
            const int src = (lane & ~3) | (g >> 1);
            const float var0 = fmaxf(__shfl_sync(0xffffffffu, d0, src) * (1.f / 512.f) - mean0 * mean0, 0.f);
            const float var1 = fmaxf(__shfl_sync(0xffffffffu, d1, src) * (1.f / 512.f) - mean1 * mean1, 0.f);
            const float sd0 = bf16_round(sqrt_fast(bf16_round(bf16_round(var0) + 1e-5f)));
            const float sd1 = bf16_round(sqrt_fast(bf16_round(bf16_round(var1) + 1e-5f)));
            rho0 = rcp_fast(sd0);
            rho1 = rcp_fast(sd1);
            r0.rho = rho0; r0.rl = rho0 * 1.4426950408889634f; r0.var = sd0 * sd0;
            r1.rho = rho1; r1.rl = rho1 * 1.4426950408889634f; r1.var = sd1 * sd1;
        }

        TS(wg, 3);
        const uint32_t desc128 = ((sb & 0x3FFFF) >> 4) | ((8192u >> 4) << 16);
        const int cc = c & 3;

        {
            mainloop128(acc, xa, 0, sb, desc128, lane, wg);
            TS(wg, 4);
            {
                TS(wg, 24);
                const uint32_t pkb = sb + (SCR0 + wg) * STAGE_BYTES;
                mbar_wait(sb + BAR_FULL + 8 * (SCR0 + wg), 0);
                const uint32_t ra = pkb + (w * 16 + g) * 128 + t * 4;
#pragma unroll
                for (int nb = 0; nb < 8; nb++) {
                    const uint32_t off = (uint32_t)((nb ^ g) << 4);
                    uint32_t p0 = pack_bf16(phi_f(acc[nb * 4], r0), phi_f(acc[nb * 4 + 1], r0));
                    uint32_t p1 = pack_bf16(phi_f(acc[nb * 4 + 2], r1), phi_f(acc[nb * 4 + 3], r1));
                    uint32_t v0 = pack_bf16(acc[32 + nb * 4] * rho0, acc[32 + nb * 4 + 1] * rho0);
                    uint32_t v1 = pack_bf16(acc[32 + nb * 4 + 2] * rho1, acc[32 + nb * 4 + 3] * rho1);
                    asm volatile("st.shared.u32 [%0], %1;" ::"r"(ra + off), "r"(p0) : "memory");
                    asm volatile("st.shared.u32 [%0], %1;" ::"r"(ra + off + 1024), "r"(p1) : "memory");
                    asm volatile("st.shared.u32 [%0], %1;" ::"r"(ra + off + 8192), "r"(v0) : "memory");
                    asm volatile("st.shared.u32 [%0], %1;" ::"r"(ra + off + 8192 + 1024), "r"(v1) : "memory");
                }
                TS(wg, 25);
                asm volatile("fence.proxy.async.shared::cta;" ::: "memory");
                bar_sync(1 + wg, 128);
                TS(wg, 26);
                const uint64_t da = make_desc(pkb, 8192, 1024, 1);
                const uint64_t db = make_desc(pkb + 8192, 8192, 1024, 1);
                const uint64_t d1 = make_desc(sb + OFF_ONES, 128, 128, 0);
                float kva[32], za[4];
                wg_fence();
#pragma unroll
                for (int ks = 0; ks < 4; ks++) {
                    wgmma_n64_ss_tt(kva, da + ks * 128, db + ks * 128, ks != 0);
                    wgmma_n8_ss_tn(za, da + ks * 128, d1, ks != 0);
                }
                wg_commit();
                wg_wait<0>();
                acc_fence(kva);
                acc_fence(za);
                if (lane < 4) mbar_arrive_cta(sb + BAR_EMPTY + 8 * (SCR0 + (lane >> 1)), lane & 1);
                TS(wg, 27);
                float o[8];
#pragma unroll
                for (int i = 0; i < 8; i++)
                    o[i] = (w == 0) ? kva[i] : (w == 1) ? kva[8 + i] : (w == 2) ? kva[16 + i] : kva[24 + i];
                mbar_wait(sb + BAR_EPOCH, 0);
                par = *(volatile unsigned*)(smem + OFF_EPOCH) & 1;
                float* dst = (float*)(g_kvacc + (par * 8 + c) * 272) + w * 272 + g * 16 + 2 * t;
                red_add2(dst, o[0], o[1]);
                red_add2(dst + 128, o[2], o[3]);
                red_add2(dst + 8, o[4], o[5]);
                red_add2(dst + 136, o[6], o[7]);
                if (t == 0) {
                    atomicAdd(dst - g * 15 + 256, za[0]);
                    atomicAdd(dst - g * 15 + 264, za[2]);
                }
            }
            bar_arrive(3 + wg, 160);
            TS(wg, 5);
        }
        uint4* a2w = g_A2 + (size_t)par * A2_N + (size_t)((m * 2 + (c >> 2)) * 18) * 4 * 256 + warp * 32 + lane;
#pragma unroll
        for (int tile = 1; tile < 3; tile++) {
            mainloop128(acc, xa, 2 + 8 * tile, sb, desc128, lane, wg);
            TS(wg, 4 + 2 * tile);
            uint4* dst = a2w + (size_t)((4 * (tile - 1) + cc) * 4) * 256;
#pragma unroll
            for (int ks = 0; ks < 4; ks++) st_frag(dst + ks * 256, swiglu8(&acc[ks * 8], &acc[32 + ks * 8], r0, r1));
            TS(wg, 5 + 2 * tile);
        }
        {
            float qa[32], gu[32];
            mainloop64x2(qa, gu, xa, 26, sb, desc128, lane, wg);
            TS(wg, 10);
            uint4* dst = a2w + (size_t)((8 + (cc >> 1)) * 4 + 2 * (cc & 1)) * 256;
#pragma unroll
            for (int ks = 0; ks < 2; ks++) st_frag(dst + ks * 256, swiglu8(&gu[ks * 8], &gu[16 + ks * 8], r0, r1));
            TS(wg, 13);
            mbar_wait(sb + BAR_KVREADY, 0);
            TS(wg, 14);
            const uint2* kf = (const uint2*)(smem + OFF_KVFRAG);
            dst = a2w + (size_t)((10 + cc) * 4) * 256;
#pragma unroll
            for (int hh = 0; hh < 4; hh++) {
                const float* q = &qa[hh * 8];
                uint32_t a[4];
                a[0] = pack_bf16(phi_f(q[0], r0), phi_f(q[1], r0));
                a[1] = pack_bf16(phi_f(q[2], r1), phi_f(q[3], r1));
                a[2] = pack_bf16(phi_f(q[4], r0), phi_f(q[5], r0));
                a[3] = pack_bf16(phi_f(q[6], r1), phi_f(q[7], r1));
                float n0[4] = {0.f, 0.f, 0.f, 0.f}, n1[4] = {0.f, 0.f, 0.f, 0.f}, dn[4] = {0.f, 0.f, 0.f, 0.f};
                const uint2 b0 = kf[(hh * 3 + 0) * 32 + lane], b1 = kf[(hh * 3 + 1) * 32 + lane],
                            bz = kf[(hh * 3 + 2) * 32 + lane];
                mma16816(n0, a, b0.x, b0.y);
                mma16816(n1, a, b1.x, b1.y);
                mma16816(dn, a, bz.x, bz.y);
                const float i0 = rcp_fast(dn[0] + 1e-6f), i1 = rcp_fast(dn[2] + 1e-6f);
                uint4 v;
                v.x = pack_bf16(n0[0] * i0, n0[1] * i0);
                v.y = pack_bf16(n0[2] * i1, n0[3] * i1);
                v.z = pack_bf16(n1[0] * i0, n1[1] * i0);
                v.w = pack_bf16(n1[2] * i1, n1[3] * i1);
                v.y = v.y ? v.y : 0x8000u;
                v.w = v.w ? v.w : 0x8000u;
                st_frag(dst + hh * 256, v);
            }
            TS(wg, 11);
        }
        const uint4* a2r = g_A2 + (size_t)par * A2_N + (size_t)((m2 * 2 + rank) * 18) * 4 * 256 + warp * 32 + lane;
        uint4 af[2][12];
        {
            mainloop128(acc, xa, 34, sb, desc128, lane, wg, true);
            TS(wg, 12);
#pragma unroll
            for (int i = 0; i < 12; i++) af[0][i] = ld_frag(a2r + i * 256);
            uint4* dst = a2w + (size_t)((14 + cc) * 4) * 256;
#pragma unroll
            for (int ks = 0; ks < 4; ks++) st_frag(dst + ks * 256, swiglu8(&acc[ks * 8], &acc[32 + ks * 8], r0, r1));
            TS(wg, 15);
        }

        {
            float ao[32], ap[32];
            const uint32_t dso = desc128 + rank * 512, dsp = desc128 + (rank ^ 1) * 512;
            TS(wg, 16);
#pragma unroll
            for (int gi = 0; gi < 6; gi++) {
                if (gi == 5) TS(wg, 17);
                uint4(&f)[12] = af[gi & 1];
                {
                    unsigned n = 0;
                    while (frag_stale(f)) {
#pragma unroll
                        for (int i = 0; i < 12; i++) f[i] = ld_frag(a2r + (gi * 12 + i) * 256);
                        if (++n > SPIN_LIMIT) asm volatile("trap;");
                    }
                }
#pragma unroll
                for (int bb = 0; bb < 3; bb++)
                    mbar_wait(sb + BAR_FULL + 8 * ring_slot(42 + gi * 3 + bb), ring_lap(42 + gi * 3 + bb) & 1);
                wg_fence();
#pragma unroll
                for (int bb = 0; bb < 3; bb++) {
                    const int u = 42 + gi * 3 + bb;
                    const uint32_t so = ring_slot(u) * (STAGE_BYTES >> 4);
#pragma unroll
                    for (int ks = 0; ks < 4; ks++) {
                        const uint32_t* a = reinterpret_cast<const uint32_t*>(&f[bb * 4 + ks]);
                        wgmma_n64_rs<DHI128>(ap, a, dsp + so + ks * 128, (gi | bb | ks) != 0);
                        if (gi < 5) wgmma_n64_rs<DHI128>(ao, a, dso + so + ks * 128, (gi | bb | ks) != 0);
                    }
                }
                wg_commit();
                if (gi < 5) {
                    if (gi > 0) {
                        wg_wait<1>();
                        if (lane < 6) mbar_arrive(sb + BAR_EMPTY + 8 * ring_slot(39 + gi * 3 + (lane >> 1)));
                    }
#pragma unroll
                    for (int i = 0; i < 12; i++) af[(gi + 1) & 1][i] = ld_frag(a2r + ((gi + 1) * 12 + i) * 256);
                }
            }
#pragma unroll
            for (int i = 0; i < 12; i++)
                wgmma_n64_rs<DHI128>(ao, reinterpret_cast<const uint32_t*>(&af[1][i]),
                                     dso + ring_slot(57 + (i >> 2)) * (STAGE_BYTES >> 4) + (i & 3) * 128, 1);
            wg_commit();
            const int row0 = m2 * 128 + wg * 64 + w * 16 + g;
            const int col0 = j2 * 128 + rank * 64 + 2 * t;
            uint32_t xr[16];
#pragma unroll
            for (int nb = 0; nb < 8; nb++) {
                xr[2 * nb] = __ldg((const uint32_t*)(xg + (size_t)row0 * 512 + col0 + nb * 8));
                xr[2 * nb + 1] = __ldg((const uint32_t*)(xg + (size_t)(row0 + 8) * 512 + col0 + nb * 8));
            }
            uint32_t rdst, rbar;
            asm volatile("mapa.shared::cluster.u32 %0, %1, %2;"
                         : "=r"(rdst) : "r"(sb + (SCR0 + wg) * STAGE_BYTES + (tid & 127) * 16), "r"(rank ^ 1));
            asm volatile("mapa.shared::cluster.u32 %0, %1, %2;" : "=r"(rbar) : "r"(sb + BAR_XCHG), "r"(rank ^ 1));
            mbar_wait(sb + BAR_XRDY, 0);
            wg_wait<1>();
            acc_fence(ap);
            TS(wg, 18);
#pragma unroll
            for (int i = 0; i < 8; i++)
                asm volatile("st.async.shared::cluster.mbarrier::complete_tx::bytes.v4.f32 [%0], {%1,%2,%3,%4}, [%5];"
                             ::"r"(rdst + i * 2048), "f"(ap[4 * i]), "f"(ap[4 * i + 1]), "f"(ap[4 * i + 2]), "f"(ap[4 * i + 3]),
                             "r"(rbar) : "memory");
            wg_wait<0>();
            acc_fence(ao);
            mbar_wait(sb + BAR_XCHG, 0);
            TS(wg, 19);
            const float4* rx = (const float4*)(smem + (SCR0 + wg) * STAGE_BYTES) + (tid & 127);
#pragma unroll
            for (int nb = 0; nb < 8; nb++) {
                const float4 p = rx[nb * 128];
                const uint32_t o0 = pack_bf16(ao[4 * nb] + p.x + bf_lo(xr[2 * nb]), ao[4 * nb + 1] + p.y + bf_hi(xr[2 * nb]));
                const uint32_t o1 = pack_bf16(ao[4 * nb + 2] + p.z + bf_lo(xr[2 * nb + 1]), ao[4 * nb + 3] + p.w + bf_hi(xr[2 * nb + 1]));
                *(uint32_t*)(outg + (size_t)row0 * 512 + col0 + nb * 8) = o0;
                *(uint32_t*)(outg + (size_t)(row0 + 8) * 512 + col0 + nb * 8) = o1;
            }
        }
        TS(wg, 20);
    }
}

typedef CUresult (*EncodeFn)(CUtensorMap*, CUtensorMapDataType, cuuint32_t, void*, const cuuint64_t*, const cuuint64_t*,
                             const cuuint32_t*, const cuuint32_t*, CUtensorMapInterleave, CUtensorMapSwizzle,
                             CUtensorMapL2promotion, CUtensorMapFloatOOBfill);

void make_map(EncodeFn enc, CUtensorMap* tm, const void* ptr, int rows, int cols, int box_rows, int box_cols,
              CUtensorMapSwizzle swz) {
    cuuint64_t dims[2] = {(cuuint64_t)cols, (cuuint64_t)rows};
    cuuint64_t strides[1] = {(cuuint64_t)cols * 2};
    cuuint32_t box[2] = {(cuuint32_t)box_cols, (cuuint32_t)box_rows};
    cuuint32_t es[2] = {1, 1};
    enc(tm, CU_TENSOR_MAP_DATA_TYPE_BFLOAT16, 2, const_cast<void*>(ptr), dims, strides, box, es,
        CU_TENSOR_MAP_INTERLEAVE_NONE, swz, CU_TENSOR_MAP_L2_PROMOTION_L2_256B, CU_TENSOR_MAP_FLOAT_OOB_FILL_NONE);
}

}

extern "C" void kernel_launch(void* const* d_in, const int* in_sizes, int n_in, void* d_out, int out_size) {
    (void)in_sizes; (void)n_in; (void)out_size;
    static EncodeFn enc = nullptr;
    if (!enc) {
        void* fn = nullptr;
        cudaDriverEntryPointQueryResult qr;
        cudaGetDriverEntryPoint("cuTensorMapEncodeTiled", &fn, cudaEnableDefault, &qr);
        enc = (EncodeFn)fn;
        cudaFuncSetAttribute(fused_kernel, cudaFuncAttributeMaxDynamicSharedMemorySize, SMEM_BYTES);
    }
    const void* x = d_in[0];
    const void* wqkv = d_in[1];
    const void* wo = d_in[2];
    const void* w1 = d_in[4];
    const void* w3 = d_in[5];
    const void* w2 = d_in[6];
    CUtensorMap tx, tqkv, t1, t3, t1h, t3h, t2, t2h, two;
    make_map(enc, &tx, x, 2048, 512, 128, 64, CU_TENSOR_MAP_SWIZZLE_128B);
    make_map(enc, &tqkv, wqkv, 512, 1536, 64, 64, CU_TENSOR_MAP_SWIZZLE_128B);
    make_map(enc, &t1, w1, 512, 1792, 64, 64, CU_TENSOR_MAP_SWIZZLE_128B);
    make_map(enc, &t3, w3, 512, 1792, 64, 64, CU_TENSOR_MAP_SWIZZLE_128B);
    make_map(enc, &t1h, w1, 512, 1792, 64, 32, CU_TENSOR_MAP_SWIZZLE_64B);
    make_map(enc, &t3h, w3, 512, 1792, 64, 32, CU_TENSOR_MAP_SWIZZLE_64B);
    make_map(enc, &t2, w2, 1792, 512, 64, 64, CU_TENSOR_MAP_SWIZZLE_128B);
    make_map(enc, &t2h, w2, 1792, 512, 32, 64, CU_TENSOR_MAP_SWIZZLE_128B);
    make_map(enc, &two, wo, 512, 512, 64, 64, CU_TENSOR_MAP_SWIZZLE_128B);
    fused_kernel<<<128, 384, SMEM_BYTES>>>(tx, tqkv, t1, t3, t1h, t3h, t2, t2h, two, (const __nv_bfloat16*)x,
                                           (__nv_bfloat16*)d_out, (const char*)wqkv, (const char*)w1, (const char*)w3,
                                           (const char*)w2, (const char*)wo);
}
```

```cpp
#include <cuda_runtime.h>
#include <cuda_bf16.h>
#include <cuda.h>
#include <stdint.h>

namespace {

constexpr int NST = 13;
constexpr int STAGE_BYTES = 16384;
constexpr int XST0 = 5;
constexpr int SCR0 = 8;
constexpr int OFF_MISC = NST * STAGE_BYTES;
constexpr int OFF_KVFRAG = OFF_MISC;
constexpr int OFF_ONES = OFF_MISC + 3072;
constexpr int OFF_BARS = OFF_MISC + 3328;
constexpr int BAR_FULL = OFF_BARS;
constexpr int BAR_EMPTY = BAR_FULL + 8 * NST;
constexpr int BAR_XFULL = BAR_EMPTY + 8 * NST;
constexpr int BAR_KVREADY = BAR_XFULL + 64;
constexpr int BAR_XCHG = BAR_KVREADY + 8;
constexpr int BAR_EPOCH = BAR_XCHG + 8;
constexpr int BAR_XRDY = BAR_EPOCH + 8;
constexpr int OFF_EPOCH = BAR_XRDY + 8;
constexpr int OFF_ZERO = OFF_MISC + 4096;
constexpr int SMEM_BYTES = OFF_MISC + 8192;

constexpr unsigned SPIN_LIMIT = 1u << 24;

constexpr int A2_N = 16 * 2 * 18 * 4 * 256;
__device__ uint4 g_A2[2 * A2_N];
__device__ float4 g_kvacc[2 * 8 * 272];
__device__ unsigned g_kvcnt[8];
__device__ unsigned g_epoch;
__device__ unsigned g_ticket;

#define TS(role, i)
#define TSW(role, i)

__device__ __forceinline__ uint32_t smem_u32(const void* p) { return (uint32_t)__cvta_generic_to_shared(p); }
__device__ __forceinline__ void mbar_init(uint32_t bar, uint32_t cnt) {
    asm volatile("mbarrier.init.shared::cta.b64 [%0], %1;" ::"r"(bar), "r"(cnt) : "memory");
}
__device__ __forceinline__ void mbar_expect_tx(uint32_t bar, uint32_t bytes) {
    asm volatile("mbarrier.arrive.expect_tx.shared::cta.b64 _, [%0], %1;" ::"r"(bar), "r"(bytes) : "memory");
}
__device__ __forceinline__ void mbar_arrive(uint32_t bar) {
    asm volatile("mbarrier.arrive.shared::cta.b64 _, [%0];" ::"r"(bar) : "memory");
}
__device__ __forceinline__ void mbar_arrive_cta(uint32_t bar, uint32_t cta) {
    asm volatile(
        "{\n.reg .b32 ra;\nmapa.shared::cluster.u32 ra, %0, %1;\n"
        "mbarrier.arrive.shared::cluster.b64 _, [ra];\n}" ::"r"(bar), "r"(cta) : "memory");
}
__device__ __forceinline__ void mbar_wait(uint32_t bar, uint32_t parity) {
    asm volatile(
        "{\n.reg .pred p, q;\n.reg .u32 n;\nmov.u32 n, 0;\n"
        "WAIT_%=:\n"
        "mbarrier.try_wait.parity.shared::cta.b64 p, [%0], %1;\n"
        "@p bra.uni DONE_%=;\n"
        "add.u32 n, n, 1;\n"
        "setp.gt.u32 q, n, %2;\n"
        "@q trap;\n"
        "bra.uni WAIT_%=;\n"
        "DONE_%=:\n}"
        ::"r"(bar), "r"(parity), "n"(SPIN_LIMIT) : "memory");
}
__device__ __forceinline__ unsigned ld_acquire(const unsigned* p) {
    unsigned v;
    asm volatile("ld.acquire.gpu.global.u32 %0, [%1];" : "=r"(v) : "l"(p) : "memory");
    return v;
}
__device__ __forceinline__ void st_release(unsigned* p, unsigned v) {
    asm volatile("st.release.gpu.global.u32 [%0], %1;" ::"l"(p), "r"(v) : "memory");
}
__device__ __forceinline__ unsigned read_epoch() {
    return __shfl_sync(0xffffffffu, *(volatile unsigned*)&g_epoch, 0) + 1;
}
__device__ __forceinline__ void tma_load(uint32_t dst, const CUtensorMap* tm, uint32_t bar, int x, int y) {
    asm volatile(
        "cp.async.bulk.tensor.2d.shared::cluster.global.mbarrier::complete_tx::bytes [%0], [%1, {%3, %4}], [%2];"
        ::"r"(dst), "l"(tm), "r"(bar), "r"(x), "r"(y) : "memory");
}
__device__ __forceinline__ void tma_load_mc(uint32_t dst, const CUtensorMap* tm, uint32_t bar, int x, int y) {
    asm volatile(
        "cp.async.bulk.tensor.2d.shared::cluster.global.mbarrier::complete_tx::bytes.multicast::cluster "
        "[%0], [%1, {%3, %4}], [%2], %5;"
        ::"r"(dst), "l"(tm), "r"(bar), "r"(x), "r"(y), "h"((uint16_t)3) : "memory");
}
__device__ __forceinline__ void prefetch_tm(const CUtensorMap* tm) {
    asm volatile("prefetch.tensormap [%0];" ::"l"(tm) : "memory");
}
__device__ __forceinline__ void l2_prefetch(const void* p, uint32_t bytes) {
    asm volatile("cp.async.bulk.prefetch.L2.global [%0], %1;" ::"l"(p), "r"(bytes) : "memory");
}
__device__ __forceinline__ void bar_sync(int id, int n) { asm volatile("bar.sync %0, %1;" ::"r"(id), "r"(n) : "memory"); }
__device__ __forceinline__ void bar_arrive(int id, int n) { asm volatile("bar.arrive %0, %1;" ::"r"(id), "r"(n) : "memory"); }
__device__ __forceinline__ void wg_fence() { asm volatile("wgmma.fence.sync.aligned;" ::: "memory"); }
__device__ __forceinline__ void wg_commit() { asm volatile("wgmma.commit_group.sync.aligned;" ::: "memory"); }
template <int N>
__device__ __forceinline__ void wg_wait() { asm volatile("wgmma.wait_group.sync.aligned %0;" ::"n"(N) : "memory"); }

__device__ __forceinline__ uint64_t make_desc(uint32_t addr, uint32_t lbo, uint32_t sbo, uint64_t swz) {
    return (uint64_t)((addr & 0x3FFFF) >> 4) | ((uint64_t)(lbo >> 4) << 16) | ((uint64_t)(sbo >> 4) << 32) | (swz << 62);
}

#define ACC8(a, o) "+f"(a[o]), "+f"(a[o + 1]), "+f"(a[o + 2]), "+f"(a[o + 3]), "+f"(a[o + 4]), "+f"(a[o + 5]), "+f"(a[o + 6]), "+f"(a[o + 7])
constexpr uint32_t DHI128 = (1024u >> 4) | (1u << 30);
constexpr uint32_t DHI64 = (512u >> 4) | (2u << 30);
__device__ __forceinline__ void wgmma_n128_rs(float (&d)[64], const uint32_t* a, uint32_t db, int scale_d) {
    asm volatile(
        "{\n.reg .pred p;\n.reg .b64 dd;\nsetp.ne.b32 p, %69, 0;\nmov.b64 dd, {%68, %70};\n"
        "wgmma.mma_async.sync.aligned.m64n128k16.f32.bf16.bf16 "
        "{%0,%1,%2,%3,%4,%5,%6,%7,%8,%9,%10,%11,%12,%13,%14,%15,%16,%17,%18,%19,%20,%21,%22,%23,%24,%25,%26,%27,%28,%29,%30,%31,"
        "%32,%33,%34,%35,%36,%37,%38,%39,%40,%41,%42,%43,%44,%45,%46,%47,%48,%49,%50,%51,%52,%53,%54,%55,%56,%57,%58,%59,%60,%61,%62,%63},"
        "{%64,%65,%66,%67}, dd, p, 1, 1, 1;\n}"
        : ACC8(d, 0), ACC8(d, 8), ACC8(d, 16), ACC8(d, 24), ACC8(d, 32), ACC8(d, 40), ACC8(d, 48), ACC8(d, 56)
        : "r"(a[0]), "r"(a[1]), "r"(a[2]), "r"(a[3]), "r"(db), "r"(scale_d), "n"(DHI128));
}
template <uint32_t HI>
__device__ __forceinline__ void wgmma_n64_rs(float (&d)[32], const uint32_t* a, uint32_t db, int scale_d) {
    asm volatile(
        "{\n.reg .pred p;\n.reg .b64 dd;\nsetp.ne.b32 p, %37, 0;\nmov.b64 dd, {%36, %38};\n"
        "wgmma.mma_async.sync.aligned.m64n64k16.f32.bf16.bf16 "
        "{%0,%1,%2,%3,%4,%5,%6,%7,%8,%9,%10,%11,%12,%13,%14,%15,%16,%17,%18,%19,%20,%21,%22,%23,%24,%25,%26,%27,%28,%29,%30,%31},"
        "{%32,%33,%34,%35}, dd, p, 1, 1, 1;\n}"
        : ACC8(d, 0), ACC8(d, 8), ACC8(d, 16), ACC8(d, 24)
        : "r"(a[0]), "r"(a[1]), "r"(a[2]), "r"(a[3]), "r"(db), "r"(scale_d), "n"(HI));
}
__device__ __forceinline__ void wgmma_n64_ss_tt(float (&d)[32], uint64_t da, uint64_t db, int scale_d) {
    asm volatile(
        "{\n.reg .pred p;\nsetp.ne.b32 p, %34, 0;\n"
        "wgmma.mma_async.sync.aligned.m64n64k16.f32.bf16.bf16 "
        "{%0,%1,%2,%3,%4,%5,%6,%7,%8,%9,%10,%11,%12,%13,%14,%15,%16,%17,%18,%19,%20,%21,%22,%23,%24,%25,%26,%27,%28,%29,%30,%31},"
        "%32, %33, p, 1, 1, 1, 1;\n}"
        : ACC8(d, 0), ACC8(d, 8), ACC8(d, 16), ACC8(d, 24)
        : "l"(da), "l"(db), "r"(scale_d));
}
__device__ __forceinline__ void wgmma_n8_ss_tn(float (&d)[4], uint64_t da, uint64_t db, int scale_d) {
    asm volatile(
        "{\n.reg .pred p;\nsetp.ne.b32 p, %6, 0;\n"
        "wgmma.mma_async.sync.aligned.m64n8k16.f32.bf16.bf16 {%0,%1,%2,%3}, %4, %5, p, 1, 1, 1, 0;\n}"
        : "+f"(d[0]), "+f"(d[1]), "+f"(d[2]), "+f"(d[3])
        : "l"(da), "l"(db), "r"(scale_d));
}
template <int N>
__device__ __forceinline__ void acc_fence(float (&d)[N]) {
#pragma unroll
    for (int i = 0; i < N; i++) asm volatile("" : "+f"(d[i])::"memory");
}
__device__ __forceinline__ void mma16816(float (&c)[4], const uint32_t* a, uint32_t b0, uint32_t b1) {
    asm volatile(
        "mma.sync.aligned.m16n8k16.row.col.f32.bf16.bf16.f32 {%0,%1,%2,%3}, {%4,%5,%6,%7}, {%8,%9}, {%0,%1,%2,%3};"
        : "+f"(c[0]), "+f"(c[1]), "+f"(c[2]), "+f"(c[3])
        : "r"(a[0]), "r"(a[1]), "r"(a[2]), "r"(a[3]), "r"(b0), "r"(b1));
}
__device__ __forceinline__ uint32_t pack_bf16(float lo, float hi) {
    uint32_t r;
    asm("cvt.rn.bf16x2.f32 %0, %1, %2;" : "=r"(r) : "f"(hi), "f"(lo));
    return r;
}
__device__ __forceinline__ float bf_lo(uint32_t v) { return __uint_as_float(v << 16); }
__device__ __forceinline__ float bf_hi(uint32_t v) { return __uint_as_float(v & 0xffff0000u); }
__device__ __forceinline__ float bf16_round(float v) { return __bfloat162float(__float2bfloat16_rn(v)); }
__device__ __forceinline__ float sqrt_fast(float v) {
    float r;
    asm("sqrt.approx.ftz.f32 %0, %1;" : "=f"(r) : "f"(v));
    return r;
}
__device__ __forceinline__ float rcp_fast(float v) {
    float r;
    asm("rcp.approx.ftz.f32 %0, %1;" : "=f"(r) : "f"(v));
    return r;
}
__device__ __forceinline__ float ex2_fast(float v) {
    float r;
    asm("ex2.approx.ftz.f32 %0, %1;" : "=f"(r) : "f"(v));
    return r;
}
struct RowScale { float rho, rl, var; };
__device__ __forceinline__ float phi_f(float a, const RowScale& r) {
    return fmaf(fmaxf(a, 0.f), r.rho, ex2_fast(fminf(a, 0.f) * r.rl) + 1e-6f);
}
__device__ __forceinline__ float swiglu_f(float ga, float ua, const RowScale& r) {
    return (ga * ua) * rcp_fast(fmaf(ex2_fast(-ga * r.rl), r.var, r.var));
}
__device__ __forceinline__ uint4 swiglu8(const float* gp, const float* up, const RowScale& r0, const RowScale& r1) {
    uint4 v;
    v.x = pack_bf16(swiglu_f(gp[0], up[0], r0), swiglu_f(gp[1], up[1], r0));
    v.y = pack_bf16(swiglu_f(gp[2], up[2], r1), swiglu_f(gp[3], up[3], r1));
    v.z = pack_bf16(swiglu_f(gp[4], up[4], r0), swiglu_f(gp[5], up[5], r0));
    v.w = pack_bf16(swiglu_f(gp[6], up[6], r1), swiglu_f(gp[7], up[7], r1));
    v.y = v.y ? v.y : 0x8000u;
    v.w = v.w ? v.w : 0x8000u;
    return v;
}
__device__ __forceinline__ bool frag_stale(const uint4 (&f)[8]) {
    unsigned v = min(f[0].y, f[0].w);
#pragma unroll
    for (int i = 1; i < 8; i++) v = min(v, min(f[i].y, f[i].w));
    return __any_sync(0xffffffffu, v == 0u);
}
__device__ __forceinline__ void st_frag(uint4* p, uint4 v) {
    asm volatile("st.relaxed.gpu.global.v4.u32 [%0], {%1,%2,%3,%4};" ::"l"(p), "r"(v.x), "r"(v.y), "r"(v.z), "r"(v.w) : "memory");
}
__device__ __forceinline__ uint4 ld_frag(const uint4* p) {
    uint4 v;
    asm volatile("ld.relaxed.gpu.global.v4.u32 {%0,%1,%2,%3}, [%4];" : "=r"(v.x), "=r"(v.y), "=r"(v.z), "=r"(v.w) : "l"(p) : "memory");
    return v;
}
__device__ __forceinline__ void red_add2(float* p, float a, float b) {
    asm volatile("red.global.add.v2.f32 [%0], {%1, %2};" ::"l"(p), "f"(a), "f"(b) : "memory");
}
__device__ __forceinline__ void cp_async16(uint32_t dst, const void* src) {
    asm volatile("cp.async.cg.shared.global [%0], [%1], 16;" ::"r"(dst), "l"(src) : "memory");
}

__device__ __forceinline__ int ring_lap(int u) { return (u * 79) >> 10; }
__device__ __forceinline__ int ring_slot(int u) { return u - NST * ring_lap(u); }

__device__ __forceinline__ void mainloop128(float (&acc)[64], const uint32_t (&xa)[128], int u0, uint32_t sb,
                                            uint32_t desc128, int lane, int wg, bool last = false) {
    bar_sync(7 + wg, 256);
#pragma unroll
    for (int kb = 0; kb < 8; kb++) {
        const int st = ring_slot(u0 + kb);
        mbar_wait(sb + BAR_FULL + 8 * st, ring_lap(u0 + kb) & 1);
        wg_fence();
        const uint32_t d = desc128 + st * (STAGE_BYTES >> 4);
#pragma unroll
        for (int ks = 0; ks < 4; ks++) wgmma_n128_rs(acc, &xa[(kb * 4 + ks) * 4], d + ks * 128, (kb | ks) != 0);
        wg_commit();
        if (kb == 7 && !(last && wg == 1)) bar_arrive(8 - wg, 256);
        if (kb > 0) {
            wg_wait<1>();
            if (lane < 2) mbar_arrive_cta(sb + BAR_EMPTY + 8 * ring_slot(u0 + kb - 1), lane);
        }
    }
    wg_wait<0>();
    acc_fence(acc);
    if (lane < 2) mbar_arrive_cta(sb + BAR_EMPTY + 8 * ring_slot(u0 + 7), lane);
}
__device__ __forceinline__ void mainloop64x2(float (&a0)[32], float (&a1)[32], const uint32_t (&xa)[128], int u0,
                                             uint32_t sb, uint32_t desc128, int lane, int wg) {
    bar_sync(7 + wg, 256);
#pragma unroll
    for (int kb = 0; kb < 8; kb++) {
        const int st = ring_slot(u0 + kb);
        mbar_wait(sb + BAR_FULL + 8 * st, ring_lap(u0 + kb) & 1);
        wg_fence();
        const uint32_t d = desc128 + st * (STAGE_BYTES >> 4);
        const uint32_t d2 = d + (8192 >> 4) - ((4096u >> 4) << 16);
#pragma unroll
        for (int ks = 0; ks < 4; ks++) {
            wgmma_n64_rs<DHI128>(a0, &xa[(kb * 4 + ks) * 4], d + ks * 128, (kb | ks) != 0);
            wgmma_n64_rs<DHI64>(a1, &xa[(kb * 4 + ks) * 4], d2 + ks * 64, (kb | ks) != 0);
        }
        wg_commit();
        if (kb == 7) bar_arrive(8 - wg, 256);
        if (kb > 0) {
            wg_wait<1>();
            if (lane < 2) mbar_arrive_cta(sb + BAR_EMPTY + 8 * ring_slot(u0 + kb - 1), lane);
        }
    }
    wg_wait<0>();
    acc_fence(a0);
    acc_fence(a1);
    if (lane < 2) mbar_arrive_cta(sb + BAR_EMPTY + 8 * ring_slot(u0 + 7), lane);
}

__global__ void __cluster_dims__(2, 1, 1) __launch_bounds__(384, 1)
fused_kernel(const __grid_constant__ CUtensorMap tm_x, const __grid_constant__ CUtensorMap tm_qkv,
             const __grid_constant__ CUtensorMap tm_w1, const __grid_constant__ CUtensorMap tm_w3,
             const __grid_constant__ CUtensorMap tm_w1h, const __grid_constant__ CUtensorMap tm_w3h,
             const __grid_constant__ CUtensorMap tm_w2, const __grid_constant__ CUtensorMap tm_w2h,
             const __grid_constant__ CUtensorMap tm_wo, const __nv_bfloat16* __restrict__ xg,
             __nv_bfloat16* __restrict__ outg, const char* __restrict__ p_qkv, const char* __restrict__ p_w1,
             const char* __restrict__ p_w3, const char* __restrict__ p_w2, const char* __restrict__ p_wo) {
    extern __shared__ __align__(1024) uint8_t smem[];
    const uint32_t sb = smem_u32(smem);
    const int tid = threadIdx.x;
    const int warp = tid >> 5, lane = tid & 31;
    const int rank = blockIdx.x & 1;
    const int pair = blockIdx.x >> 1;
    const int c = pair & 7;
    const int m = (pair >> 3) * 2 + rank;
    const int m2 = (pair >> 3) * 2 + (c & 1);
    const int j2 = c >> 1;

    TS(tid >> 7, 0);
    if (tid == 256) {
#pragma unroll
        for (int i = 0; i < 8; i++) mbar_init(sb + BAR_XFULL + 8 * i, 1);
        asm volatile("fence.proxy.async.shared::cta;" ::: "memory");
#pragma unroll
        for (int kb = 0; kb < 8; kb++) {
            mbar_expect_tx(sb + BAR_XFULL + 8 * kb, 16384);
            tma_load(sb + (XST0 + kb) * STAGE_BYTES, &tm_x, sb + BAR_XFULL + 8 * kb, kb * 64, m * 128);
        }
        TS(2, 21);
    } else if (tid == 0) {
#pragma unroll
        for (int i = 0; i < NST; i++) mbar_init(sb + BAR_FULL + 8 * i, 1);
        asm volatile("fence.mbarrier_init.release.cluster;" ::: "memory");
    } else if (tid == 32) {
#pragma unroll
        for (int i = 0; i < NST; i++) mbar_init(sb + BAR_EMPTY + 8 * i, 16);
        asm volatile("fence.mbarrier_init.release.cluster;" ::: "memory");
    } else if (tid == 64) {
#pragma unroll
        for (int i = 0; i < 4; i++) mbar_init(sb + BAR_KVREADY + 8 * i, 1);
        mbar_expect_tx(sb + BAR_XCHG, 32768);
        asm volatile("fence.mbarrier_init.release.cluster;" ::: "memory");
    } else if (tid >= 128 && tid < 256) {
        ((uint4*)(smem + OFF_ZERO))[tid - 128] = make_uint4(0, 0, 0, 0);
        ((uint4*)(smem + OFF_ZERO))[tid] = make_uint4(0, 0, 0, 0);
        asm volatile("fence.proxy.async.shared::cta;" ::: "memory");
    } else if (tid == 288) {
        prefetch_tm(&tm_qkv);
        prefetch_tm(rank ? &tm_w3 : &tm_w1);
        prefetch_tm(&tm_w1h);
        prefetch_tm(&tm_w3h);
        prefetch_tm(&tm_w2);
        prefetch_tm(&tm_w2h);
        prefetch_tm(&tm_wo);
    } else if (tid >= 320) {
        ((uint32_t*)(smem + OFF_ONES))[tid - 320] = 0x3F803F80u;
        asm volatile("fence.proxy.async.shared::cta;" ::: "memory");
    }
    __syncthreads();
    TS(tid >> 7, 22);
    asm volatile("barrier.cluster.arrive.relaxed.aligned;\nbarrier.cluster.wait.acquire.aligned;" ::: "memory");

    if (warp >= 8) {
        asm volatile("setmaxnreg.dec.sync.aligned.u32 40;");
        if (warp == 8) {
            if (lane == 0) {
                int st = 0;
                uint32_t lap = 0;
                for (int it = 0; it < 40; it++) {
                    const int tile = it >> 3, kb = it & 7;
                    const uint32_t full = sb + BAR_FULL + 8 * st;
                    mbar_wait(sb + BAR_EMPTY + 8 * st, (st >= XST0) ? (lap & 1) : ((lap & 1) ^ 1));
                    mbar_expect_tx(full, STAGE_BYTES);
                    const uint32_t dst = sb + st * STAGE_BYTES;
                    if (tile == 0) {
                        tma_load_mc(dst + rank * 8192, &tm_qkv, full, 512 + 512 * rank + 64 * c, kb * 64);
                    } else if (tile != 3) {
                        tma_load_mc(dst + rank * 8192, rank ? &tm_w3 : &tm_w1, full, 224 * c + 64 * (tile == 4 ? 2 : tile - 1), kb * 64);
                    } else if (rank == 0) {
                        tma_load_mc(dst, &tm_qkv, full, 64 * c, kb * 64);
                    } else {
                        tma_load_mc(dst + 8192, &tm_w1h, full, 224 * c + 192, kb * 64);
                        tma_load_mc(dst + 12288, &tm_w3h, full, 224 * c + 192, kb * 64);
                    }
                    if (++st == NST) { st = 0; lap++; }
                    if (it == 7) {
                        mbar_wait(sb + BAR_EMPTY + 8 * SCR0, 0);
                        mbar_arrive(sb + BAR_FULL + 8 * SCR0);
                        mbar_wait(sb + BAR_EMPTY + 8 * (SCR0 + 1), 0);
                        mbar_arrive(sb + BAR_FULL + 8 * (SCR0 + 1));
                        st += 2;
                    }
                }
                TS(2, 1);
                for (int b = 0; b < 18; b++) {
                    const uint32_t full = sb + BAR_FULL + 8 * st;
                    const uint32_t dst = sb + st * STAGE_BYTES;
                    mbar_wait(sb + BAR_EMPTY + 8 * st, (st >= XST0) ? (lap & 1) : ((lap & 1) ^ 1));
                    mbar_expect_tx(full, STAGE_BYTES);
                    if (b < 8 || b >= 14) {
                        const int row = (b < 8) ? 224 * (4 * rank + (b & 3)) + 64 * (b >> 2) : 224 * (4 * rank + b - 14) + 128;
                        tma_load(dst, &tm_w2, full, 128 * j2, row);
                        tma_load(dst + 8192, &tm_w2, full, 128 * j2 + 64, row);
                    } else if (b < 10) {
                        const int row = 224 * (4 * rank + 2 * (b - 8)) + 192;
                        tma_load(dst, &tm_w2h, full, 128 * j2, row);
                        tma_load(dst + 4096, &tm_w2h, full, 128 * j2, row + 224);
                        tma_load(dst + 8192, &tm_w2h, full, 128 * j2 + 64, row);
                        tma_load(dst + 12288, &tm_w2h, full, 128 * j2 + 64, row + 224);
                    } else {
                        const int row = 64 * (4 * rank + (b - 10));
                        tma_load(dst, &tm_wo, full, 128 * j2, row);
                        tma_load(dst + 8192, &tm_wo, full, 128 * j2 + 64, row);
                    }
                    TS(2, 2 + b);
                    if (++st == NST) { st = 0; lap++; }
                }
                mbar_wait(sb + BAR_EMPTY + 8 * SCR0, lap & 1);
                mbar_wait(sb + BAR_EMPTY + 8 * (SCR0 + 1), lap & 1);
                mbar_arrive_cta(sb + BAR_XRDY, rank ^ 1);
            }
        } else if (warp < 11) {
            const int wg = warp - 9;
            bar_sync(3 + wg, 160);
            if (lane == 0) asm volatile("red.release.gpu.global.add.u32 [%0], 1;" ::"l"(&g_kvcnt[c]) : "memory");
            TSW(3, wg);
        } else {
            const unsigned epoch = read_epoch();
            if (lane == 0) {
                const unsigned tk = atomicInc(&g_ticket, 127u);
                if (tk == 127u) *(volatile unsigned*)&g_epoch = epoch;
            }
            if (lane == 0) *(volatile unsigned*)(smem + OFF_EPOCH) = epoch;
            __syncwarp();
            if (lane == 0) mbar_arrive(sb + BAR_EPOCH);
            if (lane < 17) g_kvacc[(((epoch & 1) ^ 1) * 8 + c) * 272 + 17 * m + lane] = make_float4(0.f, 0.f, 0.f, 0.f);
            {
                unsigned n = 0;
                while ((int)(ld_acquire(&g_kvcnt[c]) - 32u * epoch) < 0) {
                    __nanosleep(200);
                    if (++n > SPIN_LIMIT) asm volatile("trap;");
                }
            }
            TSW(4, 0);
            const int g = lane >> 2, t = lane & 3;
            const float* ks = (const float*)(g_kvacc + ((epoch & 1) * 8 + c) * 272) + 32 * t + g;
            uint2* kf = (uint2*)(smem + OFF_KVFRAG) + lane;
#pragma unroll 2
            for (int hh = 0; hh < 4; hh++) {
                const float* k = ks + hh * 272;
                const float a0 = __ldcg(k), a1 = __ldcg(k + 16), a2 = __ldcg(k + 128), a3 = __ldcg(k + 144);
                const float b0 = __ldcg(k + 8), b1 = __ldcg(k + 24), b2 = __ldcg(k + 136), b3 = __ldcg(k + 152);
                const float2 z0 = __ldcg((const float2*)(k - g - 30 * t + 256)), z1 = __ldcg((const float2*)(k - g - 30 * t + 264));
                kf[(hh * 3 + 0) * 32] = make_uint2(pack_bf16(a0, a1), pack_bf16(a2, a3));
                kf[(hh * 3 + 1) * 32] = make_uint2(pack_bf16(b0, b1), pack_bf16(b2, b3));
                kf[(hh * 3 + 2) * 32] = make_uint2(pack_bf16(z0.x, z0.y), pack_bf16(z1.x, z1.y));
            }
            __syncwarp();
            if (lane == 0) mbar_arrive(sb + BAR_KVREADY);
            TSW(4, 4);
            if (lane == 0) {
                char* z = (char*)(g_A2 + (size_t)((epoch & 1) ^ 1) * A2_N + (size_t)((m * 2 + (c >> 2)) * 18) * 4 * 256);
                const int cc = c & 3;
#pragma unroll 1
                for (int i = 0; i < 18; i++) {
                    const int blk = (i < 8) ? ((i >> 2) * 4 + cc) * 4 + (i & 3)
                                  : (i < 10) ? (8 + (cc >> 1)) * 4 + 2 * (cc & 1) + (i - 8)
                                  : (i < 14) ? (10 + cc) * 4 + (i - 10) : (14 + cc) * 4 + (i - 14);
                    asm volatile("cp.async.bulk.global.shared::cta.bulk_group [%0], [%1], 4096;"
                                 ::"l"(z + (size_t)blk * 4096), "r"(sb + OFF_ZERO) : "memory");
                }
                asm volatile("cp.async.bulk.commit_group;" ::: "memory");
            }
            if (lane == 0) asm volatile("cp.async.bulk.wait_group 0;" ::: "memory");
        }
    } else {
        asm volatile("setmaxnreg.inc.sync.aligned.u32 232;");
        const int wg = warp >> 2, w = warp & 3;
        const int g = lane >> 2, t = lane & 3;
        float acc[64];
        uint32_t xa[128];
        float rho0, rho1;
        RowScale r0, r1;
        unsigned par;

        TS(wg, 1);
        {
            const int row = wg * 64 + w * 16 + (lane & 7) + ((lane >> 3) & 1) * 8;
            const uint32_t rbase = sb + XST0 * STAGE_BYTES + row * 128;
            const int hi = lane >> 4, r7 = lane & 7;
            float sm[2][4], c0[2][4], c1[2][4];
#pragma unroll
            for (int i = 0; i < 8; i++) { sm[i >> 2][i & 3] = 0.f; c0[i >> 2][i & 3] = 0.f; c1[i >> 2][i & 3] = 0.f; }
            if (wg == 1) bar_arrive(7, 256);
#pragma unroll
            for (int kb = 0; kb < 8; kb++) {
                mbar_wait(sb + BAR_XFULL + 8 * kb, 0);
#pragma unroll
                for (int ks = 0; ks < 4; ks++) {
                    uint32_t* a = &xa[(kb * 4 + ks) * 4];
                    const uint32_t addr = rbase + kb * STAGE_BYTES + (((2 * ks + hi) ^ r7) << 4);
                    asm volatile("ldmatrix.sync.aligned.m8n8.x4.shared.b16 {%0,%1,%2,%3}, [%4];"
                                 : "=r"(a[0]), "=r"(a[1]), "=r"(a[2]), "=r"(a[3]) : "r"(addr) : "memory");
                    mma16816(sm[ks & 1], a, 0x3F803F80u, 0x3F803F80u);
                    mma16816(c0[ks & 1], a, a[0], a[2]);
                    mma16816(c1[ks & 1], a, a[1], a[3]);
                }
            }
            TS(wg, 2);
            const float mean0 = (sm[0][0] + sm[1][0]) * (1.f / 512.f);
            const float mean1 = (sm[0][2] + sm[1][2]) * (1.f / 512.f);
            __syncwarp();
            if (lane < 16) mbar_arrive_cta(sb + BAR_EMPTY + 8 * (XST0 + (lane >> 1)), lane & 1);
            const __nv_bfloat162 mb0 = __float2bfloat162_rn(mean0), mb1 = __float2bfloat162_rn(mean1);
#pragma unroll
            for (int i = 0; i < 128; i++) {
                __nv_bfloat162 v = *reinterpret_cast<__nv_bfloat162*>(&xa[i]);
                v = __hsub2(v, (i & 1) ? mb1 : mb0);
                xa[i] = *reinterpret_cast<uint32_t*>(&v);
            }
            const float d0 = (g & 1) ? c0[0][1] + c0[1][1] : c0[0][0] + c0[1][0];
            const float d1 = (g & 1) ? c1[0][3] + c1[1][3] : c1[0][2] + c1[1][2];
            const int src = (lane & ~3) | (g >> 1);
            const float var0 = fmaxf(__shfl_sync(0xffffffffu, d0, src) * (1.f / 512.f) - mean0 * mean0, 0.f);
            const float var1 = fmaxf(__shfl_sync(0xffffffffu, d1, src) * (1.f / 512.f) - mean1 * mean1, 0.f);
            const float sd0 = bf16_round(sqrt_fast(bf16_round(bf16_round(var0) + 1e-5f)));
            const float sd1 = bf16_round(sqrt_fast(bf16_round(bf16_round(var1) + 1e-5f)));
            rho0 = rcp_fast(sd0);
            rho1 = rcp_fast(sd1);
            r0.rho = rho0; r0.rl = rho0 * 1.4426950408889634f; r0.var = sd0 * sd0;
            r1.rho = rho1; r1.rl = rho1 * 1.4426950408889634f; r1.var = sd1 * sd1;
        }

        TS(wg, 3);
        const uint32_t desc128 = ((sb & 0x3FFFF) >> 4) | ((8192u >> 4) << 16);
        const int cc = c & 3;

        {
            mainloop128(acc, xa, 0, sb, desc128, lane, wg);
            TS(wg, 4);
            {
                TS(wg, 24);
                const uint32_t pkb = sb + (SCR0 + wg) * STAGE_BYTES;
                mbar_wait(sb + BAR_FULL + 8 * (SCR0 + wg), 0);
                const uint32_t ra = pkb + (w * 16 + g) * 128 + t * 4;
#pragma unroll
                for (int nb = 0; nb < 8; nb++) {
                    const uint32_t off = (uint32_t)((nb ^ g) << 4);
                    uint32_t p0 = pack_bf16(phi_f(acc[nb * 4], r0), phi_f(acc[nb * 4 + 1], r0));
                    uint32_t p1 = pack_bf16(phi_f(acc[nb * 4 + 2], r1), phi_f(acc[nb * 4 + 3], r1));
                    uint32_t v0 = pack_bf16(acc[32 + nb * 4] * rho0, acc[32 + nb * 4 + 1] * rho0);
                    uint32_t v1 = pack_bf16(acc[32 + nb * 4 + 2] * rho1, acc[32 + nb * 4 + 3] * rho1);
                    asm volatile("st.shared.u32 [%0], %1;" ::"r"(ra + off), "r"(p0) : "memory");
                    asm volatile("st.shared.u32 [%0], %1;" ::"r"(ra + off + 1024), "r"(p1) : "memory");
                    asm volatile("st.shared.u32 [%0], %1;" ::"r"(ra + off + 8192), "r"(v0) : "memory");
                    asm volatile("st.shared.u32 [%0], %1;" ::"r"(ra + off + 8192 + 1024), "r"(v1) : "memory");
                }
                TS(wg, 25);
                asm volatile("fence.proxy.async.shared::cta;" ::: "memory");
                bar_sync(1 + wg, 128);
                TS(wg, 26);
                const uint64_t da = make_desc(pkb, 8192, 1024, 1);
                const uint64_t db = make_desc(pkb + 8192, 8192, 1024, 1);
                const uint64_t d1 = make_desc(sb + OFF_ONES, 128, 128, 0);
                float kva[32], za[4];
                wg_fence();
#pragma unroll
                for (int ks = 0; ks < 4; ks++) {
                    wgmma_n64_ss_tt(kva, da + ks * 128, db + ks * 128, ks != 0);
                    wgmma_n8_ss_tn(za, da + ks * 128, d1, ks != 0);
                }
                wg_commit();
                wg_wait<0>();
                acc_fence(kva);
                acc_fence(za);
                if (lane < 4) mbar_arrive_cta(sb + BAR_EMPTY + 8 * (SCR0 + (lane >> 1)), lane & 1);
                TS(wg, 27);
                float o[8];
#pragma unroll
                for (int i = 0; i < 8; i++)
                    o[i] = (w == 0) ? kva[i] : (w == 1) ? kva[8 + i] : (w == 2) ? kva[16 + i] : kva[24 + i];
                mbar_wait(sb + BAR_EPOCH, 0);
                par = *(volatile unsigned*)(smem + OFF_EPOCH) & 1;
                float* dst = (float*)(g_kvacc + (par * 8 + c) * 272) + w * 272 + g * 16 + 2 * t;
                red_add2(dst, o[0], o[1]);
                red_add2(dst + 128, o[2], o[3]);
                red_add2(dst + 8, o[4], o[5]);
                red_add2(dst + 136, o[6], o[7]);
                if (t == 0) {
                    atomicAdd(dst - g * 15 + 256, za[0]);
                    atomicAdd(dst - g * 15 + 264, za[2]);
                }
            }
            bar_arrive(3 + wg, 160);
            TS(wg, 5);
        }
        uint4* a2w = g_A2 + (size_t)par * A2_N + (size_t)((m * 2 + (c >> 2)) * 18) * 4 * 256 + warp * 32 + lane;
#pragma unroll
        for (int tile = 1; tile < 3; tile++) {
            mainloop128(acc, xa, 2 + 8 * tile, sb, desc128, lane, wg);
            TS(wg, 4 + 2 * tile);
            uint4* dst = a2w + (size_t)((4 * (tile - 1) + cc) * 4) * 256;
#pragma unroll
            for (int ks = 0; ks < 4; ks++) st_frag(dst + ks * 256, swiglu8(&acc[ks * 8], &acc[32 + ks * 8], r0, r1));
            TS(wg, 5 + 2 * tile);
        }
        {
            float qa[32], gu[32];
            mainloop64x2(qa, gu, xa, 26, sb, desc128, lane, wg);
            TS(wg, 10);
            uint4* dst = a2w + (size_t)((8 + (cc >> 1)) * 4 + 2 * (cc & 1)) * 256;
#pragma unroll
            for (int ks = 0; ks < 2; ks++) st_frag(dst + ks * 256, swiglu8(&gu[ks * 8], &gu[16 + ks * 8], r0, r1));
            TS(wg, 13);
            mbar_wait(sb + BAR_KVREADY, 0);
            TS(wg, 14);
            const uint2* kf = (const uint2*)(smem + OFF_KVFRAG);
            dst = a2w + (size_t)((10 + cc) * 4) * 256;
#pragma unroll
            for (int hh = 0; hh < 4; hh++) {
                const float* q = &qa[hh * 8];
                uint32_t a[4];
                a[0] = pack_bf16(phi_f(q[0], r0), phi_f(q[1], r0));
                a[1] = pack_bf16(phi_f(q[2], r1), phi_f(q[3], r1));
                a[2] = pack_bf16(phi_f(q[4], r0), phi_f(q[5], r0));
                a[3] = pack_bf16(phi_f(q[6], r1), phi_f(q[7], r1));
                float n0[4] = {0.f, 0.f, 0.f, 0.f}, n1[4] = {0.f, 0.f, 0.f, 0.f}, dn[4] = {0.f, 0.f, 0.f, 0.f};
                const uint2 b0 = kf[(hh * 3 + 0) * 32 + lane], b1 = kf[(hh * 3 + 1) * 32 + lane],
                            bz = kf[(hh * 3 + 2) * 32 + lane];
                mma16816(n0, a, b0.x, b0.y);
                mma16816(n1, a, b1.x, b1.y);
                mma16816(dn, a, bz.x, bz.y);
                const float i0 = rcp_fast(dn[0] + 1e-6f), i1 = rcp_fast(dn[2] + 1e-6f);
                uint4 v;
                v.x = pack_bf16(n0[0] * i0, n0[1] * i0);
                v.y = pack_bf16(n0[2] * i1, n0[3] * i1);
                v.z = pack_bf16(n1[0] * i0, n1[1] * i0);
                v.w = pack_bf16(n1[2] * i1, n1[3] * i1);
                v.y = v.y ? v.y : 0x8000u;
                v.w = v.w ? v.w : 0x8000u;
                st_frag(dst + hh * 256, v);
            }
            TS(wg, 11);
        }
        const uint4* a2r = g_A2 + (size_t)par * A2_N + (size_t)((m2 * 2 + rank) * 18) * 4 * 256 + warp * 32 + lane;
        uint4 af[3][8];
        {
            mainloop128(acc, xa, 34, sb, desc128, lane, wg, true);
            TS(wg, 12);
#pragma unroll
            for (int i = 0; i < 8; i++) af[0][i] = ld_frag(a2r + i * 256);
            uint4* dst = a2w + (size_t)((14 + cc) * 4) * 256;
#pragma unroll
            for (int ks = 0; ks < 4; ks++) st_frag(dst + ks * 256, swiglu8(&acc[ks * 8], &acc[32 + ks * 8], r0, r1));
            TS(wg, 15);
        }

        {
            float ao[32], ap[32];
            const uint32_t dso = desc128 + rank * 512, dsp = desc128 + (rank ^ 1) * 512;
            TS(wg, 16);
#pragma unroll
            for (int gi = 0; gi < 9; gi++) {
                if (gi == 7) TS(wg, 17);
                uint4(&f)[8] = af[gi % 3];
                {
                    unsigned n = 0;
                    while (frag_stale(f)) {
#pragma unroll
                        for (int i = 0; i < 8; i++) f[i] = ld_frag(a2r + (gi * 8 + i) * 256);
                        if (++n > SPIN_LIMIT) asm volatile("trap;");
                    }
                }
                mbar_wait(sb + BAR_FULL + 8 * ring_slot(42 + gi * 2), ring_lap(42 + gi * 2) & 1);
                mbar_wait(sb + BAR_FULL + 8 * ring_slot(43 + gi * 2), ring_lap(43 + gi * 2) & 1);
                wg_fence();
#pragma unroll
                for (int i = 0; i < 8; i++) {
                    const uint32_t so = ring_slot(42 + gi * 2 + (i >> 2)) * (STAGE_BYTES >> 4) + (i & 3) * 128;
                    const uint32_t* a = reinterpret_cast<const uint32_t*>(&f[i]);
                    wgmma_n64_rs<DHI128>(ap, a, dsp + so, (gi | i) != 0);
                    if (gi < 7) wgmma_n64_rs<DHI128>(ao, a, dso + so, (gi | i) != 0);
                    if (i == 0 && gi < 8) {
#pragma unroll
                        for (int k = 0; k < 8; k++) af[(gi + 1) % 3][k] = ld_frag(a2r + ((gi + 1) * 8 + k) * 256);
                    }
                }
                wg_commit();
                if (gi > 0 && gi < 8) {
                    wg_wait<1>();
                    if (gi < 7 && lane < 4) mbar_arrive(sb + BAR_EMPTY + 8 * ring_slot(40 + gi * 2 + (lane >> 1)));
                }
            }
#pragma unroll
            for (int i = 0; i < 16; i++)
                wgmma_n64_rs<DHI128>(ao, reinterpret_cast<const uint32_t*>(&af[(7 + (i >> 3)) % 3][i & 7]),
                                     dso + ring_slot(56 + (i >> 2)) * (STAGE_BYTES >> 4) + (i & 3) * 128, 1);
            wg_commit();
            const int row0 = m2 * 128 + wg * 64 + w * 16 + g;
            const int col0 = j2 * 128 + rank * 64 + 2 * t;
            uint32_t xr[16];
#pragma unroll
            for (int nb = 0; nb < 8; nb++) {
                xr[2 * nb] = __ldg((const uint32_t*)(xg + (size_t)row0 * 512 + col0 + nb * 8));
                xr[2 * nb + 1] = __ldg((const uint32_t*)(xg + (size_t)(row0 + 8) * 512 + col0 + nb * 8));
            }
            uint32_t rdst, rbar;
            asm volatile("mapa.shared::cluster.u32 %0, %1, %2;"
                         : "=r"(rdst) : "r"(sb + (SCR0 + wg) * STAGE_BYTES + (tid & 127) * 16), "r"(rank ^ 1));
            asm volatile("mapa.shared::cluster.u32 %0, %1, %2;" : "=r"(rbar) : "r"(sb + BAR_XCHG), "r"(rank ^ 1));
            mbar_wait(sb + BAR_XRDY, 0);
            wg_wait<1>();
            acc_fence(ap);
            TS(wg, 18);
#pragma unroll
            for (int i = 0; i < 8; i++)
                asm volatile("st.async.shared::cluster.mbarrier::complete_tx::bytes.v4.f32 [%0], {%1,%2,%3,%4}, [%5];"
                             ::"r"(rdst + i * 2048), "f"(ap[4 * i]), "f"(ap[4 * i + 1]), "f"(ap[4 * i + 2]), "f"(ap[4 * i + 3]),
                             "r"(rbar) : "memory");
            wg_wait<0>();
            acc_fence(ao);
            mbar_wait(sb + BAR_XCHG, 0);
            TS(wg, 19);
            const float4* rx = (const float4*)(smem + (SCR0 + wg) * STAGE_BYTES) + (tid & 127);
#pragma unroll
            for (int nb = 0; nb < 8; nb++) {
                const float4 p = rx[nb * 128];
                const uint32_t o0 = pack_bf16(ao[4 * nb] + p.x + bf_lo(xr[2 * nb]), ao[4 * nb + 1] + p.y + bf_hi(xr[2 * nb]));
                const uint32_t o1 = pack_bf16(ao[4 * nb + 2] + p.z + bf_lo(xr[2 * nb + 1]), ao[4 * nb + 3] + p.w + bf_hi(xr[2 * nb + 1]));
                *(uint32_t*)(outg + (size_t)row0 * 512 + col0 + nb * 8) = o0;
                *(uint32_t*)(outg + (size_t)(row0 + 8) * 512 + col0 + nb * 8) = o1;
            }
        }
        TS(wg, 20);
    }
}

typedef CUresult (*EncodeFn)(CUtensorMap*, CUtensorMapDataType, cuuint32_t, void*, const cuuint64_t*, const cuuint64_t*,
                             const cuuint32_t*, const cuuint32_t*, CUtensorMapInterleave, CUtensorMapSwizzle,
                             CUtensorMapL2promotion, CUtensorMapFloatOOBfill);

void make_map(EncodeFn enc, CUtensorMap* tm, const void* ptr, int rows, int cols, int box_rows, int box_cols,
              CUtensorMapSwizzle swz) {
    cuuint64_t dims[2] = {(cuuint64_t)cols, (cuuint64_t)rows};
    cuuint64_t strides[1] = {(cuuint64_t)cols * 2};
    cuuint32_t box[2] = {(cuuint32_t)box_cols, (cuuint32_t)box_rows};
    cuuint32_t es[2] = {1, 1};
    enc(tm, CU_TENSOR_MAP_DATA_TYPE_BFLOAT16, 2, const_cast<void*>(ptr), dims, strides, box, es,
        CU_TENSOR_MAP_INTERLEAVE_NONE, swz, CU_TENSOR_MAP_L2_PROMOTION_L2_256B, CU_TENSOR_MAP_FLOAT_OOB_FILL_NONE);
}

}

extern "C" void kernel_launch(void* const* d_in, const int* in_sizes, int n_in, void* d_out, int out_size) {
    (void)in_sizes; (void)n_in; (void)out_size;
    static EncodeFn enc = nullptr;
    if (!enc) {
        void* fn = nullptr;
        cudaDriverEntryPointQueryResult qr;
        cudaGetDriverEntryPoint("cuTensorMapEncodeTiled", &fn, cudaEnableDefault, &qr);
        enc = (EncodeFn)fn;
        cudaFuncSetAttribute(fused_kernel, cudaFuncAttributeMaxDynamicSharedMemorySize, SMEM_BYTES);
    }
    const void* x = d_in[0];
    const void* wqkv = d_in[1];
    const void* wo = d_in[2];
    const void* w1 = d_in[4];
    const void* w3 = d_in[5];
    const void* w2 = d_in[6];
    CUtensorMap tx, tqkv, t1, t3, t1h, t3h, t2, t2h, two;
    make_map(enc, &tx, x, 2048, 512, 128, 64, CU_TENSOR_MAP_SWIZZLE_128B);
    make_map(enc, &tqkv, wqkv, 512, 1536, 64, 64, CU_TENSOR_MAP_SWIZZLE_128B);
    make_map(enc, &t1, w1, 512, 1792, 64, 64, CU_TENSOR_MAP_SWIZZLE_128B);
    make_map(enc, &t3, w3, 512, 1792, 64, 64, CU_TENSOR_MAP_SWIZZLE_128B);
    make_map(enc, &t1h, w1, 512, 1792, 64, 32, CU_TENSOR_MAP_SWIZZLE_64B);
    make_map(enc, &t3h, w3, 512, 1792, 64, 32, CU_TENSOR_MAP_SWIZZLE_64B);
    make_map(enc, &t2, w2, 1792, 512, 64, 64, CU_TENSOR_MAP_SWIZZLE_128B);
    make_map(enc, &t2h, w2, 1792, 512, 32, 64, CU_TENSOR_MAP_SWIZZLE_128B);
    make_map(enc, &two, wo, 512, 512, 64, 64, CU_TENSOR_MAP_SWIZZLE_128B);
    fused_kernel<<<128, 384, SMEM_BYTES>>>(tx, tqkv, t1, t3, t1h, t3h, t2, t2h, two, (const __nv_bfloat16*)x,
                                           (__nv_bfloat16*)d_out, (const char*)wqkv, (const char*)w1, (const char*)w3,
                                           (const char*)w2, (const char*)wo);
}
```

```cpp
#include <cuda_runtime.h>
#include <cuda_bf16.h>
#include <cuda.h>
#include <stdint.h>

namespace {

constexpr int NST = 13;
constexpr int STAGE_BYTES = 16384;
constexpr int XST0 = 5;
constexpr int SCR0 = 8;
constexpr int OFF_MISC = NST * STAGE_BYTES;
constexpr int OFF_KVFRAG = OFF_MISC;
constexpr int OFF_ONES = OFF_MISC + 3072;
constexpr int OFF_BARS = OFF_MISC + 3328;
constexpr int BAR_FULL = OFF_BARS;
constexpr int BAR_EMPTY = BAR_FULL + 8 * NST;
constexpr int BAR_XFULL = BAR_EMPTY + 8 * NST;
constexpr int BAR_KVREADY = BAR_XFULL + 64;
constexpr int BAR_XCHG = BAR_KVREADY + 8;
constexpr int BAR_EPOCH = BAR_XCHG + 8;
constexpr int BAR_XRDY = BAR_EPOCH + 8;
constexpr int OFF_EPOCH = BAR_XRDY + 8;
constexpr int OFF_ZERO = OFF_MISC + 4096;
constexpr int SMEM_BYTES = OFF_MISC + 8192;

constexpr unsigned SPIN_LIMIT = 1u << 24;

constexpr int A2_N = 16 * 2 * 18 * 4 * 256;
__device__ uint4 g_A2[2 * A2_N];
__device__ float4 g_kvacc[2 * 8 * 272];
__device__ unsigned g_kvcnt[8];
__device__ unsigned g_epoch;
__device__ unsigned g_ticket;

#define TS(role, i)
#define TSW(role, i)

__device__ __forceinline__ uint32_t smem_u32(const void* p) { return (uint32_t)__cvta_generic_to_shared(p); }
__device__ __forceinline__ void mbar_init(uint32_t bar, uint32_t cnt) {
    asm volatile("mbarrier.init.shared::cta.b64 [%0], %1;" ::"r"(bar), "r"(cnt) : "memory");
}
__device__ __forceinline__ void mbar_expect_tx(uint32_t bar, uint32_t bytes) {
    asm volatile("mbarrier.arrive.expect_tx.shared::cta.b64 _, [%0], %1;" ::"r"(bar), "r"(bytes) : "memory");
}
__device__ __forceinline__ void mbar_arrive(uint32_t bar) {
    asm volatile("mbarrier.arrive.shared::cta.b64 _, [%0];" ::"r"(bar) : "memory");
}
__device__ __forceinline__ void mbar_arrive_cta(uint32_t bar, uint32_t cta) {
    asm volatile(
        "{\n.reg .b32 ra;\nmapa.shared::cluster.u32 ra, %0, %1;\n"
        "mbarrier.arrive.shared::cluster.b64 _, [ra];\n}" ::"r"(bar), "r"(cta) : "memory");
}
__device__ __forceinline__ void mbar_wait(uint32_t bar, uint32_t parity) {
    asm volatile(
        "{\n.reg .pred p, q;\n.reg .u32 n;\nmov.u32 n, 0;\n"
        "WAIT_%=:\n"
        "mbarrier.try_wait.parity.shared::cta.b64 p, [%0], %1;\n"
        "@p bra.uni DONE_%=;\n"
        "add.u32 n, n, 1;\n"
        "setp.gt.u32 q, n, %2;\n"
        "@q trap;\n"
        "bra.uni WAIT_%=;\n"
        "DONE_%=:\n}"
        ::"r"(bar), "r"(parity), "n"(SPIN_LIMIT) : "memory");
}
__device__ __forceinline__ unsigned ld_acquire(const unsigned* p) {
    unsigned v;
    asm volatile("ld.acquire.gpu.global.u32 %0, [%1];" : "=r"(v) : "l"(p) : "memory");
    return v;
}
__device__ __forceinline__ void st_release(unsigned* p, unsigned v) {
    asm volatile("st.release.gpu.global.u32 [%0], %1;" ::"l"(p), "r"(v) : "memory");
}
__device__ __forceinline__ unsigned read_epoch() {
    return __shfl_sync(0xffffffffu, *(volatile unsigned*)&g_epoch, 0) + 1;
}
__device__ __forceinline__ void tma_load(uint32_t dst, const CUtensorMap* tm, uint32_t bar, int x, int y) {
    asm volatile(
        "cp.async.bulk.tensor.2d.shared::cluster.global.mbarrier::complete_tx::bytes [%0], [%1, {%3, %4}], [%2];"
        ::"r"(dst), "l"(tm), "r"(bar), "r"(x), "r"(y) : "memory");
}
__device__ __forceinline__ void tma_load_mc(uint32_t dst, const CUtensorMap* tm, uint32_t bar, int x, int y) {
    asm volatile(
        "cp.async.bulk.tensor.2d.shared::cluster.global.mbarrier::complete_tx::bytes.multicast::cluster "
        "[%0], [%1, {%3, %4}], [%2], %5;"
        ::"r"(dst), "l"(tm), "r"(bar), "r"(x), "r"(y), "h"((uint16_t)3) : "memory");
}
__device__ __forceinline__ void prefetch_tm(const CUtensorMap* tm) {
    asm volatile("prefetch.tensormap [%0];" ::"l"(tm) : "memory");
}
__device__ __forceinline__ void l2_prefetch(const void* p, uint32_t bytes) {
    asm volatile("cp.async.bulk.prefetch.L2.global [%0], %1;" ::"l"(p), "r"(bytes) : "memory");
}
__device__ __forceinline__ void bar_sync(int id, int n) { asm volatile("bar.sync %0, %1;" ::"r"(id), "r"(n) : "memory"); }
__device__ __forceinline__ void bar_arrive(int id, int n) { asm volatile("bar.arrive %0, %1;" ::"r"(id), "r"(n) : "memory"); }
__device__ __forceinline__ void wg_fence() { asm volatile("wgmma.fence.sync.aligned;" ::: "memory"); }
__device__ __forceinline__ void wg_commit() { asm volatile("wgmma.commit_group.sync.aligned;" ::: "memory"); }
template <int N>
__device__ __forceinline__ void wg_wait() { asm volatile("wgmma.wait_group.sync.aligned %0;" ::"n"(N) : "memory"); }

__device__ __forceinline__ uint64_t make_desc(uint32_t addr, uint32_t lbo, uint32_t sbo, uint64_t swz) {
    return (uint64_t)((addr & 0x3FFFF) >> 4) | ((uint64_t)(lbo >> 4) << 16) | ((uint64_t)(sbo >> 4) << 32) | (swz << 62);
}

#define ACC8(a, o) "+f"(a[o]), "+f"(a[o + 1]), "+f"(a[o + 2]), "+f"(a[o + 3]), "+f"(a[o + 4]), "+f"(a[o + 5]), "+f"(a[o + 6]), "+f"(a[o + 7])
constexpr uint32_t DHI128 = (1024u >> 4) | (1u << 30);
constexpr uint32_t DHI64 = (512u >> 4) | (2u << 30);
__device__ __forceinline__ void wgmma_n128_rs(float (&d)[64], const uint32_t* a, uint32_t db, int scale_d) {
    asm volatile(
        "{\n.reg .pred p;\n.reg .b64 dd;\nsetp.ne.b32 p, %69, 0;\nmov.b64 dd, {%68, %70};\n"
        "wgmma.mma_async.sync.aligned.m64n128k16.f32.bf16.bf16 "
        "{%0,%1,%2,%3,%4,%5,%6,%7,%8,%9,%10,%11,%12,%13,%14,%15,%16,%17,%18,%19,%20,%21,%22,%23,%24,%25,%26,%27,%28,%29,%30,%31,"
        "%32,%33,%34,%35,%36,%37,%38,%39,%40,%41,%42,%43,%44,%45,%46,%47,%48,%49,%50,%51,%52,%53,%54,%55,%56,%57,%58,%59,%60,%61,%62,%63},"
        "{%64,%65,%66,%67}, dd, p, 1, 1, 1;\n}"
        : ACC8(d, 0), ACC8(d, 8), ACC8(d, 16), ACC8(d, 24), ACC8(d, 32), ACC8(d, 40), ACC8(d, 48), ACC8(d, 56)
        : "r"(a[0]), "r"(a[1]), "r"(a[2]), "r"(a[3]), "r"(db), "r"(scale_d), "n"(DHI128));
}
template <uint32_t HI>
__device__ __forceinline__ void wgmma_n64_rs(float (&d)[32], const uint32_t* a, uint32_t db, int scale_d) {
    asm volatile(
        "{\n.reg .pred p;\n.reg .b64 dd;\nsetp.ne.b32 p, %37, 0;\nmov.b64 dd, {%36, %38};\n"
        "wgmma.mma_async.sync.aligned.m64n64k16.f32.bf16.bf16 "
        "{%0,%1,%2,%3,%4,%5,%6,%7,%8,%9,%10,%11,%12,%13,%14,%15,%16,%17,%18,%19,%20,%21,%22,%23,%24,%25,%26,%27,%28,%29,%30,%31},"
        "{%32,%33,%34,%35}, dd, p, 1, 1, 1;\n}"
        : ACC8(d, 0), ACC8(d, 8), ACC8(d, 16), ACC8(d, 24)
        : "r"(a[0]), "r"(a[1]), "r"(a[2]), "r"(a[3]), "r"(db), "r"(scale_d), "n"(HI));
}
__device__ __forceinline__ void wgmma_n64_ss_tt(float (&d)[32], uint64_t da, uint64_t db, int scale_d) {
    asm volatile(
        "{\n.reg .pred p;\nsetp.ne.b32 p, %34, 0;\n"
        "wgmma.mma_async.sync.aligned.m64n64k16.f32.bf16.bf16 "
        "{%0,%1,%2,%3,%4,%5,%6,%7,%8,%9,%10,%11,%12,%13,%14,%15,%16,%17,%18,%19,%20,%21,%22,%23,%24,%25,%26,%27,%28,%29,%30,%31},"
        "%32, %33, p, 1, 1, 1, 1;\n}"
        : ACC8(d, 0), ACC8(d, 8), ACC8(d, 16), ACC8(d, 24)
        : "l"(da), "l"(db), "r"(scale_d));
}
__device__ __forceinline__ void wgmma_n8_ss_tn(float (&d)[4], uint64_t da, uint64_t db, int scale_d) {
    asm volatile(
        "{\n.reg .pred p;\nsetp.ne.b32 p, %6, 0;\n"
        "wgmma.mma_async.sync.aligned.m64n8k16.f32.bf16.bf16 {%0,%1,%2,%3}, %4, %5, p, 1, 1, 1, 0;\n}"
        : "+f"(d[0]), "+f"(d[1]), "+f"(d[2]), "+f"(d[3])
        : "l"(da), "l"(db), "r"(scale_d));
}
template <int N>
__device__ __forceinline__ void acc_fence(float (&d)[N]) {
#pragma unroll
    for (int i = 0; i < N; i++) asm volatile("" : "+f"(d[i])::"memory");
}
__device__ __forceinline__ void mma16816(float (&c)[4], const uint32_t* a, uint32_t b0, uint32_t b1) {
    asm volatile(
        "mma.sync.aligned.m16n8k16.row.col.f32.bf16.bf16.f32 {%0,%1,%2,%3}, {%4,%5,%6,%7}, {%8,%9}, {%0,%1,%2,%3};"
        : "+f"(c[0]), "+f"(c[1]), "+f"(c[2]), "+f"(c[3])
        : "r"(a[0]), "r"(a[1]), "r"(a[2]), "r"(a[3]), "r"(b0), "r"(b1));
}
__device__ __forceinline__ uint32_t pack_bf16(float lo, float hi) {
    uint32_t r;
    asm("cvt.rn.bf16x2.f32 %0, %1, %2;" : "=r"(r) : "f"(hi), "f"(lo));
    return r;
}
__device__ __forceinline__ float bf_lo(uint32_t v) { return __uint_as_float(v << 16); }
__device__ __forceinline__ float bf_hi(uint32_t v) { return __uint_as_float(v & 0xffff0000u); }
__device__ __forceinline__ float bf16_round(float v) { return __bfloat162float(__float2bfloat16_rn(v)); }
__device__ __forceinline__ float sqrt_fast(float v) {
    float r;
    asm("sqrt.approx.ftz.f32 %0, %1;" : "=f"(r) : "f"(v));
    return r;
}
__device__ __forceinline__ float rcp_fast(float v) {
    float r;
    asm("rcp.approx.ftz.f32 %0, %1;" : "=f"(r) : "f"(v));
    return r;
}
__device__ __forceinline__ float ex2_fast(float v) {
    float r;
    asm("ex2.approx.ftz.f32 %0, %1;" : "=f"(r) : "f"(v));
    return r;
}
struct RowScale { float rho, rl, var; };
__device__ __forceinline__ float phi_f(float a, const RowScale& r) {
    return fmaf(fmaxf(a, 0.f), r.rho, ex2_fast(fminf(a, 0.f) * r.rl) + 1e-6f);
}
__device__ __forceinline__ float swiglu_f(float ga, float ua, const RowScale& r) {
    return (ga * ua) * rcp_fast(fmaf(ex2_fast(-ga * r.rl), r.var, r.var));
}
__device__ __forceinline__ uint4 swiglu8(const float* gp, const float* up, const RowScale& r0, const RowScale& r1) {
    uint4 v;
    v.x = pack_bf16(swiglu_f(gp[0], up[0], r0), swiglu_f(gp[1], up[1], r0));
    v.y = pack_bf16(swiglu_f(gp[2], up[2], r1), swiglu_f(gp[3], up[3], r1));
    v.z = pack_bf16(swiglu_f(gp[4], up[4], r0), swiglu_f(gp[5], up[5], r0));
    v.w = pack_bf16(swiglu_f(gp[6], up[6], r1), swiglu_f(gp[7], up[7], r1));
    v.y = v.y ? v.y : 0x8000u;
    v.w = v.w ? v.w : 0x8000u;
    return v;
}
__device__ __forceinline__ bool frag_stale(const uint4 (&f)[12]) {
    unsigned v = min(f[0].y, f[0].w);
#pragma unroll
    for (int i = 1; i < 12; i++) v = min(v, min(f[i].y, f[i].w));
    return __any_sync(0xffffffffu, v == 0u);
}
__device__ __forceinline__ void st_frag(uint4* p, uint4 v) {
    asm volatile("st.relaxed.gpu.global.v4.u32 [%0], {%1,%2,%3,%4};" ::"l"(p), "r"(v.x), "r"(v.y), "r"(v.z), "r"(v.w) : "memory");
}
__device__ __forceinline__ uint4 ld_frag(const uint4* p) {
    uint4 v;
    asm volatile("ld.relaxed.gpu.global.v4.u32 {%0,%1,%2,%3}, [%4];" : "=r"(v.x), "=r"(v.y), "=r"(v.z), "=r"(v.w) : "l"(p) : "memory");
    return v;
}
__device__ __forceinline__ void red_add2(float* p, float a, float b) {
    asm volatile("red.global.add.v2.f32 [%0], {%1, %2};" ::"l"(p), "f"(a), "f"(b) : "memory");
}
__device__ __forceinline__ void cp_async16(uint32_t dst, const void* src) {
    asm volatile("cp.async.cg.shared.global [%0], [%1], 16;" ::"r"(dst), "l"(src) : "memory");
}

__device__ __forceinline__ int ring_lap(int u) { return (u * 79) >> 10; }
__device__ __forceinline__ int ring_slot(int u) { return u - NST * ring_lap(u); }

__device__ __forceinline__ void mainloop128(float (&acc)[64], const uint32_t (&xa)[128], int u0, uint32_t sb,
                                            uint32_t desc128, int lane, int wg, bool last = false) {
    bar_sync(7 + wg, 256);
#pragma unroll
    for (int kb = 0; kb < 8; kb++) {
        const int st = ring_slot(u0 + kb);
        mbar_wait(sb + BAR_FULL + 8 * st, ring_lap(u0 + kb) & 1);
        wg_fence();
        const uint32_t d = desc128 + st * (STAGE_BYTES >> 4);
#pragma unroll
        for (int ks = 0; ks < 4; ks++) wgmma_n128_rs(acc, &xa[(kb * 4 + ks) * 4], d + ks * 128, (kb | ks) != 0);
        wg_commit();
        if (kb == 7 && !(last && wg == 1)) bar_arrive(8 - wg, 256);
        if (kb > 0) {
            wg_wait<1>();
            if (lane < 2) mbar_arrive_cta(sb + BAR_EMPTY + 8 * ring_slot(u0 + kb - 1), lane);
        }
    }
    wg_wait<0>();
    acc_fence(acc);
    if (lane < 2) mbar_arrive_cta(sb + BAR_EMPTY + 8 * ring_slot(u0 + 7), lane);
}
__device__ __forceinline__ void mainloop64x2(float (&a0)[32], float (&a1)[32], const uint32_t (&xa)[128], int u0,
                                             uint32_t sb, uint32_t desc128, int lane, int wg) {
    bar_sync(7 + wg, 256);
#pragma unroll
    for (int kb = 0; kb < 8; kb++) {
        const int st = ring_slot(u0 + kb);
        mbar_wait(sb + BAR_FULL + 8 * st, ring_lap(u0 + kb) & 1);
        wg_fence();
        const uint32_t d = desc128 + st * (STAGE_BYTES >> 4);
        const uint32_t d2 = d + (8192 >> 4) - ((4096u >> 4) << 16);
#pragma unroll
        for (int ks = 0; ks < 4; ks++) {
            wgmma_n64_rs<DHI128>(a0, &xa[(kb * 4 + ks) * 4], d + ks * 128, (kb | ks) != 0);
            wgmma_n64_rs<DHI64>(a1, &xa[(kb * 4 + ks) * 4], d2 + ks * 64, (kb | ks) != 0);
        }
        wg_commit();
        if (kb == 7) bar_arrive(8 - wg, 256);
        if (kb > 0) {
            wg_wait<1>();
            if (lane < 2) mbar_arrive_cta(sb + BAR_EMPTY + 8 * ring_slot(u0 + kb - 1), lane);
        }
    }
    wg_wait<0>();
    acc_fence(a0);
    acc_fence(a1);
    if (lane < 2) mbar_arrive_cta(sb + BAR_EMPTY + 8 * ring_slot(u0 + 7), lane);
}

__global__ void __cluster_dims__(2, 1, 1) __launch_bounds__(384, 1)
fused_kernel(const __grid_constant__ CUtensorMap tm_x, const __grid_constant__ CUtensorMap tm_qkv,
             const __grid_constant__ CUtensorMap tm_w1, const __grid_constant__ CUtensorMap tm_w3,
             const __grid_constant__ CUtensorMap tm_w1h, const __grid_constant__ CUtensorMap tm_w3h,
             const __grid_constant__ CUtensorMap tm_w2, const __grid_constant__ CUtensorMap tm_w2h,
             const __grid_constant__ CUtensorMap tm_wo, const __nv_bfloat16* __restrict__ xg,
             __nv_bfloat16* __restrict__ outg, const char* __restrict__ p_qkv, const char* __restrict__ p_w1,
             const char* __restrict__ p_w3, const char* __restrict__ p_w2, const char* __restrict__ p_wo) {
    extern __shared__ __align__(1024) uint8_t smem[];
    const uint32_t sb = smem_u32(smem);
    const int tid = threadIdx.x;
    const int warp = tid >> 5, lane = tid & 31;
    const int rank = blockIdx.x & 1;
    const int pair = blockIdx.x >> 1;
    const int c = pair & 7;
    const int m = (pair >> 3) * 2 + rank;
    const int m2 = (pair >> 3) * 2 + (c & 1);
    const int j2 = c >> 1;

    TS(tid >> 7, 0);
    if (tid == 256) {
#pragma unroll
        for (int i = 0; i < 8; i++) mbar_init(sb + BAR_XFULL + 8 * i, 1);
        asm volatile("fence.proxy.async.shared::cta;" ::: "memory");
#pragma unroll
        for (int kb = 0; kb < 8; kb++) {
            mbar_expect_tx(sb + BAR_XFULL + 8 * kb, 16384);
            tma_load(sb + (XST0 + kb) * STAGE_BYTES, &tm_x, sb + BAR_XFULL + 8 * kb, kb * 64, m * 128);
        }
        TS(2, 21);
    } else if (tid == 0) {
#pragma unroll
        for (int i = 0; i < NST; i++) mbar_init(sb + BAR_FULL + 8 * i, 1);
        asm volatile("fence.mbarrier_init.release.cluster;" ::: "memory");
    } else if (tid == 32) {
#pragma unroll
        for (int i = 0; i < NST; i++) mbar_init(sb + BAR_EMPTY + 8 * i, 16);
        asm volatile("fence.mbarrier_init.release.cluster;" ::: "memory");
    } else if (tid == 64) {
#pragma unroll
        for (int i = 0; i < 4; i++) mbar_init(sb + BAR_KVREADY + 8 * i, 1);
        mbar_expect_tx(sb + BAR_XCHG, 32768);
        asm volatile("fence.mbarrier_init.release.cluster;" ::: "memory");
    } else if (tid >= 128 && tid < 256) {
        ((uint4*)(smem + OFF_ZERO))[tid - 128] = make_uint4(0, 0, 0, 0);
        ((uint4*)(smem + OFF_ZERO))[tid] = make_uint4(0, 0, 0, 0);
        asm volatile("fence.proxy.async.shared::cta;" ::: "memory");
    } else if (tid == 288) {
        prefetch_tm(&tm_qkv);
        prefetch_tm(rank ? &tm_w3 : &tm_w1);
        prefetch_tm(&tm_w1h);
        prefetch_tm(&tm_w3h);
        prefetch_tm(&tm_w2);
        prefetch_tm(&tm_w2h);
        prefetch_tm(&tm_wo);
    } else if (tid >= 320) {
        ((uint32_t*)(smem + OFF_ONES))[tid - 320] = 0x3F803F80u;
        asm volatile("fence.proxy.async.shared::cta;" ::: "memory");
    }
    __syncthreads();
    TS(tid >> 7, 22);
    asm volatile("barrier.cluster.arrive.relaxed.aligned;\nbarrier.cluster.wait.acquire.aligned;" ::: "memory");

    if (warp >= 8) {
        asm volatile("setmaxnreg.dec.sync.aligned.u32 40;");
        if (warp == 8) {
            if (lane == 0) {
                int st = 0;
                uint32_t lap = 0;
                for (int it = 0; it < 40; it++) {
                    const int tile = it >> 3, kb = it & 7;
                    const uint32_t full = sb + BAR_FULL + 8 * st;
                    mbar_wait(sb + BAR_EMPTY + 8 * st, (st >= XST0) ? (lap & 1) : ((lap & 1) ^ 1));
                    mbar_expect_tx(full, STAGE_BYTES);
                    const uint32_t dst = sb + st * STAGE_BYTES;
                    if (tile == 0) {
                        tma_load_mc(dst + rank * 8192, &tm_qkv, full, 512 + 512 * rank + 64 * c, kb * 64);
                    } else if (tile != 3) {
                        tma_load_mc(dst + rank * 8192, rank ? &tm_w3 : &tm_w1, full, 224 * c + 64 * (tile == 4 ? 2 : tile - 1), kb * 64);
                    } else if (rank == 0) {
                        tma_load_mc(dst, &tm_qkv, full, 64 * c, kb * 64);
                    } else {
                        tma_load_mc(dst + 8192, &tm_w1h, full, 224 * c + 192, kb * 64);
                        tma_load_mc(dst + 12288, &tm_w3h, full, 224 * c + 192, kb * 64);
                    }
                    if (++st == NST) { st = 0; lap++; }
                    if (it == 7) {
                        mbar_wait(sb + BAR_EMPTY + 8 * SCR0, 0);
                        mbar_arrive(sb + BAR_FULL + 8 * SCR0);
                        mbar_wait(sb + BAR_EMPTY + 8 * (SCR0 + 1), 0);
                        mbar_arrive(sb + BAR_FULL + 8 * (SCR0 + 1));
                        st += 2;
                    }
                }
                TS(2, 1);
                for (int b = 0; b < 18; b++) {
                    const uint32_t full = sb + BAR_FULL + 8 * st;
                    const uint32_t dst = sb + st * STAGE_BYTES;
                    mbar_wait(sb + BAR_EMPTY + 8 * st, (st >= XST0) ? (lap & 1) : ((lap & 1) ^ 1));
                    mbar_expect_tx(full, STAGE_BYTES);
                    if (b < 8 || b >= 14) {
                        const int row = (b < 8) ? 224 * (4 * rank + (b & 3)) + 64 * (b >> 2) : 224 * (4 * rank + b - 14) + 128;
                        tma_load(dst, &tm_w2, full, 128 * j2, row);
                        tma_load(dst + 8192, &tm_w2, full, 128 * j2 + 64, row);
                    } else if (b < 10) {
                        const int row = 224 * (4 * rank + 2 * (b - 8)) + 192;
                        tma_load(dst, &tm_w2h, full, 128 * j2, row);
                        tma_load(dst + 4096, &tm_w2h, full, 128 * j2, row + 224);
                        tma_load(dst + 8192, &tm_w2h, full, 128 * j2 + 64, row);
                        tma_load(dst + 12288, &tm_w2h, full, 128 * j2 + 64, row + 224);
                    } else {
                        const int row = 64 * (4 * rank + (b - 10));
                        tma_load(dst, &tm_wo, full, 128 * j2, row);
                        tma_load(dst + 8192, &tm_wo, full, 128 * j2 + 64, row);
                    }
                    TS(2, 2 + b);
                    if (++st == NST) { st = 0; lap++; }
                }
                mbar_wait(sb + BAR_EMPTY + 8 * SCR0, lap & 1);
                mbar_wait(sb + BAR_EMPTY + 8 * (SCR0 + 1), lap & 1);
                mbar_arrive_cta(sb + BAR_XRDY, rank ^ 1);
            }
        } else if (warp < 11) {
            const int wg = warp - 9;
            bar_sync(3 + wg, 160);
            if (lane == 0) asm volatile("red.release.gpu.global.add.u32 [%0], 1;" ::"l"(&g_kvcnt[c]) : "memory");
            TSW(3, wg);
        } else {
            const unsigned epoch = read_epoch();
            if (lane == 0) {
                const unsigned tk = atomicInc(&g_ticket, 127u);
                if (tk == 127u) *(volatile unsigned*)&g_epoch = epoch;
            }
            if (lane == 0) *(volatile unsigned*)(smem + OFF_EPOCH) = epoch;
            __syncwarp();
            if (lane == 0) mbar_arrive(sb + BAR_EPOCH);
            if (lane < 17) g_kvacc[(((epoch & 1) ^ 1) * 8 + c) * 272 + 17 * m + lane] = make_float4(0.f, 0.f, 0.f, 0.f);
            {
                unsigned n = 0;
                while ((int)(ld_acquire(&g_kvcnt[c]) - 32u * epoch) < 0) {
                    __nanosleep(200);
                    if (++n > SPIN_LIMIT) asm volatile("trap;");
                }
            }
            TSW(4, 0);
            const int g = lane >> 2, t = lane & 3;
            const float* ks = (const float*)(g_kvacc + ((epoch & 1) * 8 + c) * 272) + 32 * t + g;
            uint2* kf = (uint2*)(smem + OFF_KVFRAG) + lane;
#pragma unroll 2
            for (int hh = 0; hh < 4; hh++) {
                const float* k = ks + hh * 272;
                const float a0 = __ldcg(k), a1 = __ldcg(k + 16), a2 = __ldcg(k + 128), a3 = __ldcg(k + 144);
                const float b0 = __ldcg(k + 8), b1 = __ldcg(k + 24), b2 = __ldcg(k + 136), b3 = __ldcg(k + 152);
                const float2 z0 = __ldcg((const float2*)(k - g - 30 * t + 256)), z1 = __ldcg((const float2*)(k - g - 30 * t + 264));
                kf[(hh * 3 + 0) * 32] = make_uint2(pack_bf16(a0, a1), pack_bf16(a2, a3));
                kf[(hh * 3 + 1) * 32] = make_uint2(pack_bf16(b0, b1), pack_bf16(b2, b3));
                kf[(hh * 3 + 2) * 32] = make_uint2(pack_bf16(z0.x, z0.y), pack_bf16(z1.x, z1.y));
            }
            __syncwarp();
            if (lane == 0) mbar_arrive(sb + BAR_KVREADY);
            TSW(4, 4);
            if (lane == 0) {
                char* z = (char*)(g_A2 + (size_t)((epoch & 1) ^ 1) * A2_N + (size_t)((m * 2 + (c >> 2)) * 18) * 4 * 256);
                const int cc = c & 3;
#pragma unroll 1
                for (int i = 0; i < 18; i++) {
                    const int blk = (i < 8) ? ((i >> 2) * 4 + cc) * 4 + (i & 3)
                                  : (i < 10) ? (8 + (cc >> 1)) * 4 + 2 * (cc & 1) + (i - 8)
                                  : (i < 14) ? (10 + cc) * 4 + (i - 10) : (14 + cc) * 4 + (i - 14);
                    asm volatile("cp.async.bulk.global.shared::cta.bulk_group [%0], [%1], 4096;"
                                 ::"l"(z + (size_t)blk * 4096), "r"(sb + OFF_ZERO) : "memory");
                }
                asm volatile("cp.async.bulk.commit_group;" ::: "memory");
            }
            if (lane == 0) asm volatile("cp.async.bulk.wait_group 0;" ::: "memory");
        }
    } else {
        asm volatile("setmaxnreg.inc.sync.aligned.u32 232;");
        const int wg = warp >> 2, w = warp & 3;
        const int g = lane >> 2, t = lane & 3;
        float acc[64];
        uint32_t xa[128];
        float rho0, rho1;
        RowScale r0, r1;
        unsigned par;

        TS(wg, 1);
        {
            const int row = wg * 64 + w * 16 + (lane & 7) + ((lane >> 3) & 1) * 8;
            const uint32_t rbase = sb + XST0 * STAGE_BYTES + row * 128;
            const int hi = lane >> 4, r7 = lane & 7;
            float sm[2][4], c0[2][4], c1[2][4];
#pragma unroll
            for (int i = 0; i < 8; i++) { sm[i >> 2][i & 3] = 0.f; c0[i >> 2][i & 3] = 0.f; c1[i >> 2][i & 3] = 0.f; }
            if (wg == 1) bar_arrive(7, 256);
#pragma unroll
            for (int kb = 0; kb < 8; kb++) {
                mbar_wait(sb + BAR_XFULL + 8 * kb, 0);
#pragma unroll
                for (int ks = 0; ks < 4; ks++) {
                    uint32_t* a = &xa[(kb * 4 + ks) * 4];
                    const uint32_t addr = rbase + kb * STAGE_BYTES + (((2 * ks + hi) ^ r7) << 4);
                    asm volatile("ldmatrix.sync.aligned.m8n8.x4.shared.b16 {%0,%1,%2,%3}, [%4];"
                                 : "=r"(a[0]), "=r"(a[1]), "=r"(a[2]), "=r"(a[3]) : "r"(addr) : "memory");
                    mma16816(sm[ks & 1], a, 0x3F803F80u, 0x3F803F80u);
                    mma16816(c0[ks & 1], a, a[0], a[2]);
                    mma16816(c1[ks & 1], a, a[1], a[3]);
                }
            }
            TS(wg, 2);
            const float mean0 = (sm[0][0] + sm[1][0]) * (1.f / 512.f);
            const float mean1 = (sm[0][2] + sm[1][2]) * (1.f / 512.f);
            __syncwarp();
            if (lane < 16) mbar_arrive_cta(sb + BAR_EMPTY + 8 * (XST0 + (lane >> 1)), lane & 1);
            const __nv_bfloat162 mb0 = __float2bfloat162_rn(mean0), mb1 = __float2bfloat162_rn(mean1);
#pragma unroll
            for (int i = 0; i < 128; i++) {
                __nv_bfloat162 v = *reinterpret_cast<__nv_bfloat162*>(&xa[i]);
                v = __hsub2(v, (i & 1) ? mb1 : mb0);
                xa[i] = *reinterpret_cast<uint32_t*>(&v);
            }
            const float d0 = (g & 1) ? c0[0][1] + c0[1][1] : c0[0][0] + c0[1][0];
            const float d1 = (g & 1) ? c1[0][3] + c1[1][3] : c1[0][2] + c1[1][2];
            const int src = (lane & ~3) | (g >> 1);
            const float var0 = fmaxf(__shfl_sync(0xffffffffu, d0, src) * (1.f / 512.f) - mean0 * mean0, 0.f);
            const float var1 = fmaxf(__shfl_sync(0xffffffffu, d1, src) * (1.f / 512.f) - mean1 * mean1, 0.f);
            const float sd0 = bf16_round(sqrt_fast(bf16_round(bf16_round(var0) + 1e-5f)));
            const float sd1 = bf16_round(sqrt_fast(bf16_round(bf16_round(var1) + 1e-5f)));
            rho0 = rcp_fast(sd0);
            rho1 = rcp_fast(sd1);
            r0.rho = rho0; r0.rl = rho0 * 1.4426950408889634f; r0.var = sd0 * sd0;
            r1.rho = rho1; r1.rl = rho1 * 1.4426950408889634f; r1.var = sd1 * sd1;
        }

        TS(wg, 3);
        const uint32_t desc128 = ((sb & 0x3FFFF) >> 4) | ((8192u >> 4) << 16);
        const int cc = c & 3;

        {
            mainloop128(acc, xa, 0, sb, desc128, lane, wg);
            TS(wg, 4);
            {
                TS(wg, 24);
                const uint32_t pkb = sb + (SCR0 + wg) * STAGE_BYTES;
                mbar_wait(sb + BAR_FULL + 8 * (SCR0 + wg), 0);
                const uint32_t ra = pkb + (w * 16 + g) * 128 + t * 4;
#pragma unroll
                for (int nb = 0; nb < 8; nb++) {
                    const uint32_t off = (uint32_t)((nb ^ g) << 4);
                    uint32_t p0 = pack_bf16(phi_f(acc[nb * 4], r0), phi_f(acc[nb * 4 + 1], r0));
                    uint32_t p1 = pack_bf16(phi_f(acc[nb * 4 + 2], r1), phi_f(acc[nb * 4 + 3], r1));
                    uint32_t v0 = pack_bf16(acc[32 + nb * 4] * rho0, acc[32 + nb * 4 + 1] * rho0);
                    uint32_t v1 = pack_bf16(acc[32 + nb * 4 + 2] * rho1, acc[32 + nb * 4 + 3] * rho1);
                    asm volatile("st.shared.u32 [%0], %1;" ::"r"(ra + off), "r"(p0) : "memory");
                    asm volatile("st.shared.u32 [%0], %1;" ::"r"(ra + off + 1024), "r"(p1) : "memory");
                    asm volatile("st.shared.u32 [%0], %1;" ::"r"(ra + off + 8192), "r"(v0) : "memory");
                    asm volatile("st.shared.u32 [%0], %1;" ::"r"(ra + off + 8192 + 1024), "r"(v1) : "memory");
                }
                TS(wg, 25);
                asm volatile("fence.proxy.async.shared::cta;" ::: "memory");
                bar_sync(1 + wg, 128);
                TS(wg, 26);
                const uint64_t da = make_desc(pkb, 8192, 1024, 1);
                const uint64_t db = make_desc(pkb + 8192, 8192, 1024, 1);
                const uint64_t d1 = make_desc(sb + OFF_ONES, 128, 128, 0);
                float kva[32], za[4];
                wg_fence();
#pragma unroll
                for (int ks = 0; ks < 4; ks++) {
                    wgmma_n64_ss_tt(kva, da + ks * 128, db + ks * 128, ks != 0);
                    wgmma_n8_ss_tn(za, da + ks * 128, d1, ks != 0);
                }
                wg_commit();
                wg_wait<0>();
                acc_fence(kva);
                acc_fence(za);
                if (lane < 4) mbar_arrive_cta(sb + BAR_EMPTY + 8 * (SCR0 + (lane >> 1)), lane & 1);
                TS(wg, 27);
                float o[8];
#pragma unroll
                for (int i = 0; i < 8; i++)
                    o[i] = (w == 0) ? kva[i] : (w == 1) ? kva[8 + i] : (w == 2) ? kva[16 + i] : kva[24 + i];
                mbar_wait(sb + BAR_EPOCH, 0);
                par = *(volatile unsigned*)(smem + OFF_EPOCH) & 1;
                float* dst = (float*)(g_kvacc + (par * 8 + c) * 272) + w * 272 + g * 16 + 2 * t;
                red_add2(dst, o[0], o[1]);
                red_add2(dst + 128, o[2], o[3]);
                red_add2(dst + 8, o[4], o[5]);
                red_add2(dst + 136, o[6], o[7]);
                if (t == 0) {
                    atomicAdd(dst - g * 15 + 256, za[0]);
                    atomicAdd(dst - g * 15 + 264, za[2]);
                }
            }
            bar_arrive(3 + wg, 160);
            TS(wg, 5);
        }
        uint4* a2w = g_A2 + (size_t)par * A2_N + (size_t)((m * 2 + (c >> 2)) * 18) * 4 * 256 + warp * 32 + lane;
#pragma unroll
        for (int tile = 1; tile < 3; tile++) {
            mainloop128(acc, xa, 2 + 8 * tile, sb, desc128, lane, wg);
            TS(wg, 4 + 2 * tile);
            uint4* dst = a2w + (size_t)((4 * (tile - 1) + cc) * 4) * 256;
#pragma unroll
            for (int ks = 0; ks < 4; ks++) st_frag(dst + ks * 256, swiglu8(&acc[ks * 8], &acc[32 + ks * 8], r0, r1));
            TS(wg, 5 + 2 * tile);
        }
        {
            float qa[32], gu[32];
            mainloop64x2(qa, gu, xa, 26, sb, desc128, lane, wg);
            TS(wg, 10);
            uint4* dst = a2w + (size_t)((8 + (cc >> 1)) * 4 + 2 * (cc & 1)) * 256;
#pragma unroll
            for (int ks = 0; ks < 2; ks++) st_frag(dst + ks * 256, swiglu8(&gu[ks * 8], &gu[16 + ks * 8], r0, r1));
            TS(wg, 13);
            mbar_wait(sb + BAR_KVREADY, 0);
            TS(wg, 14);
            const uint2* kf = (const uint2*)(smem + OFF_KVFRAG);
            dst = a2w + (size_t)((10 + cc) * 4) * 256;
#pragma unroll
            for (int hh = 0; hh < 4; hh++) {
                const float* q = &qa[hh * 8];
                uint32_t a[4];
                a[0] = pack_bf16(phi_f(q[0], r0), phi_f(q[1], r0));
                a[1] = pack_bf16(phi_f(q[2], r1), phi_f(q[3], r1));
                a[2] = pack_bf16(phi_f(q[4], r0), phi_f(q[5], r0));
                a[3] = pack_bf16(phi_f(q[6], r1), phi_f(q[7], r1));
                float n0[4] = {0.f, 0.f, 0.f, 0.f}, n1[4] = {0.f, 0.f, 0.f, 0.f}, dn[4] = {0.f, 0.f, 0.f, 0.f};
                const uint2 b0 = kf[(hh * 3 + 0) * 32 + lane], b1 = kf[(hh * 3 + 1) * 32 + lane],
                            bz = kf[(hh * 3 + 2) * 32 + lane];
                mma16816(n0, a, b0.x, b0.y);
                mma16816(n1, a, b1.x, b1.y);
                mma16816(dn, a, bz.x, bz.y);
                const float i0 = rcp_fast(dn[0] + 1e-6f), i1 = rcp_fast(dn[2] + 1e-6f);
                uint4 v;
                v.x = pack_bf16(n0[0] * i0, n0[1] * i0);
                v.y = pack_bf16(n0[2] * i1, n0[3] * i1);
                v.z = pack_bf16(n1[0] * i0, n1[1] * i0);
                v.w = pack_bf16(n1[2] * i1, n1[3] * i1);
                v.y = v.y ? v.y : 0x8000u;
                v.w = v.w ? v.w : 0x8000u;
                st_frag(dst + hh * 256, v);
            }
            TS(wg, 11);
        }
        const uint4* a2r = g_A2 + (size_t)par * A2_N + (size_t)((m2 * 2 + rank) * 18) * 4 * 256 + warp * 32 + lane;
        uint4 af[2][12];
        {
            mainloop128(acc, xa, 34, sb, desc128, lane, wg);
            TS(wg, 12);
#pragma unroll
            for (int i = 0; i < 12; i++) af[0][i] = ld_frag(a2r + i * 256);
            uint4* dst = a2w + (size_t)((14 + cc) * 4) * 256;
#pragma unroll
            for (int ks = 0; ks < 4; ks++) st_frag(dst + ks * 256, swiglu8(&acc[ks * 8], &acc[32 + ks * 8], r0, r1));
            TS(wg, 15);
        }

        {
            float ao[32], ap[32];
            const uint32_t dso = desc128 + rank * 512, dsp = desc128 + (rank ^ 1) * 512;
            TS(wg, 16);
#pragma unroll
            for (int gi = 0; gi < 6; gi++) {
                if (gi == 5) TS(wg, 17);
                uint4(&f)[12] = af[gi & 1];
                {
                    unsigned n = 0;
                    while (frag_stale(f)) {
#pragma unroll
                        for (int i = 0; i < 12; i++) f[i] = ld_frag(a2r + (gi * 12 + i) * 256);
                        if (++n > SPIN_LIMIT) asm volatile("trap;");
                    }
                }
#pragma unroll
                for (int bb = 0; bb < 3; bb++)
                    mbar_wait(sb + BAR_FULL + 8 * ring_slot(42 + gi * 3 + bb), ring_lap(42 + gi * 3 + bb) & 1);
                bar_sync(7 + wg, 256);
                wg_fence();
#pragma unroll
                for (int i = 0; i < 12; i++) {
                    const uint32_t so = ring_slot(42 + gi * 3 + (i >> 2)) * (STAGE_BYTES >> 4) + (i & 3) * 128;
                    const uint32_t* a = reinterpret_cast<const uint32_t*>(&f[i]);
                    wgmma_n64_rs<DHI128>(ap, a, dsp + so, (gi | i) != 0);
                    if (gi < 5) wgmma_n64_rs<DHI128>(ao, a, dso + so, (gi | i) != 0);
                }
                wg_commit();
                bar_arrive(8 - wg, 256);
                if (gi < 5) {
                    if (gi > 0) {
                        wg_wait<1>();
                        if (lane < 6) mbar_arrive(sb + BAR_EMPTY + 8 * ring_slot(39 + gi * 3 + (lane >> 1)));
                    }
#pragma unroll
                    for (int i = 0; i < 12; i++) af[(gi + 1) & 1][i] = ld_frag(a2r + ((gi + 1) * 12 + i) * 256);
                }
            }
            const int row0 = m2 * 128 + wg * 64 + w * 16 + g;
            const int col0 = j2 * 128 + rank * 64 + 2 * t;
            uint32_t xr[16];
#pragma unroll
            for (int nb = 0; nb < 8; nb++) {
                xr[2 * nb] = __ldg((const uint32_t*)(xg + (size_t)row0 * 512 + col0 + nb * 8));
                xr[2 * nb + 1] = __ldg((const uint32_t*)(xg + (size_t)(row0 + 8) * 512 + col0 + nb * 8));
            }
            uint32_t rdst, rbar;
            asm volatile("mapa.shared::cluster.u32 %0, %1, %2;"
                         : "=r"(rdst) : "r"(sb + (SCR0 + wg) * STAGE_BYTES + (tid & 127) * 16), "r"(rank ^ 1));
            asm volatile("mapa.shared::cluster.u32 %0, %1, %2;" : "=r"(rbar) : "r"(sb + BAR_XCHG), "r"(rank ^ 1));
            mbar_wait(sb + BAR_XRDY, 0);
            wg_wait<0>();
            acc_fence(ap);
            TS(wg, 18);
#pragma unroll
            for (int i = 0; i < 8; i++)
                asm volatile("st.async.shared::cluster.mbarrier::complete_tx::bytes.v4.f32 [%0], {%1,%2,%3,%4}, [%5];"
                             ::"r"(rdst + i * 2048), "f"(ap[4 * i]), "f"(ap[4 * i + 1]), "f"(ap[4 * i + 2]), "f"(ap[4 * i + 3]),
                             "r"(rbar) : "memory");
            bar_sync(7 + wg, 256);
            wg_fence();
#pragma unroll
            for (int i = 0; i < 12; i++)
                wgmma_n64_rs<DHI128>(ao, reinterpret_cast<const uint32_t*>(&af[1][i]),
                                     dso + ring_slot(57 + (i >> 2)) * (STAGE_BYTES >> 4) + (i & 3) * 128, 1);
            wg_commit();
            if (wg == 0) bar_arrive(8, 256);
            wg_wait<0>();
            acc_fence(ao);
            mbar_wait(sb + BAR_XCHG, 0);
            TS(wg, 19);
            const float4* rx = (const float4*)(smem + (SCR0 + wg) * STAGE_BYTES) + (tid & 127);
#pragma unroll
            for (int nb = 0; nb < 8; nb++) {
                const float4 p = rx[nb * 128];
                const uint32_t o0 = pack_bf16(ao[4 * nb] + p.x + bf_lo(xr[2 * nb]), ao[4 * nb + 1] + p.y + bf_hi(xr[2 * nb]));
                const uint32_t o1 = pack_bf16(ao[4 * nb + 2] + p.z + bf_lo(xr[2 * nb + 1]), ao[4 * nb + 3] + p.w + bf_hi(xr[2 * nb + 1]));
                *(uint32_t*)(outg + (size_t)row0 * 512 + col0 + nb * 8) = o0;
                *(uint32_t*)(outg + (size_t)(row0 + 8) * 512 + col0 + nb * 8) = o1;
            }
        }
        TS(wg, 20);
    }
}

typedef CUresult (*EncodeFn)(CUtensorMap*, CUtensorMapDataType, cuuint32_t, void*, const cuuint64_t*, const cuuint64_t*,
                             const cuuint32_t*, const cuuint32_t*, CUtensorMapInterleave, CUtensorMapSwizzle,
                             CUtensorMapL2promotion, CUtensorMapFloatOOBfill);

void make_map(EncodeFn enc, CUtensorMap* tm, const void* ptr, int rows, int cols, int box_rows, int box_cols,
              CUtensorMapSwizzle swz) {
    cuuint64_t dims[2] = {(cuuint64_t)cols, (cuuint64_t)rows};
    cuuint64_t strides[1] = {(cuuint64_t)cols * 2};
    cuuint32_t box[2] = {(cuuint32_t)box_cols, (cuuint32_t)box_rows};
    cuuint32_t es[2] = {1, 1};
    enc(tm, CU_TENSOR_MAP_DATA_TYPE_BFLOAT16, 2, const_cast<void*>(ptr), dims, strides, box, es,
        CU_TENSOR_MAP_INTERLEAVE_NONE, swz, CU_TENSOR_MAP_L2_PROMOTION_L2_256B, CU_TENSOR_MAP_FLOAT_OOB_FILL_NONE);
}

}

extern "C" void kernel_launch(void* const* d_in, const int* in_sizes, int n_in, void* d_out, int out_size) {
    (void)in_sizes; (void)n_in; (void)out_size;
    static EncodeFn enc = nullptr;
    if (!enc) {
        void* fn = nullptr;
        cudaDriverEntryPointQueryResult qr;
        cudaGetDriverEntryPoint("cuTensorMapEncodeTiled", &fn, cudaEnableDefault, &qr);
        enc = (EncodeFn)fn;
        cudaFuncSetAttribute(fused_kernel, cudaFuncAttributeMaxDynamicSharedMemorySize, SMEM_BYTES);
    }
    const void* x = d_in[0];
    const void* wqkv = d_in[1];
    const void* wo = d_in[2];
    const void* w1 = d_in[4];
    const void* w3 = d_in[5];
    const void* w2 = d_in[6];
    CUtensorMap tx, tqkv, t1, t3, t1h, t3h, t2, t2h, two;
    make_map(enc, &tx, x, 2048, 512, 128, 64, CU_TENSOR_MAP_SWIZZLE_128B);
    make_map(enc, &tqkv, wqkv, 512, 1536, 64, 64, CU_TENSOR_MAP_SWIZZLE_128B);
    make_map(enc, &t1, w1, 512, 1792, 64, 64, CU_TENSOR_MAP_SWIZZLE_128B);
    make_map(enc, &t3, w3, 512, 1792, 64, 64, CU_TENSOR_MAP_SWIZZLE_128B);
    make_map(enc, &t1h, w1, 512, 1792, 64, 32, CU_TENSOR_MAP_SWIZZLE_64B);
    make_map(enc, &t3h, w3, 512, 1792, 64, 32, CU_TENSOR_MAP_SWIZZLE_64B);
    make_map(enc, &t2, w2, 1792, 512, 64, 64, CU_TENSOR_MAP_SWIZZLE_128B);
    make_map(enc, &t2h, w2, 1792, 512, 32, 64, CU_TENSOR_MAP_SWIZZLE_128B);
    make_map(enc, &two, wo, 512, 512, 64, 64, CU_TENSOR_MAP_SWIZZLE_128B);
    fused_kernel<<<128, 384, SMEM_BYTES>>>(tx, tqkv, t1, t3, t1h, t3h, t2, t2h, two, (const __nv_bfloat16*)x,
                                           (__nv_bfloat16*)d_out, (const char*)wqkv, (const char*)w1, (const char*)w3,
                                           (const char*)w2, (const char*)wo);
}
```

```cpp
#include <cuda_runtime.h>
#include <cuda_bf16.h>
#include <cuda.h>
#include <stdint.h>

namespace {

constexpr int NST = 13;
constexpr int STAGE_BYTES = 16384;
constexpr int XST0 = 5;
constexpr int SCR0 = 8;
constexpr int XCH0 = 3;
__host__ __device__ constexpr int p2_id(int i) {
    constexpr int t[18] = {0, 1, 2, 3, 8, 4, 5, 9, 10, 6, 11, 12, 7, 13, 14, 15, 16, 17};
    return t[i];
}
__host__ __device__ constexpr int p2_useB(int i) {
    constexpr int t[18] = {43, 45, 47, 49, 50, 52, 54, 55, 56, 58, 59, 60, 62, 63, 64, 65, 66, 67};
    return t[i];
}
constexpr int OFF_MISC = NST * STAGE_BYTES;
constexpr int OFF_KVFRAG = OFF_MISC;
constexpr int OFF_ONES = OFF_MISC + 3072;
constexpr int OFF_BARS = OFF_MISC + 3328;
constexpr int BAR_FULL = OFF_BARS;
constexpr int BAR_EMPTY = BAR_FULL + 8 * NST;
constexpr int BAR_XFULL = BAR_EMPTY + 8 * NST;
constexpr int BAR_KVREADY = BAR_XFULL + 64;
constexpr int BAR_XCHG = BAR_KVREADY + 8;
constexpr int BAR_EPOCH = BAR_XCHG + 8;
constexpr int BAR_XRDY = BAR_EPOCH + 8;
constexpr int OFF_EPOCH = BAR_XRDY + 8;
constexpr int OFF_ZERO = OFF_MISC + 4096;
constexpr int SMEM_BYTES = OFF_MISC + 8192;

constexpr unsigned SPIN_LIMIT = 1u << 24;

constexpr int A2_N = 16 * 2 * 18 * 4 * 256;
__device__ uint4 g_A2[2 * A2_N];
__device__ float4 g_kvacc[2 * 8 * 272];
__device__ unsigned g_kvcnt[8];
__constant__ unsigned char P2_ID[18] = {0, 1, 2, 3, 8, 4, 5, 9, 10, 6, 11, 12, 7, 13, 14, 15, 16, 17};
__device__ unsigned g_epoch;
__device__ unsigned g_ticket;

#define TS(role, i)
#define TSW(role, i)

__device__ __forceinline__ uint32_t smem_u32(const void* p) { return (uint32_t)__cvta_generic_to_shared(p); }
__device__ __forceinline__ void mbar_init(uint32_t bar, uint32_t cnt) {
    asm volatile("mbarrier.init.shared::cta.b64 [%0], %1;" ::"r"(bar), "r"(cnt) : "memory");
}
__device__ __forceinline__ void mbar_expect_tx(uint32_t bar, uint32_t bytes) {
    asm volatile("mbarrier.arrive.expect_tx.shared::cta.b64 _, [%0], %1;" ::"r"(bar), "r"(bytes) : "memory");
}
__device__ __forceinline__ void mbar_arrive(uint32_t bar) {
    asm volatile("mbarrier.arrive.shared::cta.b64 _, [%0];" ::"r"(bar) : "memory");
}
__device__ __forceinline__ void mbar_arrive_cta(uint32_t bar, uint32_t cta) {
    asm volatile(
        "{\n.reg .b32 ra;\nmapa.shared::cluster.u32 ra, %0, %1;\n"
        "mbarrier.arrive.shared::cluster.b64 _, [ra];\n}" ::"r"(bar), "r"(cta) : "memory");
}
__device__ __forceinline__ void mbar_wait(uint32_t bar, uint32_t parity) {
    asm volatile(
        "{\n.reg .pred p, q;\n.reg .u32 n;\nmov.u32 n, 0;\n"
        "WAIT_%=:\n"
        "mbarrier.try_wait.parity.shared::cta.b64 p, [%0], %1;\n"
        "@p bra.uni DONE_%=;\n"
        "add.u32 n, n, 1;\n"
        "setp.gt.u32 q, n, %2;\n"
        "@q trap;\n"
        "bra.uni WAIT_%=;\n"
        "DONE_%=:\n}"
        ::"r"(bar), "r"(parity), "n"(SPIN_LIMIT) : "memory");
}
__device__ __forceinline__ unsigned ld_acquire(const unsigned* p) {
    unsigned v;
    asm volatile("ld.acquire.gpu.global.u32 %0, [%1];" : "=r"(v) : "l"(p) : "memory");
    return v;
}
__device__ __forceinline__ void st_release(unsigned* p, unsigned v) {
    asm volatile("st.release.gpu.global.u32 [%0], %1;" ::"l"(p), "r"(v) : "memory");
}
__device__ __forceinline__ unsigned read_epoch() {
    return __shfl_sync(0xffffffffu, *(volatile unsigned*)&g_epoch, 0) + 1;
}
__device__ __forceinline__ void tma_load(uint32_t dst, const CUtensorMap* tm, uint32_t bar, int x, int y) {
    asm volatile(
        "cp.async.bulk.tensor.2d.shared::cluster.global.mbarrier::complete_tx::bytes [%0], [%1, {%3, %4}], [%2];"
        ::"r"(dst), "l"(tm), "r"(bar), "r"(x), "r"(y) : "memory");
}
__device__ __forceinline__ void tma_load_mc(uint32_t dst, const CUtensorMap* tm, uint32_t bar, int x, int y) {
    asm volatile(
        "cp.async.bulk.tensor.2d.shared::cluster.global.mbarrier::complete_tx::bytes.multicast::cluster "
        "[%0], [%1, {%3, %4}], [%2], %5;"
        ::"r"(dst), "l"(tm), "r"(bar), "r"(x), "r"(y), "h"((uint16_t)3) : "memory");
}
__device__ __forceinline__ void prefetch_tm(const CUtensorMap* tm) {
    asm volatile("prefetch.tensormap [%0];" ::"l"(tm) : "memory");
}
__device__ __forceinline__ void l2_prefetch(const void* p, uint32_t bytes) {
    asm volatile("cp.async.bulk.prefetch.L2.global [%0], %1;" ::"l"(p), "r"(bytes) : "memory");
}
__device__ __forceinline__ void bar_sync(int id, int n) { asm volatile("bar.sync %0, %1;" ::"r"(id), "r"(n) : "memory"); }
__device__ __forceinline__ void bar_arrive(int id, int n) { asm volatile("bar.arrive %0, %1;" ::"r"(id), "r"(n) : "memory"); }
__device__ __forceinline__ void wg_fence() { asm volatile("wgmma.fence.sync.aligned;" ::: "memory"); }
__device__ __forceinline__ void wg_commit() { asm volatile("wgmma.commit_group.sync.aligned;" ::: "memory"); }
template <int N>
__device__ __forceinline__ void wg_wait() { asm volatile("wgmma.wait_group.sync.aligned %0;" ::"n"(N) : "memory"); }

__device__ __forceinline__ uint64_t make_desc(uint32_t addr, uint32_t lbo, uint32_t sbo, uint64_t swz) {
    return (uint64_t)((addr & 0x3FFFF) >> 4) | ((uint64_t)(lbo >> 4) << 16) | ((uint64_t)(sbo >> 4) << 32) | (swz << 62);
}

#define ACC8(a, o) "+f"(a[o]), "+f"(a[o + 1]), "+f"(a[o + 2]), "+f"(a[o + 3]), "+f"(a[o + 4]), "+f"(a[o + 5]), "+f"(a[o + 6]), "+f"(a[o + 7])
constexpr uint32_t DHI128 = (1024u >> 4) | (1u << 30);
constexpr uint32_t DHI64 = (512u >> 4) | (2u << 30);
__device__ __forceinline__ void wgmma_n128_rs(float (&d)[64], const uint32_t* a, uint32_t db, int scale_d) {
    asm volatile(
        "{\n.reg .pred p;\n.reg .b64 dd;\nsetp.ne.b32 p, %69, 0;\nmov.b64 dd, {%68, %70};\n"
        "wgmma.mma_async.sync.aligned.m64n128k16.f32.bf16.bf16 "
        "{%0,%1,%2,%3,%4,%5,%6,%7,%8,%9,%10,%11,%12,%13,%14,%15,%16,%17,%18,%19,%20,%21,%22,%23,%24,%25,%26,%27,%28,%29,%30,%31,"
        "%32,%33,%34,%35,%36,%37,%38,%39,%40,%41,%42,%43,%44,%45,%46,%47,%48,%49,%50,%51,%52,%53,%54,%55,%56,%57,%58,%59,%60,%61,%62,%63},"
        "{%64,%65,%66,%67}, dd, p, 1, 1, 1;\n}"
        : ACC8(d, 0), ACC8(d, 8), ACC8(d, 16), ACC8(d, 24), ACC8(d, 32), ACC8(d, 40), ACC8(d, 48), ACC8(d, 56)
        : "r"(a[0]), "r"(a[1]), "r"(a[2]), "r"(a[3]), "r"(db), "r"(scale_d), "n"(DHI128));
}
template <uint32_t HI>
__device__ __forceinline__ void wgmma_n64_rs(float (&d)[32], const uint32_t* a, uint32_t db, int scale_d) {
    asm volatile(
        "{\n.reg .pred p;\n.reg .b64 dd;\nsetp.ne.b32 p, %37, 0;\nmov.b64 dd, {%36, %38};\n"
        "wgmma.mma_async.sync.aligned.m64n64k16.f32.bf16.bf16 "
        "{%0,%1,%2,%3,%4,%5,%6,%7,%8,%9,%10,%11,%12,%13,%14,%15,%16,%17,%18,%19,%20,%21,%22,%23,%24,%25,%26,%27,%28,%29,%30,%31},"
        "{%32,%33,%34,%35}, dd, p, 1, 1, 1;\n}"
        : ACC8(d, 0), ACC8(d, 8), ACC8(d, 16), ACC8(d, 24)
        : "r"(a[0]), "r"(a[1]), "r"(a[2]), "r"(a[3]), "r"(db), "r"(scale_d), "n"(HI));
}
__device__ __forceinline__ void wgmma_n64_ss_tt(float (&d)[32], uint64_t da, uint64_t db, int scale_d) {
    asm volatile(
        "{\n.reg .pred p;\nsetp.ne.b32 p, %34, 0;\n"
        "wgmma.mma_async.sync.aligned.m64n64k16.f32.bf16.bf16 "
        "{%0,%1,%2,%3,%4,%5,%6,%7,%8,%9,%10,%11,%12,%13,%14,%15,%16,%17,%18,%19,%20,%21,%22,%23,%24,%25,%26,%27,%28,%29,%30,%31},"
        "%32, %33, p, 1, 1, 1, 1;\n}"
        : ACC8(d, 0), ACC8(d, 8), ACC8(d, 16), ACC8(d, 24)
        : "l"(da), "l"(db), "r"(scale_d));
}
__device__ __forceinline__ void wgmma_n8_ss_tn(float (&d)[4], uint64_t da, uint64_t db, int scale_d) {
    asm volatile(
        "{\n.reg .pred p;\nsetp.ne.b32 p, %6, 0;\n"
        "wgmma.mma_async.sync.aligned.m64n8k16.f32.bf16.bf16 {%0,%1,%2,%3}, %4, %5, p, 1, 1, 1, 0;\n}"
        : "+f"(d[0]), "+f"(d[1]), "+f"(d[2]), "+f"(d[3])
        : "l"(da), "l"(db), "r"(scale_d));
}
template <int N>
__device__ __forceinline__ void acc_fence(float (&d)[N]) {
#pragma unroll
    for (int i = 0; i < N; i++) asm volatile("" : "+f"(d[i])::"memory");
}
__device__ __forceinline__ void mma16816(float (&c)[4], const uint32_t* a, uint32_t b0, uint32_t b1) {
    asm volatile(
        "mma.sync.aligned.m16n8k16.row.col.f32.bf16.bf16.f32 {%0,%1,%2,%3}, {%4,%5,%6,%7}, {%8,%9}, {%0,%1,%2,%3};"
        : "+f"(c[0]), "+f"(c[1]), "+f"(c[2]), "+f"(c[3])
        : "r"(a[0]), "r"(a[1]), "r"(a[2]), "r"(a[3]), "r"(b0), "r"(b1));
}
__device__ __forceinline__ uint32_t pack_bf16(float lo, float hi) {
    uint32_t r;
    asm("cvt.rn.bf16x2.f32 %0, %1, %2;" : "=r"(r) : "f"(hi), "f"(lo));
    return r;
}
__device__ __forceinline__ float bf_lo(uint32_t v) { return __uint_as_float(v << 16); }
__device__ __forceinline__ float bf_hi(uint32_t v) { return __uint_as_float(v & 0xffff0000u); }
__device__ __forceinline__ float bf16_round(float v) { return __bfloat162float(__float2bfloat16_rn(v)); }
__device__ __forceinline__ float sqrt_fast(float v) {
    float r;
    asm("sqrt.approx.ftz.f32 %0, %1;" : "=f"(r) : "f"(v));
    return r;
}
__device__ __forceinline__ float rcp_fast(float v) {
    float r;
    asm("rcp.approx.ftz.f32 %0, %1;" : "=f"(r) : "f"(v));
    return r;
}
__device__ __forceinline__ float ex2_fast(float v) {
    float r;
    asm("ex2.approx.ftz.f32 %0, %1;" : "=f"(r) : "f"(v));
    return r;
}
struct RowScale { float rho, rl, var; };
__device__ __forceinline__ float phi_f(float a, const RowScale& r) {
    return fmaf(fmaxf(a, 0.f), r.rho, ex2_fast(fminf(a, 0.f) * r.rl) + 1e-6f);
}
__device__ __forceinline__ float swiglu_f(float ga, float ua, const RowScale& r) {
    return (ga * ua) * rcp_fast(fmaf(ex2_fast(-ga * r.rl), r.var, r.var));
}
__device__ __forceinline__ uint4 swiglu8(const float* gp, const float* up, const RowScale& r0, const RowScale& r1) {
    uint4 v;
    v.x = pack_bf16(swiglu_f(gp[0], up[0], r0), swiglu_f(gp[1], up[1], r0));
    v.y = pack_bf16(swiglu_f(gp[2], up[2], r1), swiglu_f(gp[3], up[3], r1));
    v.z = pack_bf16(swiglu_f(gp[4], up[4], r0), swiglu_f(gp[5], up[5], r0));
    v.w = pack_bf16(swiglu_f(gp[6], up[6], r1), swiglu_f(gp[7], up[7], r1));
    v.y = v.y ? v.y : 0x8000u;
    v.w = v.w ? v.w : 0x8000u;
    return v;
}
__device__ __forceinline__ bool frag_stale(const uint4 (&f)[12]) {
    unsigned v = min(f[0].y, f[0].w);
#pragma unroll
    for (int i = 1; i < 12; i++) v = min(v, min(f[i].y, f[i].w));
    return __any_sync(0xffffffffu, v == 0u);
}
__device__ __forceinline__ void st_frag(uint4* p, uint4 v) {
    asm volatile("st.relaxed.gpu.global.v4.u32 [%0], {%1,%2,%3,%4};" ::"l"(p), "r"(v.x), "r"(v.y), "r"(v.z), "r"(v.w) : "memory");
}
__device__ __forceinline__ uint4 ld_frag(const uint4* p) {
    uint4 v;
    asm volatile("ld.relaxed.gpu.global.v4.u32 {%0,%1,%2,%3}, [%4];" : "=r"(v.x), "=r"(v.y), "=r"(v.z), "=r"(v.w) : "l"(p) : "memory");
    return v;
}
__device__ __forceinline__ void red_add2(float* p, float a, float b) {
    asm volatile("red.global.add.v2.f32 [%0], {%1, %2};" ::"l"(p), "f"(a), "f"(b) : "memory");
}
__device__ __forceinline__ void cp_async16(uint32_t dst, const void* src) {
    asm volatile("cp.async.cg.shared.global [%0], [%1], 16;" ::"r"(dst), "l"(src) : "memory");
}

__host__ __device__ constexpr int ring_lap(int u) { return (u * 79) >> 10; }
__host__ __device__ constexpr int ring_slot(int u) { return u - NST * ring_lap(u); }

__device__ __forceinline__ void mainloop128(float (&acc)[64], const uint32_t (&xa)[128], int u0, uint32_t sb,
                                            uint32_t desc128, int lane, int wg, bool last = false) {
    bar_sync(7 + wg, 256);
#pragma unroll
    for (int kb = 0; kb < 8; kb++) {
        const int st = ring_slot(u0 + kb);
        mbar_wait(sb + BAR_FULL + 8 * st, ring_lap(u0 + kb) & 1);
        wg_fence();
        const uint32_t d = desc128 + st * (STAGE_BYTES >> 4);
#pragma unroll
        for (int ks = 0; ks < 4; ks++) wgmma_n128_rs(acc, &xa[(kb * 4 + ks) * 4], d + ks * 128, (kb | ks) != 0);
        wg_commit();
        if (kb == 7 && !(last && wg == 1)) bar_arrive(8 - wg, 256);
        if (kb > 0) {
            wg_wait<1>();
            if (lane < 2) mbar_arrive_cta(sb + BAR_EMPTY + 8 * ring_slot(u0 + kb - 1), lane);
        }
    }
    wg_wait<0>();
    acc_fence(acc);
    if (lane < 2) mbar_arrive_cta(sb + BAR_EMPTY + 8 * ring_slot(u0 + 7), lane);
}
__device__ __forceinline__ void mainloop64x2(float (&a0)[32], float (&a1)[32], const uint32_t (&xa)[128], int u0,
                                             uint32_t sb, uint32_t desc128, int lane, int wg) {
    bar_sync(7 + wg, 256);
#pragma unroll
    for (int kb = 0; kb < 8; kb++) {
        const int st = ring_slot(u0 + kb);
        mbar_wait(sb + BAR_FULL + 8 * st, ring_lap(u0 + kb) & 1);
        wg_fence();
        const uint32_t d = desc128 + st * (STAGE_BYTES >> 4);
        const uint32_t d2 = d + (8192 >> 4) - ((4096u >> 4) << 16);
#pragma unroll
        for (int ks = 0; ks < 4; ks++) {
            wgmma_n64_rs<DHI128>(a0, &xa[(kb * 4 + ks) * 4], d + ks * 128, (kb | ks) != 0);
            wgmma_n64_rs<DHI64>(a1, &xa[(kb * 4 + ks) * 4], d2 + ks * 64, (kb | ks) != 0);
        }
        wg_commit();
        if (kb == 7) bar_arrive(8 - wg, 256);
        if (kb > 0) {
            wg_wait<1>();
            if (lane < 2) mbar_arrive_cta(sb + BAR_EMPTY + 8 * ring_slot(u0 + kb - 1), lane);
        }
    }
    wg_wait<0>();
    acc_fence(a0);
    acc_fence(a1);
    if (lane < 2) mbar_arrive_cta(sb + BAR_EMPTY + 8 * ring_slot(u0 + 7), lane);
}

__global__ void __cluster_dims__(2, 1, 1) __launch_bounds__(384, 1)
fused_kernel(const __grid_constant__ CUtensorMap tm_x, const __grid_constant__ CUtensorMap tm_qkv,
             const __grid_constant__ CUtensorMap tm_w1, const __grid_constant__ CUtensorMap tm_w3,
             const __grid_constant__ CUtensorMap tm_w1h, const __grid_constant__ CUtensorMap tm_w3h,
             const __grid_constant__ CUtensorMap tm_w2, const __grid_constant__ CUtensorMap tm_w2h,
             const __grid_constant__ CUtensorMap tm_wo, const __nv_bfloat16* __restrict__ xg,
             __nv_bfloat16* __restrict__ outg, const char* __restrict__ p_qkv, const char* __restrict__ p_w1,
             const char* __restrict__ p_w3, const char* __restrict__ p_w2, const char* __restrict__ p_wo) {
    extern __shared__ __align__(1024) uint8_t smem[];
    const uint32_t sb = smem_u32(smem);
    const int tid = threadIdx.x;
    const int warp = tid >> 5, lane = tid & 31;
    const int rank = blockIdx.x & 1;
    const int pair = blockIdx.x >> 1;
    const int c = pair & 7;
    const int m = (pair >> 3) * 2 + rank;
    const int m2 = (pair >> 3) * 2 + (c & 1);
    const int j2 = c >> 1;

    TS(tid >> 7, 0);
    if (tid == 256) {
#pragma unroll
        for (int i = 0; i < 8; i++) mbar_init(sb + BAR_XFULL + 8 * i, 1);
        asm volatile("fence.proxy.async.shared::cta;" ::: "memory");
#pragma unroll
        for (int kb = 0; kb < 8; kb++) {
            mbar_expect_tx(sb + BAR_XFULL + 8 * kb, 16384);
            tma_load(sb + (XST0 + kb) * STAGE_BYTES, &tm_x, sb + BAR_XFULL + 8 * kb, kb * 64, m * 128);
        }
        TS(2, 21);
    } else if (tid == 0) {
#pragma unroll
        for (int i = 0; i < NST; i++) mbar_init(sb + BAR_FULL + 8 * i, 1);
        asm volatile("fence.mbarrier_init.release.cluster;" ::: "memory");
    } else if (tid == 32) {
#pragma unroll
        for (int i = 0; i < NST; i++) mbar_init(sb + BAR_EMPTY + 8 * i, 16);
        asm volatile("fence.mbarrier_init.release.cluster;" ::: "memory");
    } else if (tid == 64) {
#pragma unroll
        for (int i = 0; i < 4; i++) mbar_init(sb + BAR_KVREADY + 8 * i, 1);
        mbar_expect_tx(sb + BAR_XCHG, 32768);
        asm volatile("fence.mbarrier_init.release.cluster;" ::: "memory");
    } else if (tid >= 128 && tid < 256) {
        ((uint4*)(smem + OFF_ZERO))[tid - 128] = make_uint4(0, 0, 0, 0);
        ((uint4*)(smem + OFF_ZERO))[tid] = make_uint4(0, 0, 0, 0);
        asm volatile("fence.proxy.async.shared::cta;" ::: "memory");
    } else if (tid == 288) {
        prefetch_tm(&tm_qkv);
        prefetch_tm(rank ? &tm_w3 : &tm_w1);
        prefetch_tm(&tm_w1h);
        prefetch_tm(&tm_w3h);
        prefetch_tm(&tm_w2);
        prefetch_tm(&tm_w2h);
        prefetch_tm(&tm_wo);
    } else if (tid >= 320) {
        ((uint32_t*)(smem + OFF_ONES))[tid - 320] = 0x3F803F80u;
        asm volatile("fence.proxy.async.shared::cta;" ::: "memory");
    }
    __syncthreads();
    TS(tid >> 7, 22);
    asm volatile("barrier.cluster.arrive.relaxed.aligned;\nbarrier.cluster.wait.acquire.aligned;" ::: "memory");

    if (warp >= 8) {
        asm volatile("setmaxnreg.dec.sync.aligned.u32 40;");
        if (warp == 8) {
            if (lane == 0) {
                int st = 0;
                uint32_t lap = 0;
                for (int it = 0; it < 40; it++) {
                    const int tile = it >> 3, kb = it & 7;
                    const uint32_t full = sb + BAR_FULL + 8 * st;
                    mbar_wait(sb + BAR_EMPTY + 8 * st, (st >= XST0) ? (lap & 1) : ((lap & 1) ^ 1));
                    mbar_expect_tx(full, STAGE_BYTES);
                    const uint32_t dst = sb + st * STAGE_BYTES;
                    if (tile == 0) {
                        tma_load_mc(dst + rank * 8192, &tm_qkv, full, 512 + 512 * rank + 64 * c, kb * 64);
                    } else if (tile != 3) {
                        tma_load_mc(dst + rank * 8192, rank ? &tm_w3 : &tm_w1, full, 224 * c + 64 * (tile == 4 ? 2 : tile - 1), kb * 64);
                    } else if (rank == 0) {
                        tma_load_mc(dst, &tm_qkv, full, 64 * c, kb * 64);
                    } else {
                        tma_load_mc(dst + 8192, &tm_w1h, full, 224 * c + 192, kb * 64);
                        tma_load_mc(dst + 12288, &tm_w3h, full, 224 * c + 192, kb * 64);
                    }
                    if (++st == NST) { st = 0; lap++; }
                    if (it == 7) {
                        mbar_wait(sb + BAR_EMPTY + 8 * SCR0, 0);
                        mbar_arrive(sb + BAR_FULL + 8 * SCR0);
                        mbar_wait(sb + BAR_EMPTY + 8 * (SCR0 + 1), 0);
                        mbar_arrive(sb + BAR_FULL + 8 * (SCR0 + 1));
                        st += 2;
                    }
                }
                TS(2, 1);
                mbar_wait(sb + BAR_EPOCH, 0);
                const char* a2b = (const char*)(g_A2 + (size_t)(*(volatile unsigned*)(smem + OFF_EPOCH) & 1) * A2_N +
                                                (size_t)((m2 * 2 + rank) * 18) * 4 * 256);
#pragma unroll 1
                for (int i = 0; i < 18; i++) {
                    const int b = P2_ID[i];
                    if (b < 8) {
                        mbar_wait(sb + BAR_EMPTY + 8 * st, (st >= XST0) ? (lap & 1) : ((lap & 1) ^ 1));
                        mbar_expect_tx(sb + BAR_FULL + 8 * st, STAGE_BYTES);
                        asm volatile("cp.async.bulk.shared::cluster.global.mbarrier::complete_tx::bytes [%0], [%1], 16384, [%2];"
                                     ::"r"(sb + st * STAGE_BYTES), "l"(a2b + b * 16384), "r"(sb + BAR_FULL + 8 * st) : "memory");
                        if (++st == NST) { st = 0; lap++; }
                    }
                    const uint32_t full = sb + BAR_FULL + 8 * st;
                    const uint32_t dst = sb + st * STAGE_BYTES;
                    mbar_wait(sb + BAR_EMPTY + 8 * st, (st >= XST0) ? (lap & 1) : ((lap & 1) ^ 1));
                    mbar_expect_tx(full, STAGE_BYTES);
                    if (b < 8 || b >= 14) {
                        const int row = (b < 8) ? 224 * (4 * rank + (b & 3)) + 64 * (b >> 2) : 224 * (4 * rank + b - 14) + 128;
                        tma_load(dst, &tm_w2, full, 128 * j2, row);
                        tma_load(dst + 8192, &tm_w2, full, 128 * j2 + 64, row);
                    } else if (b < 10) {
                        const int row = 224 * (4 * rank + 2 * (b - 8)) + 192;
                        tma_load(dst, &tm_w2h, full, 128 * j2, row);
                        tma_load(dst + 4096, &tm_w2h, full, 128 * j2, row + 224);
                        tma_load(dst + 8192, &tm_w2h, full, 128 * j2 + 64, row);
                        tma_load(dst + 12288, &tm_w2h, full, 128 * j2 + 64, row + 224);
                    } else {
                        const int row = 64 * (4 * rank + (b - 10));
                        tma_load(dst, &tm_wo, full, 128 * j2, row);
                        tma_load(dst + 8192, &tm_wo, full, 128 * j2 + 64, row);
                    }
                    TS(2, 2 + i);
                    if (++st == NST) { st = 0; lap++; }
                }
                mbar_wait(sb + BAR_EMPTY + 8 * XCH0, (lap & 1) ^ 1);
                mbar_wait(sb + BAR_EMPTY + 8 * (XCH0 + 1), (lap & 1) ^ 1);
                mbar_arrive_cta(sb + BAR_XRDY, rank ^ 1);
            }
        } else if (warp < 11) {
            const int wg = warp - 9;
            bar_sync(3 + wg, 160);
            if (lane == 0) asm volatile("red.release.gpu.global.add.u32 [%0], 1;" ::"l"(&g_kvcnt[c]) : "memory");
            TSW(3, wg);
        } else {
            const unsigned epoch = read_epoch();
            if (lane == 0) {
                const unsigned tk = atomicInc(&g_ticket, 127u);
                if (tk == 127u) *(volatile unsigned*)&g_epoch = epoch;
            }
            if (lane == 0) *(volatile unsigned*)(smem + OFF_EPOCH) = epoch;
            __syncwarp();
            if (lane == 0) mbar_arrive(sb + BAR_EPOCH);
            if (lane < 17) g_kvacc[(((epoch & 1) ^ 1) * 8 + c) * 272 + 17 * m + lane] = make_float4(0.f, 0.f, 0.f, 0.f);
            {
                unsigned n = 0;
                while ((int)(ld_acquire(&g_kvcnt[c]) - 32u * epoch) < 0) {
                    __nanosleep(200);
                    if (++n > SPIN_LIMIT) asm volatile("trap;");
                }
            }
            TSW(4, 0);
            const int g = lane >> 2, t = lane & 3;
            const float* ks = (const float*)(g_kvacc + ((epoch & 1) * 8 + c) * 272) + 32 * t + g;
            uint2* kf = (uint2*)(smem + OFF_KVFRAG) + lane;
#pragma unroll 2
            for (int hh = 0; hh < 4; hh++) {
                const float* k = ks + hh * 272;
                const float a0 = __ldcg(k), a1 = __ldcg(k + 16), a2 = __ldcg(k + 128), a3 = __ldcg(k + 144);
                const float b0 = __ldcg(k + 8), b1 = __ldcg(k + 24), b2 = __ldcg(k + 136), b3 = __ldcg(k + 152);
                const float2 z0 = __ldcg((const float2*)(k - g - 30 * t + 256)), z1 = __ldcg((const float2*)(k - g - 30 * t + 264));
                kf[(hh * 3 + 0) * 32] = make_uint2(pack_bf16(a0, a1), pack_bf16(a2, a3));
                kf[(hh * 3 + 1) * 32] = make_uint2(pack_bf16(b0, b1), pack_bf16(b2, b3));
                kf[(hh * 3 + 2) * 32] = make_uint2(pack_bf16(z0.x, z0.y), pack_bf16(z1.x, z1.y));
            }
            __syncwarp();
            if (lane == 0) mbar_arrive(sb + BAR_KVREADY);
            TSW(4, 4);
            if (lane == 0) {
                char* z = (char*)(g_A2 + (size_t)((epoch & 1) ^ 1) * A2_N + (size_t)((m * 2 + (c >> 2)) * 18) * 4 * 256);
                const int cc = c & 3;
#pragma unroll 1
                for (int i = 0; i < 18; i++) {
                    const int blk = (i < 8) ? ((i >> 2) * 4 + cc) * 4 + (i & 3)
                                  : (i < 10) ? (8 + (cc >> 1)) * 4 + 2 * (cc & 1) + (i - 8)
                                  : (i < 14) ? (10 + cc) * 4 + (i - 10) : (14 + cc) * 4 + (i - 14);
                    asm volatile("cp.async.bulk.global.shared::cta.bulk_group [%0], [%1], 4096;"
                                 ::"l"(z + (size_t)blk * 4096), "r"(sb + OFF_ZERO) : "memory");
                }
                asm volatile("cp.async.bulk.commit_group;" ::: "memory");
            }
            if (lane == 0) asm volatile("cp.async.bulk.wait_group 0;" ::: "memory");
        }
    } else {
        asm volatile("setmaxnreg.inc.sync.aligned.u32 232;");
        const int wg = warp >> 2, w = warp & 3;
        const int g = lane >> 2, t = lane & 3;
        float acc[64];
        uint32_t xa[128];
        float rho0, rho1;
        RowScale r0, r1;
        unsigned par;

        TS(wg, 1);
        {
            const int row = wg * 64 + w * 16 + (lane & 7) + ((lane >> 3) & 1) * 8;
            const uint32_t rbase = sb + XST0 * STAGE_BYTES + row * 128;
            const int hi = lane >> 4, r7 = lane & 7;
            float sm[2][4], c0[2][4], c1[2][4];
#pragma unroll
            for (int i = 0; i < 8; i++) { sm[i >> 2][i & 3] = 0.f; c0[i >> 2][i & 3] = 0.f; c1[i >> 2][i & 3] = 0.f; }
            if (wg == 1) bar_arrive(7, 256);
#pragma unroll
            for (int kb = 0; kb < 8; kb++) {
                mbar_wait(sb + BAR_XFULL + 8 * kb, 0);
#pragma unroll
                for (int ks = 0; ks < 4; ks++) {
                    uint32_t* a = &xa[(kb * 4 + ks) * 4];
                    const uint32_t addr = rbase + kb * STAGE_BYTES + (((2 * ks + hi) ^ r7) << 4);
                    asm volatile("ldmatrix.sync.aligned.m8n8.x4.shared.b16 {%0,%1,%2,%3}, [%4];"
                                 : "=r"(a[0]), "=r"(a[1]), "=r"(a[2]), "=r"(a[3]) : "r"(addr) : "memory");
                    mma16816(sm[ks & 1], a, 0x3F803F80u, 0x3F803F80u);
                    mma16816(c0[ks & 1], a, a[0], a[2]);
                    mma16816(c1[ks & 1], a, a[1], a[3]);
                }
            }
            TS(wg, 2);
            const float mean0 = (sm[0][0] + sm[1][0]) * (1.f / 512.f);
            const float mean1 = (sm[0][2] + sm[1][2]) * (1.f / 512.f);
            __syncwarp();
            if (lane < 16) mbar_arrive_cta(sb + BAR_EMPTY + 8 * (XST0 + (lane >> 1)), lane & 1);
            const __nv_bfloat162 mb0 = __float2bfloat162_rn(mean0), mb1 = __float2bfloat162_rn(mean1);
#pragma unroll
            for (int i = 0; i < 128; i++) {
                __nv_bfloat162 v = *reinterpret_cast<__nv_bfloat162*>(&xa[i]);
                v = __hsub2(v, (i & 1) ? mb1 : mb0);
                xa[i] = *reinterpret_cast<uint32_t*>(&v);
            }
            const float d0 = (g & 1) ? c0[0][1] + c0[1][1] : c0[0][0] + c0[1][0];
            const float d1 = (g & 1) ? c1[0][3] + c1[1][3] : c1[0][2] + c1[1][2];
            const int src = (lane & ~3) | (g >> 1);
            const float var0 = fmaxf(__shfl_sync(0xffffffffu, d0, src) * (1.f / 512.f) - mean0 * mean0, 0.f);
            const float var1 = fmaxf(__shfl_sync(0xffffffffu, d1, src) * (1.f / 512.f) - mean1 * mean1, 0.f);
            const float sd0 = bf16_round(sqrt_fast(bf16_round(bf16_round(var0) + 1e-5f)));
            const float sd1 = bf16_round(sqrt_fast(bf16_round(bf16_round(var1) + 1e-5f)));
            rho0 = rcp_fast(sd0);
            rho1 = rcp_fast(sd1);
            r0.rho = rho0; r0.rl = rho0 * 1.4426950408889634f; r0.var = sd0 * sd0;
            r1.rho = rho1; r1.rl = rho1 * 1.4426950408889634f; r1.var = sd1 * sd1;
        }

        TS(wg, 3);
        const uint32_t desc128 = ((sb & 0x3FFFF) >> 4) | ((8192u >> 4) << 16);
        const int cc = c & 3;

        {
            mainloop128(acc, xa, 0, sb, desc128, lane, wg);
            TS(wg, 4);
            {
                TS(wg, 24);
                const uint32_t pkb = sb + (SCR0 + wg) * STAGE_BYTES;
                mbar_wait(sb + BAR_FULL + 8 * (SCR0 + wg), 0);
                const uint32_t ra = pkb + (w * 16 + g) * 128 + t * 4;
#pragma unroll
                for (int nb = 0; nb < 8; nb++) {
                    const uint32_t off = (uint32_t)((nb ^ g) << 4);
                    uint32_t p0 = pack_bf16(phi_f(acc[nb * 4], r0), phi_f(acc[nb * 4 + 1], r0));
                    uint32_t p1 = pack_bf16(phi_f(acc[nb * 4 + 2], r1), phi_f(acc[nb * 4 + 3], r1));
                    uint32_t v0 = pack_bf16(acc[32 + nb * 4] * rho0, acc[32 + nb * 4 + 1] * rho0);
                    uint32_t v1 = pack_bf16(acc[32 + nb * 4 + 2] * rho1, acc[32 + nb * 4 + 3] * rho1);
                    asm volatile("st.shared.u32 [%0], %1;" ::"r"(ra + off), "r"(p0) : "memory");
                    asm volatile("st.shared.u32 [%0], %1;" ::"r"(ra + off + 1024), "r"(p1) : "memory");
                    asm volatile("st.shared.u32 [%0], %1;" ::"r"(ra + off + 8192), "r"(v0) : "memory");
                    asm volatile("st.shared.u32 [%0], %1;" ::"r"(ra + off + 8192 + 1024), "r"(v1) : "memory");
                }
                TS(wg, 25);
                asm volatile("fence.proxy.async.shared::cta;" ::: "memory");
                bar_sync(1 + wg, 128);
                TS(wg, 26);
                const uint64_t da = make_desc(pkb, 8192, 1024, 1);
                const uint64_t db = make_desc(pkb + 8192, 8192, 1024, 1);
                const uint64_t d1 = make_desc(sb + OFF_ONES, 128, 128, 0);
                float kva[32], za[4];
                wg_fence();
#pragma unroll
                for (int ks = 0; ks < 4; ks++) {
                    wgmma_n64_ss_tt(kva, da + ks * 128, db + ks * 128, ks != 0);
                    wgmma_n8_ss_tn(za, da + ks * 128, d1, ks != 0);
                }
                wg_commit();
                wg_wait<0>();
                acc_fence(kva);
                acc_fence(za);
                if (lane < 4) mbar_arrive_cta(sb + BAR_EMPTY + 8 * (SCR0 + (lane >> 1)), lane & 1);
                TS(wg, 27);
                float o[8];
#pragma unroll
                for (int i = 0; i < 8; i++)
                    o[i] = (w == 0) ? kva[i] : (w == 1) ? kva[8 + i] : (w == 2) ? kva[16 + i] : kva[24 + i];
                mbar_wait(sb + BAR_EPOCH, 0);
                par = *(volatile unsigned*)(smem + OFF_EPOCH) & 1;
                float* dst = (float*)(g_kvacc + (par * 8 + c) * 272) + w * 272 + g * 16 + 2 * t;
                red_add2(dst, o[0], o[1]);
                red_add2(dst + 128, o[2], o[3]);
                red_add2(dst + 8, o[4], o[5]);
                red_add2(dst + 136, o[6], o[7]);
                if (t == 0) {
                    atomicAdd(dst - g * 15 + 256, za[0]);
                    atomicAdd(dst - g * 15 + 264, za[2]);
                }
            }
            bar_arrive(3 + wg, 160);
            TS(wg, 5);
        }
        uint4* a2w = g_A2 + (size_t)par * A2_N + (size_t)((m * 2 + (c >> 2)) * 18) * 4 * 256 + warp * 32 + lane;
#pragma unroll
        for (int tile = 1; tile < 3; tile++) {
            mainloop128(acc, xa, 2 + 8 * tile, sb, desc128, lane, wg);
            TS(wg, 4 + 2 * tile);
            uint4* dst = a2w + (size_t)((4 * (tile - 1) + cc) * 4) * 256;
#pragma unroll
            for (int ks = 0; ks < 4; ks++) st_frag(dst + ks * 256, swiglu8(&acc[ks * 8], &acc[32 + ks * 8], r0, r1));
            TS(wg, 5 + 2 * tile);
        }
        {
            float qa[32], gu[32];
            mainloop64x2(qa, gu, xa, 26, sb, desc128, lane, wg);
            TS(wg, 10);
            uint4* dst = a2w + (size_t)((8 + (cc >> 1)) * 4 + 2 * (cc & 1)) * 256;
#pragma unroll
            for (int ks = 0; ks < 2; ks++) st_frag(dst + ks * 256, swiglu8(&gu[ks * 8], &gu[16 + ks * 8], r0, r1));
            TS(wg, 13);
            mbar_wait(sb + BAR_KVREADY, 0);
            TS(wg, 14);
            const uint2* kf = (const uint2*)(smem + OFF_KVFRAG);
            dst = a2w + (size_t)((10 + cc) * 4) * 256;
#pragma unroll
            for (int hh = 0; hh < 4; hh++) {
                const float* q = &qa[hh * 8];
                uint32_t a[4];
                a[0] = pack_bf16(phi_f(q[0], r0), phi_f(q[1], r0));
                a[1] = pack_bf16(phi_f(q[2], r1), phi_f(q[3], r1));
                a[2] = pack_bf16(phi_f(q[4], r0), phi_f(q[5], r0));
                a[3] = pack_bf16(phi_f(q[6], r1), phi_f(q[7], r1));
                float n0[4] = {0.f, 0.f, 0.f, 0.f}, n1[4] = {0.f, 0.f, 0.f, 0.f}, dn[4] = {0.f, 0.f, 0.f, 0.f};
                const uint2 b0 = kf[(hh * 3 + 0) * 32 + lane], b1 = kf[(hh * 3 + 1) * 32 + lane],
                            bz = kf[(hh * 3 + 2) * 32 + lane];
                mma16816(n0, a, b0.x, b0.y);
                mma16816(n1, a, b1.x, b1.y);
                mma16816(dn, a, bz.x, bz.y);
                const float i0 = rcp_fast(dn[0] + 1e-6f), i1 = rcp_fast(dn[2] + 1e-6f);
                uint4 v;
                v.x = pack_bf16(n0[0] * i0, n0[1] * i0);
                v.y = pack_bf16(n0[2] * i1, n0[3] * i1);
                v.z = pack_bf16(n1[0] * i0, n1[1] * i0);
                v.w = pack_bf16(n1[2] * i1, n1[3] * i1);
                v.y = v.y ? v.y : 0x8000u;
                v.w = v.w ? v.w : 0x8000u;
                st_frag(dst + hh * 256, v);
            }
            TS(wg, 11);
        }
        const uint4* a2r = g_A2 + (size_t)par * A2_N + (size_t)((m2 * 2 + rank) * 18) * 4 * 256 + warp * 32 + lane;
        uint4 af[2][12];
        {
            mainloop128(acc, xa, 34, sb, desc128, lane, wg);
            TS(wg, 12);
            uint4* dst = a2w + (size_t)((14 + cc) * 4) * 256;
#pragma unroll
            for (int ks = 0; ks < 4; ks++) st_frag(dst + ks * 256, swiglu8(&acc[ks * 8], &acc[32 + ks * 8], r0, r1));
            TS(wg, 15);
        }

        {
            float ao[32], ap[32];
            const uint32_t dso = desc128 + rank * 512, dsp = desc128 + (rank ^ 1) * 512;
            TS(wg, 16);
#pragma unroll
            for (int gi = 0; gi < 6; gi++) {
                if (gi == 5) TS(wg, 17);
                uint4(&f)[12] = af[gi & 1];
#pragma unroll
                for (int bb = 0; bb < 3; bb++) {
                    const int ub = p2_useB(gi * 3 + bb);
                    if (p2_id(gi * 3 + bb) < 8) {
                        mbar_wait(sb + BAR_FULL + 8 * ring_slot(ub - 1), ring_lap(ub - 1) & 1);
                        const uint4* src = (const uint4*)(smem + ring_slot(ub - 1) * STAGE_BYTES) + tid;
#pragma unroll
                        for (int ks = 0; ks < 4; ks++) f[bb * 4 + ks] = src[ks * 256];
                    }
                    mbar_wait(sb + BAR_FULL + 8 * ring_slot(ub), ring_lap(ub) & 1);
                }
                {
                    unsigned n = 0;
                    while (frag_stale(f)) {
#pragma unroll
                        for (int i = 0; i < 12; i++) f[i] = ld_frag(a2r + (p2_id(gi * 3 + (i >> 2)) * 4 + (i & 3)) * 256);
                        if (++n > SPIN_LIMIT) asm volatile("trap;");
                    }
                }
                bar_sync(7 + wg, 256);
                wg_fence();
#pragma unroll
                for (int i = 0; i < 12; i++) {
                    const uint32_t so = ring_slot(p2_useB(gi * 3 + (i >> 2))) * (STAGE_BYTES >> 4) + (i & 3) * 128;
                    const uint32_t* a = reinterpret_cast<const uint32_t*>(&f[i]);
                    wgmma_n64_rs<DHI128>(ap, a, dsp + so, (gi | i) != 0);
                    if (gi < 5) wgmma_n64_rs<DHI128>(ao, a, dso + so, (gi | i) != 0);
                }
                wg_commit();
                bar_arrive(8 - wg, 256);
                if (gi < 5) {
#pragma unroll
                    for (int i = 0; i < 12; i++)
                        if (p2_id(gi * 3 + 3 + (i >> 2)) >= 8)
                            af[(gi + 1) & 1][i] = ld_frag(a2r + (p2_id(gi * 3 + 3 + (i >> 2)) * 4 + (i & 3)) * 256);
                    wg_wait<0>();
                    if (gi < 3 && lane < 12 - 2 * gi)
                        mbar_arrive(sb + BAR_EMPTY + 8 * ring_slot((gi == 0 ? 42 : gi == 1 ? 48 : 53) + (lane >> 1)));
                }
            }
            const int row0 = m2 * 128 + wg * 64 + w * 16 + g;
            const int col0 = j2 * 128 + rank * 64 + 2 * t;
            uint32_t xr[16];
#pragma unroll
            for (int nb = 0; nb < 8; nb++) {
                xr[2 * nb] = __ldg((const uint32_t*)(xg + (size_t)row0 * 512 + col0 + nb * 8));
                xr[2 * nb + 1] = __ldg((const uint32_t*)(xg + (size_t)(row0 + 8) * 512 + col0 + nb * 8));
            }
            uint32_t rdst, rbar;
            asm volatile("mapa.shared::cluster.u32 %0, %1, %2;"
                         : "=r"(rdst) : "r"(sb + (XCH0 + wg) * STAGE_BYTES + (tid & 127) * 16), "r"(rank ^ 1));
            asm volatile("mapa.shared::cluster.u32 %0, %1, %2;" : "=r"(rbar) : "r"(sb + BAR_XCHG), "r"(rank ^ 1));
            mbar_wait(sb + BAR_XRDY, 0);
            wg_wait<0>();
            acc_fence(ap);
            TS(wg, 18);
#pragma unroll
            for (int i = 0; i < 8; i++)
                asm volatile("st.async.shared::cluster.mbarrier::complete_tx::bytes.v4.f32 [%0], {%1,%2,%3,%4}, [%5];"
                             ::"r"(rdst + i * 2048), "f"(ap[4 * i]), "f"(ap[4 * i + 1]), "f"(ap[4 * i + 2]), "f"(ap[4 * i + 3]),
                             "r"(rbar) : "memory");
            bar_sync(7 + wg, 256);
            wg_fence();
#pragma unroll
            for (int i = 0; i < 12; i++)
                wgmma_n64_rs<DHI128>(ao, reinterpret_cast<const uint32_t*>(&af[1][i]),
                                     dso + ring_slot(65 + (i >> 2)) * (STAGE_BYTES >> 4) + (i & 3) * 128, 1);
            wg_commit();
            if (wg == 0) bar_arrive(8, 256);
            wg_wait<0>();
            acc_fence(ao);
            mbar_wait(sb + BAR_XCHG, 0);
            TS(wg, 19);
            const float4* rx = (const float4*)(smem + (XCH0 + wg) * STAGE_BYTES) + (tid & 127);
#pragma unroll
            for (int nb = 0; nb < 8; nb++) {
                const float4 p = rx[nb * 128];
                const uint32_t o0 = pack_bf16(ao[4 * nb] + p.x + bf_lo(xr[2 * nb]), ao[4 * nb + 1] + p.y + bf_hi(xr[2 * nb]));
                const uint32_t o1 = pack_bf16(ao[4 * nb + 2] + p.z + bf_lo(xr[2 * nb + 1]), ao[4 * nb + 3] + p.w + bf_hi(xr[2 * nb + 1]));
                *(uint32_t*)(outg + (size_t)row0 * 512 + col0 + nb * 8) = o0;
                *(uint32_t*)(outg + (size_t)(row0 + 8) * 512 + col0 + nb * 8) = o1;
            }
        }
        TS(wg, 20);
    }
}

typedef CUresult (*EncodeFn)(CUtensorMap*, CUtensorMapDataType, cuuint32_t, void*, const cuuint64_t*, const cuuint64_t*,
                             const cuuint32_t*, const cuuint32_t*, CUtensorMapInterleave, CUtensorMapSwizzle,
                             CUtensorMapL2promotion, CUtensorMapFloatOOBfill);

void make_map(EncodeFn enc, CUtensorMap* tm, const void* ptr, int rows, int cols, int box_rows, int box_cols,
              CUtensorMapSwizzle swz) {
    cuuint64_t dims[2] = {(cuuint64_t)cols, (cuuint64_t)rows};
    cuuint64_t strides[1] = {(cuuint64_t)cols * 2};
    cuuint32_t box[2] = {(cuuint32_t)box_cols, (cuuint32_t)box_rows};
    cuuint32_t es[2] = {1, 1};
    enc(tm, CU_TENSOR_MAP_DATA_TYPE_BFLOAT16, 2, const_cast<void*>(ptr), dims, strides, box, es,
        CU_TENSOR_MAP_INTERLEAVE_NONE, swz, CU_TENSOR_MAP_L2_PROMOTION_L2_256B, CU_TENSOR_MAP_FLOAT_OOB_FILL_NONE);
}

}

extern "C" void kernel_launch(void* const* d_in, const int* in_sizes, int n_in, void* d_out, int out_size) {
    (void)in_sizes; (void)n_in; (void)out_size;
    static EncodeFn enc = nullptr;
    if (!enc) {
        void* fn = nullptr;
        cudaDriverEntryPointQueryResult qr;
        cudaGetDriverEntryPoint("cuTensorMapEncodeTiled", &fn, cudaEnableDefault, &qr);
        enc = (EncodeFn)fn;
        cudaFuncSetAttribute(fused_kernel, cudaFuncAttributeMaxDynamicSharedMemorySize, SMEM_BYTES);
    }
    const void* x = d_in[0];
    const void* wqkv = d_in[1];
    const void* wo = d_in[2];
    const void* w1 = d_in[4];
    const void* w3 = d_in[5];
    const void* w2 = d_in[6];
    CUtensorMap tx, tqkv, t1, t3, t1h, t3h, t2, t2h, two;
    make_map(enc, &tx, x, 2048, 512, 128, 64, CU_TENSOR_MAP_SWIZZLE_128B);
    make_map(enc, &tqkv, wqkv, 512, 1536, 64, 64, CU_TENSOR_MAP_SWIZZLE_128B);
    make_map(enc, &t1, w1, 512, 1792, 64, 64, CU_TENSOR_MAP_SWIZZLE_128B);
    make_map(enc, &t3, w3, 512, 1792, 64, 64, CU_TENSOR_MAP_SWIZZLE_128B);
    make_map(enc, &t1h, w1, 512, 1792, 64, 32, CU_TENSOR_MAP_SWIZZLE_64B);
    make_map(enc, &t3h, w3, 512, 1792, 64, 32, CU_TENSOR_MAP_SWIZZLE_64B);
    make_map(enc, &t2, w2, 1792, 512, 64, 64, CU_TENSOR_MAP_SWIZZLE_128B);
    make_map(enc, &t2h, w2, 1792, 512, 32, 64, CU_TENSOR_MAP_SWIZZLE_128B);
    make_map(enc, &two, wo, 512, 512, 64, 64, CU_TENSOR_MAP_SWIZZLE_128B);
    fused_kernel<<<128, 384, SMEM_BYTES>>>(tx, tqkv, t1, t3, t1h, t3h, t2, t2h, two, (const __nv_bfloat16*)x,
                                           (__nv_bfloat16*)d_out, (const char*)wqkv, (const char*)w1, (const char*)w3,
                                           (const char*)w2, (const char*)wo);
}
```

```cpp
#include <cuda_runtime.h>
#include <cuda_bf16.h>
#include <cuda.h>
#include <stdint.h>

namespace {

constexpr int NST = 13;
constexpr int STAGE_BYTES = 16384;
constexpr int XST0 = 5;
constexpr int SCR0 = 8;
__host__ __device__ constexpr int p2_id(int i) {
    constexpr int t[18] = {0, 1, 2, 3, 8, 4, 5, 9, 10, 6, 11, 12, 7, 13, 14, 15, 16, 17};
    return t[i];
}
__host__ __device__ constexpr int p2_useB(int i) {
    constexpr int t[18] = {43, 45, 47, 49, 50, 52, 54, 55, 56, 58, 59, 60, 62, 63, 64, 65, 66, 67};
    return t[i];
}
constexpr int OFF_MISC = NST * STAGE_BYTES;
constexpr int OFF_KVFRAG = OFF_MISC;
constexpr int OFF_ONES = OFF_MISC + 3072;
constexpr int OFF_BARS = OFF_MISC + 3328;
constexpr int BAR_FULL = OFF_BARS;
constexpr int BAR_EMPTY = BAR_FULL + 8 * NST;
constexpr int BAR_XFULL = BAR_EMPTY + 8 * NST;
constexpr int BAR_KVREADY = BAR_XFULL + 64;
constexpr int BAR_XCHG = BAR_KVREADY + 8;
constexpr int BAR_EPOCH = BAR_XCHG + 8;
constexpr int BAR_XRDY = BAR_EPOCH + 8;
constexpr int OFF_EPOCH = BAR_XRDY + 8;
constexpr int OFF_ZERO = OFF_MISC + 4096;
constexpr int SMEM_BYTES = OFF_MISC + 8192;

constexpr unsigned SPIN_LIMIT = 1u << 24;

constexpr int A2_N = 16 * 2 * 18 * 4 * 256;
__device__ uint4 g_A2[2 * A2_N];
__device__ uint4 g_xch[2 * 128 * 2048];
__device__ float4 g_kvacc[2 * 8 * 272];
__device__ unsigned g_kvcnt[8];
__constant__ unsigned char P2_ID[18] = {0, 1, 2, 3, 8, 4, 5, 9, 10, 6, 11, 12, 7, 13, 14, 15, 16, 17};
__device__ unsigned g_epoch;
__device__ unsigned g_ticket;

#define TS(role, i)
#define TSW(role, i)

__device__ __forceinline__ uint32_t smem_u32(const void* p) { return (uint32_t)__cvta_generic_to_shared(p); }
__device__ __forceinline__ void mbar_init(uint32_t bar, uint32_t cnt) {
    asm volatile("mbarrier.init.shared::cta.b64 [%0], %1;" ::"r"(bar), "r"(cnt) : "memory");
}
__device__ __forceinline__ void mbar_expect_tx(uint32_t bar, uint32_t bytes) {
    asm volatile("mbarrier.arrive.expect_tx.shared::cta.b64 _, [%0], %1;" ::"r"(bar), "r"(bytes) : "memory");
}
__device__ __forceinline__ void mbar_arrive(uint32_t bar) {
    asm volatile("mbarrier.arrive.shared::cta.b64 _, [%0];" ::"r"(bar) : "memory");
}
__device__ __forceinline__ void mbar_arrive_cta(uint32_t bar, uint32_t cta) {
    asm volatile(
        "{\n.reg .b32 ra;\nmapa.shared::cluster.u32 ra, %0, %1;\n"
        "mbarrier.arrive.shared::cluster.b64 _, [ra];\n}" ::"r"(bar), "r"(cta) : "memory");
}
__device__ __forceinline__ void mbar_wait(uint32_t bar, uint32_t parity) {
    asm volatile(
        "{\n.reg .pred p, q;\n.reg .u32 n;\nmov.u32 n, 0;\n"
        "WAIT_%=:\n"
        "mbarrier.try_wait.parity.shared::cta.b64 p, [%0], %1;\n"
        "@p bra.uni DONE_%=;\n"
        "add.u32 n, n, 1;\n"
        "setp.gt.u32 q, n, %2;\n"
        "@q trap;\n"
        "bra.uni WAIT_%=;\n"
        "DONE_%=:\n}"
        ::"r"(bar), "r"(parity), "n"(SPIN_LIMIT) : "memory");
}
__device__ __forceinline__ unsigned ld_acquire(const unsigned* p) {
    unsigned v;
    asm volatile("ld.acquire.gpu.global.u32 %0, [%1];" : "=r"(v) : "l"(p) : "memory");
    return v;
}
__device__ __forceinline__ void st_release(unsigned* p, unsigned v) {
    asm volatile("st.release.gpu.global.u32 [%0], %1;" ::"l"(p), "r"(v) : "memory");
}
__device__ __forceinline__ unsigned read_epoch() {
    return __shfl_sync(0xffffffffu, *(volatile unsigned*)&g_epoch, 0) + 1;
}
__device__ __forceinline__ void tma_load(uint32_t dst, const CUtensorMap* tm, uint32_t bar, int x, int y) {
    asm volatile(
        "cp.async.bulk.tensor.2d.shared::cluster.global.mbarrier::complete_tx::bytes [%0], [%1, {%3, %4}], [%2];"
        ::"r"(dst), "l"(tm), "r"(bar), "r"(x), "r"(y) : "memory");
}
__device__ __forceinline__ void tma_load_mc(uint32_t dst, const CUtensorMap* tm, uint32_t bar, int x, int y) {
    asm volatile(
        "cp.async.bulk.tensor.2d.shared::cluster.global.mbarrier::complete_tx::bytes.multicast::cluster "
        "[%0], [%1, {%3, %4}], [%2], %5;"
        ::"r"(dst), "l"(tm), "r"(bar), "r"(x), "r"(y), "h"((uint16_t)3) : "memory");
}
__device__ __forceinline__ void prefetch_tm(const CUtensorMap* tm) {
    asm volatile("prefetch.tensormap [%0];" ::"l"(tm) : "memory");
}
__device__ __forceinline__ void l2_prefetch(const void* p, uint32_t bytes) {
    asm volatile("cp.async.bulk.prefetch.L2.global [%0], %1;" ::"l"(p), "r"(bytes) : "memory");
}
__device__ __forceinline__ void bar_sync(int id, int n) { asm volatile("bar.sync %0, %1;" ::"r"(id), "r"(n) : "memory"); }
__device__ __forceinline__ void bar_arrive(int id, int n) { asm volatile("bar.arrive %0, %1;" ::"r"(id), "r"(n) : "memory"); }
__device__ __forceinline__ void wg_fence() { asm volatile("wgmma.fence.sync.aligned;" ::: "memory"); }
__device__ __forceinline__ void wg_commit() { asm volatile("wgmma.commit_group.sync.aligned;" ::: "memory"); }
template <int N>
__device__ __forceinline__ void wg_wait() { asm volatile("wgmma.wait_group.sync.aligned %0;" ::"n"(N) : "memory"); }

__device__ __forceinline__ uint64_t make_desc(uint32_t addr, uint32_t lbo, uint32_t sbo, uint64_t swz) {
    return (uint64_t)((addr & 0x3FFFF) >> 4) | ((uint64_t)(lbo >> 4) << 16) | ((uint64_t)(sbo >> 4) << 32) | (swz << 62);
}

#define ACC8(a, o) "+f"(a[o]), "+f"(a[o + 1]), "+f"(a[o + 2]), "+f"(a[o + 3]), "+f"(a[o + 4]), "+f"(a[o + 5]), "+f"(a[o + 6]), "+f"(a[o + 7])
constexpr uint32_t DHI128 = (1024u >> 4) | (1u << 30);
constexpr uint32_t DHI64 = (512u >> 4) | (2u << 30);
__device__ __forceinline__ void wgmma_n128_rs(float (&d)[64], const uint32_t* a, uint32_t db, int scale_d) {
    asm volatile(
        "{\n.reg .pred p;\n.reg .b64 dd;\nsetp.ne.b32 p, %69, 0;\nmov.b64 dd, {%68, %70};\n"
        "wgmma.mma_async.sync.aligned.m64n128k16.f32.bf16.bf16 "
        "{%0,%1,%2,%3,%4,%5,%6,%7,%8,%9,%10,%11,%12,%13,%14,%15,%16,%17,%18,%19,%20,%21,%22,%23,%24,%25,%26,%27,%28,%29,%30,%31,"
        "%32,%33,%34,%35,%36,%37,%38,%39,%40,%41,%42,%43,%44,%45,%46,%47,%48,%49,%50,%51,%52,%53,%54,%55,%56,%57,%58,%59,%60,%61,%62,%63},"
        "{%64,%65,%66,%67}, dd, p, 1, 1, 1;\n}"
        : ACC8(d, 0), ACC8(d, 8), ACC8(d, 16), ACC8(d, 24), ACC8(d, 32), ACC8(d, 40), ACC8(d, 48), ACC8(d, 56)
        : "r"(a[0]), "r"(a[1]), "r"(a[2]), "r"(a[3]), "r"(db), "r"(scale_d), "n"(DHI128));
}
template <uint32_t HI>
__device__ __forceinline__ void wgmma_n64_rs(float (&d)[32], const uint32_t* a, uint32_t db, int scale_d) {
    asm volatile(
        "{\n.reg .pred p;\n.reg .b64 dd;\nsetp.ne.b32 p, %37, 0;\nmov.b64 dd, {%36, %38};\n"
        "wgmma.mma_async.sync.aligned.m64n64k16.f32.bf16.bf16 "
        "{%0,%1,%2,%3,%4,%5,%6,%7,%8,%9,%10,%11,%12,%13,%14,%15,%16,%17,%18,%19,%20,%21,%22,%23,%24,%25,%26,%27,%28,%29,%30,%31},"
        "{%32,%33,%34,%35}, dd, p, 1, 1, 1;\n}"
        : ACC8(d, 0), ACC8(d, 8), ACC8(d, 16), ACC8(d, 24)
        : "r"(a[0]), "r"(a[1]), "r"(a[2]), "r"(a[3]), "r"(db), "r"(scale_d), "n"(HI));
}
__device__ __forceinline__ void wgmma_n64_ss_tt(float (&d)[32], uint64_t da, uint64_t db, int scale_d) {
    asm volatile(
        "{\n.reg .pred p;\nsetp.ne.b32 p, %34, 0;\n"
        "wgmma.mma_async.sync.aligned.m64n64k16.f32.bf16.bf16 "
        "{%0,%1,%2,%3,%4,%5,%6,%7,%8,%9,%10,%11,%12,%13,%14,%15,%16,%17,%18,%19,%20,%21,%22,%23,%24,%25,%26,%27,%28,%29,%30,%31},"
        "%32, %33, p, 1, 1, 1, 1;\n}"
        : ACC8(d, 0), ACC8(d, 8), ACC8(d, 16), ACC8(d, 24)
        : "l"(da), "l"(db), "r"(scale_d));
}
__device__ __forceinline__ void wgmma_n8_ss_tn(float (&d)[4], uint64_t da, uint64_t db, int scale_d) {
    asm volatile(
        "{\n.reg .pred p;\nsetp.ne.b32 p, %6, 0;\n"
        "wgmma.mma_async.sync.aligned.m64n8k16.f32.bf16.bf16 {%0,%1,%2,%3}, %4, %5, p, 1, 1, 1, 0;\n}"
        : "+f"(d[0]), "+f"(d[1]), "+f"(d[2]), "+f"(d[3])
        : "l"(da), "l"(db), "r"(scale_d));
}
template <int N>
__device__ __forceinline__ void acc_fence(float (&d)[N]) {
#pragma unroll
    for (int i = 0; i < N; i++) asm volatile("" : "+f"(d[i])::"memory");
}
__device__ __forceinline__ void mma16816(float (&c)[4], const uint32_t* a, uint32_t b0, uint32_t b1) {
    asm volatile(
        "mma.sync.aligned.m16n8k16.row.col.f32.bf16.bf16.f32 {%0,%1,%2,%3}, {%4,%5,%6,%7}, {%8,%9}, {%0,%1,%2,%3};"
        : "+f"(c[0]), "+f"(c[1]), "+f"(c[2]), "+f"(c[3])
        : "r"(a[0]), "r"(a[1]), "r"(a[2]), "r"(a[3]), "r"(b0), "r"(b1));
}
__device__ __forceinline__ uint32_t pack_bf16(float lo, float hi) {
    uint32_t r;
    asm("cvt.rn.bf16x2.f32 %0, %1, %2;" : "=r"(r) : "f"(hi), "f"(lo));
    return r;
}
__device__ __forceinline__ float bf_lo(uint32_t v) { return __uint_as_float(v << 16); }
__device__ __forceinline__ float bf_hi(uint32_t v) { return __uint_as_float(v & 0xffff0000u); }
__device__ __forceinline__ float bf16_round(float v) { return __bfloat162float(__float2bfloat16_rn(v)); }
__device__ __forceinline__ float sqrt_fast(float v) {
    float r;
    asm("sqrt.approx.ftz.f32 %0, %1;" : "=f"(r) : "f"(v));
    return r;
}
__device__ __forceinline__ float rcp_fast(float v) {
    float r;
    asm("rcp.approx.ftz.f32 %0, %1;" : "=f"(r) : "f"(v));
    return r;
}
__device__ __forceinline__ float ex2_fast(float v) {
    float r;
    asm("ex2.approx.ftz.f32 %0, %1;" : "=f"(r) : "f"(v));
    return r;
}
struct RowScale { float rho, rl, var; };
__device__ __forceinline__ float phi_f(float a, const RowScale& r) {
    return fmaf(fmaxf(a, 0.f), r.rho, ex2_fast(fminf(a, 0.f) * r.rl) + 1e-6f);
}
__device__ __forceinline__ float swiglu_f(float ga, float ua, const RowScale& r) {
    return (ga * ua) * rcp_fast(fmaf(ex2_fast(-ga * r.rl), r.var, r.var));
}
__device__ __forceinline__ uint4 swiglu8(const float* gp, const float* up, const RowScale& r0, const RowScale& r1) {
    uint4 v;
    v.x = pack_bf16(swiglu_f(gp[0], up[0], r0), swiglu_f(gp[1], up[1], r0));
    v.y = pack_bf16(swiglu_f(gp[2], up[2], r1), swiglu_f(gp[3], up[3], r1));
    v.z = pack_bf16(swiglu_f(gp[4], up[4], r0), swiglu_f(gp[5], up[5], r0));
    v.w = pack_bf16(swiglu_f(gp[6], up[6], r1), swiglu_f(gp[7], up[7], r1));
    v.y = v.y ? v.y : 0x8000u;
    v.w = v.w ? v.w : 0x8000u;
    return v;
}
__device__ __forceinline__ bool frag_stale(const uint4 (&f)[12]) {
    unsigned v = min(f[0].y, f[0].w);
#pragma unroll
    for (int i = 1; i < 12; i++) v = min(v, min(f[i].y, f[i].w));
    return __any_sync(0xffffffffu, v == 0u);
}
__device__ __forceinline__ void st_frag(uint4* p, uint4 v) {
    asm volatile("st.relaxed.gpu.global.v4.u32 [%0], {%1,%2,%3,%4};" ::"l"(p), "r"(v.x), "r"(v.y), "r"(v.z), "r"(v.w) : "memory");
}
__device__ __forceinline__ uint4 ld_frag(const uint4* p) {
    uint4 v;
    asm volatile("ld.relaxed.gpu.global.v4.u32 {%0,%1,%2,%3}, [%4];" : "=r"(v.x), "=r"(v.y), "=r"(v.z), "=r"(v.w) : "l"(p) : "memory");
    return v;
}
__device__ __forceinline__ void red_add2(float* p, float a, float b) {
    asm volatile("red.global.add.v2.f32 [%0], {%1, %2};" ::"l"(p), "f"(a), "f"(b) : "memory");
}
__device__ __forceinline__ void cp_async16(uint32_t dst, const void* src) {
    asm volatile("cp.async.cg.shared.global [%0], [%1], 16;" ::"r"(dst), "l"(src) : "memory");
}

__host__ __device__ constexpr int ring_lap(int u) { return (u * 79) >> 10; }
__host__ __device__ constexpr int ring_slot(int u) { return u - NST * ring_lap(u); }

__device__ __forceinline__ void mainloop128(float (&acc)[64], const uint32_t (&xa)[128], int u0, uint32_t sb,
                                            uint32_t desc128, int lane, int wg, bool last = false) {
    bar_sync(7 + wg, 256);
#pragma unroll
    for (int kb = 0; kb < 8; kb++) {
        const int st = ring_slot(u0 + kb);
        mbar_wait(sb + BAR_FULL + 8 * st, ring_lap(u0 + kb) & 1);
        wg_fence();
        const uint32_t d = desc128 + st * (STAGE_BYTES >> 4);
#pragma unroll
        for (int ks = 0; ks < 4; ks++) wgmma_n128_rs(acc, &xa[(kb * 4 + ks) * 4], d + ks * 128, (kb | ks) != 0);
        wg_commit();
        if (kb == 7 && !(last && wg == 1)) bar_arrive(8 - wg, 256);
        if (kb > 0) {
            wg_wait<1>();
            if (lane < 2) mbar_arrive_cta(sb + BAR_EMPTY + 8 * ring_slot(u0 + kb - 1), lane);
        }
    }
    wg_wait<0>();
    acc_fence(acc);
    if (lane < 2) mbar_arrive_cta(sb + BAR_EMPTY + 8 * ring_slot(u0 + 7), lane);
}
__device__ __forceinline__ void mainloop64x2(float (&a0)[32], float (&a1)[32], const uint32_t (&xa)[128], int u0,
                                             uint32_t sb, uint32_t desc128, int lane, int wg) {
    bar_sync(7 + wg, 256);
#pragma unroll
    for (int kb = 0; kb < 8; kb++) {
        const int st = ring_slot(u0 + kb);
        mbar_wait(sb + BAR_FULL + 8 * st, ring_lap(u0 + kb) & 1);
        wg_fence();
        const uint32_t d = desc128 + st * (STAGE_BYTES >> 4);
        const uint32_t d2 = d + (8192 >> 4) - ((4096u >> 4) << 16);
#pragma unroll
        for (int ks = 0; ks < 4; ks++) {
            wgmma_n64_rs<DHI128>(a0, &xa[(kb * 4 + ks) * 4], d + ks * 128, (kb | ks) != 0);
            wgmma_n64_rs<DHI64>(a1, &xa[(kb * 4 + ks) * 4], d2 + ks * 64, (kb | ks) != 0);
        }
        wg_commit();
        if (kb == 7) bar_arrive(8 - wg, 256);
        if (kb > 0) {
            wg_wait<1>();
            if (lane < 2) mbar_arrive_cta(sb + BAR_EMPTY + 8 * ring_slot(u0 + kb - 1), lane);
        }
    }
    wg_wait<0>();
    acc_fence(a0);
    acc_fence(a1);
    if (lane < 2) mbar_arrive_cta(sb + BAR_EMPTY + 8 * ring_slot(u0 + 7), lane);
}

__global__ void __cluster_dims__(2, 1, 1) __launch_bounds__(384, 1)
fused_kernel(const __grid_constant__ CUtensorMap tm_x, const __grid_constant__ CUtensorMap tm_qkv,
             const __grid_constant__ CUtensorMap tm_w1, const __grid_constant__ CUtensorMap tm_w3,
             const __grid_constant__ CUtensorMap tm_w1h, const __grid_constant__ CUtensorMap tm_w3h,
             const __grid_constant__ CUtensorMap tm_w2, const __grid_constant__ CUtensorMap tm_w2h,
             const __grid_constant__ CUtensorMap tm_wo, const __nv_bfloat16* __restrict__ xg,
             __nv_bfloat16* __restrict__ outg, const char* __restrict__ p_qkv, const char* __restrict__ p_w1,
             const char* __restrict__ p_w3, const char* __restrict__ p_w2, const char* __restrict__ p_wo) {
    extern __shared__ __align__(1024) uint8_t smem[];
    const uint32_t sb = smem_u32(smem);
    const int tid = threadIdx.x;
    const int warp = tid >> 5, lane = tid & 31;
    const int rank = blockIdx.x & 1;
    const int pair = blockIdx.x >> 1;
    const int c = pair & 7;
    const int m = (pair >> 3) * 2 + rank;
    const int j2 = c >> 1, kh = c & 1;

    TS(tid >> 7, 0);
    if (tid == 256) {
#pragma unroll
        for (int i = 0; i < 8; i++) mbar_init(sb + BAR_XFULL + 8 * i, 1);
        asm volatile("fence.proxy.async.shared::cta;" ::: "memory");
#pragma unroll
        for (int kb = 0; kb < 8; kb++) {
            mbar_expect_tx(sb + BAR_XFULL + 8 * kb, 16384);
            tma_load(sb + (XST0 + kb) * STAGE_BYTES, &tm_x, sb + BAR_XFULL + 8 * kb, kb * 64, m * 128);
        }
        TS(2, 21);
    } else if (tid == 0) {
#pragma unroll
        for (int i = 0; i < NST; i++) mbar_init(sb + BAR_FULL + 8 * i, 1);
        asm volatile("fence.mbarrier_init.release.cluster;" ::: "memory");
    } else if (tid == 32) {
#pragma unroll
        for (int i = 0; i < NST; i++) mbar_init(sb + BAR_EMPTY + 8 * i, 16);
        asm volatile("fence.mbarrier_init.release.cluster;" ::: "memory");
    } else if (tid == 64) {
#pragma unroll
        for (int i = 0; i < 4; i++) mbar_init(sb + BAR_KVREADY + 8 * i, 1);
        asm volatile("fence.mbarrier_init.release.cluster;" ::: "memory");
    } else if (tid >= 128 && tid < 256) {
        ((uint4*)(smem + OFF_ZERO))[tid - 128] = make_uint4(0, 0, 0, 0);
        ((uint4*)(smem + OFF_ZERO))[tid] = make_uint4(0, 0, 0, 0);
        asm volatile("fence.proxy.async.shared::cta;" ::: "memory");
    } else if (tid == 288) {
        prefetch_tm(&tm_qkv);
        prefetch_tm(rank ? &tm_w3 : &tm_w1);
        prefetch_tm(&tm_w1h);
        prefetch_tm(&tm_w3h);
        prefetch_tm(&tm_w2);
        prefetch_tm(&tm_w2h);
        prefetch_tm(&tm_wo);
    } else if (tid >= 320) {
        ((uint32_t*)(smem + OFF_ONES))[tid - 320] = 0x3F803F80u;
        asm volatile("fence.proxy.async.shared::cta;" ::: "memory");
    }
    __syncthreads();
    TS(tid >> 7, 22);
    asm volatile("barrier.cluster.arrive.relaxed.aligned;\nbarrier.cluster.wait.acquire.aligned;" ::: "memory");

    if (warp >= 8) {
        asm volatile("setmaxnreg.dec.sync.aligned.u32 40;");
        if (warp == 8) {
            if (lane == 0) {
                int st = 0;
                uint32_t lap = 0;
                for (int it = 0; it < 40; it++) {
                    const int tile = it >> 3, kb = it & 7;
                    const uint32_t full = sb + BAR_FULL + 8 * st;
                    mbar_wait(sb + BAR_EMPTY + 8 * st, (st >= XST0) ? (lap & 1) : ((lap & 1) ^ 1));
                    mbar_expect_tx(full, STAGE_BYTES);
                    const uint32_t dst = sb + st * STAGE_BYTES;
                    if (tile == 0) {
                        tma_load_mc(dst + rank * 8192, &tm_qkv, full, 512 + 512 * rank + 64 * c, kb * 64);
                    } else if (tile != 3) {
                        tma_load_mc(dst + rank * 8192, rank ? &tm_w3 : &tm_w1, full, 224 * c + 64 * (tile == 4 ? 2 : tile - 1), kb * 64);
                    } else if (rank == 0) {
                        tma_load_mc(dst, &tm_qkv, full, 64 * c, kb * 64);
                    } else {
                        tma_load_mc(dst + 8192, &tm_w1h, full, 224 * c + 192, kb * 64);
                        tma_load_mc(dst + 12288, &tm_w3h, full, 224 * c + 192, kb * 64);
                    }
                    if (++st == NST) { st = 0; lap++; }
                    if (it == 7) {
                        mbar_wait(sb + BAR_EMPTY + 8 * SCR0, 0);
                        mbar_arrive(sb + BAR_FULL + 8 * SCR0);
                        mbar_wait(sb + BAR_EMPTY + 8 * (SCR0 + 1), 0);
                        mbar_arrive(sb + BAR_FULL + 8 * (SCR0 + 1));
                        st += 2;
                    }
                }
                TS(2, 1);
                mbar_wait(sb + BAR_EPOCH, 0);
                const char* a2b = (const char*)(g_A2 + (size_t)(*(volatile unsigned*)(smem + OFF_EPOCH) & 1) * A2_N +
                                                (size_t)((m * 2 + kh) * 18) * 4 * 256);
#pragma unroll 1
                for (int i = 0; i < 18; i++) {
                    const int b = P2_ID[i];
                    if (b < 8) {
                        mbar_wait(sb + BAR_EMPTY + 8 * st, (st >= XST0) ? (lap & 1) : ((lap & 1) ^ 1));
                        mbar_expect_tx(sb + BAR_FULL + 8 * st, STAGE_BYTES);
                        asm volatile("cp.async.bulk.shared::cluster.global.mbarrier::complete_tx::bytes [%0], [%1], 16384, [%2];"
                                     ::"r"(sb + st * STAGE_BYTES), "l"(a2b + b * 16384), "r"(sb + BAR_FULL + 8 * st) : "memory");
                        if (++st == NST) { st = 0; lap++; }
                    }
                    const uint32_t full = sb + BAR_FULL + 8 * st;
                    const uint32_t dst = sb + st * STAGE_BYTES;
                    mbar_wait(sb + BAR_EMPTY + 8 * st, (st >= XST0) ? (lap & 1) : ((lap & 1) ^ 1));
                    mbar_expect_tx(full, STAGE_BYTES);
                    const int col = 128 * j2 + 64 * rank;
                    if (b < 8 || b >= 14) {
                        const int row = (b < 8) ? 224 * (4 * kh + (b & 3)) + 64 * (b >> 2) : 224 * (4 * kh + b - 14) + 128;
                        tma_load_mc(dst + rank * 8192, &tm_w2, full, col, row);
                    } else if (b < 10) {
                        const int row = 224 * (4 * kh + 2 * (b - 8)) + 192;
                        tma_load_mc(dst + rank * 8192, &tm_w2h, full, col, row);
                        tma_load_mc(dst + rank * 8192 + 4096, &tm_w2h, full, col, row + 224);
                    } else {
                        tma_load_mc(dst + rank * 8192, &tm_wo, full, col, 64 * (4 * kh + (b - 10)));
                    }
                    TS(2, 2 + i);
                    if (++st == NST) { st = 0; lap++; }
                }
            }
        } else if (warp < 11) {
            const int wg = warp - 9;
            bar_sync(3 + wg, 160);
            if (lane == 0) asm volatile("red.release.gpu.global.add.u32 [%0], 1;" ::"l"(&g_kvcnt[c]) : "memory");
            TSW(3, wg);
        } else {
            const unsigned epoch = read_epoch();
            if (lane == 0) {
                const unsigned tk = atomicInc(&g_ticket, 127u);
                if (tk == 127u) *(volatile unsigned*)&g_epoch = epoch;
            }
            if (lane == 0) *(volatile unsigned*)(smem + OFF_EPOCH) = epoch;
            __syncwarp();
            if (lane == 0) mbar_arrive(sb + BAR_EPOCH);
            if (lane < 17) g_kvacc[(((epoch & 1) ^ 1) * 8 + c) * 272 + 17 * m + lane] = make_float4(0.f, 0.f, 0.f, 0.f);
            {
                unsigned n = 0;
                while ((int)(ld_acquire(&g_kvcnt[c]) - 32u * epoch) < 0) {
                    __nanosleep(200);
                    if (++n > SPIN_LIMIT) asm volatile("trap;");
                }
            }
            TSW(4, 0);
            const int g = lane >> 2, t = lane & 3;
            const float* ks = (const float*)(g_kvacc + ((epoch & 1) * 8 + c) * 272) + 32 * t + g;
            uint2* kf = (uint2*)(smem + OFF_KVFRAG) + lane;
#pragma unroll 2
            for (int hh = 0; hh < 4; hh++) {
                const float* k = ks + hh * 272;
                const float a0 = __ldcg(k), a1 = __ldcg(k + 16), a2 = __ldcg(k + 128), a3 = __ldcg(k + 144);
                const float b0 = __ldcg(k + 8), b1 = __ldcg(k + 24), b2 = __ldcg(k + 136), b3 = __ldcg(k + 152);
                const float2 z0 = __ldcg((const float2*)(k - g - 30 * t + 256)), z1 = __ldcg((const float2*)(k - g - 30 * t + 264));
                kf[(hh * 3 + 0) * 32] = make_uint2(pack_bf16(a0, a1), pack_bf16(a2, a3));
                kf[(hh * 3 + 1) * 32] = make_uint2(pack_bf16(b0, b1), pack_bf16(b2, b3));
                kf[(hh * 3 + 2) * 32] = make_uint2(pack_bf16(z0.x, z0.y), pack_bf16(z1.x, z1.y));
            }
            __syncwarp();
            if (lane == 0) mbar_arrive(sb + BAR_KVREADY);
            TSW(4, 4);
            if (lane == 0) {
                char* z = (char*)(g_A2 + (size_t)((epoch & 1) ^ 1) * A2_N + (size_t)((m * 2 + (c >> 2)) * 18) * 4 * 256);
                const int cc = c & 3;
#pragma unroll 1
                for (int i = 0; i < 18; i++) {
                    const int blk = (i < 8) ? ((i >> 2) * 4 + cc) * 4 + (i & 3)
                                  : (i < 10) ? (8 + (cc >> 1)) * 4 + 2 * (cc & 1) + (i - 8)
                                  : (i < 14) ? (10 + cc) * 4 + (i - 10) : (14 + cc) * 4 + (i - 14);
                    asm volatile("cp.async.bulk.global.shared::cta.bulk_group [%0], [%1], 4096;"
                                 ::"l"(z + (size_t)blk * 4096), "r"(sb + OFF_ZERO) : "memory");
                }
                char* zx = (char*)(g_xch + (size_t)(((epoch & 1) ^ 1) * 128 + blockIdx.x) * 2048);
#pragma unroll 1
                for (int i = 0; i < 8; i++)
                    asm volatile("cp.async.bulk.global.shared::cta.bulk_group [%0], [%1], 4096;"
                                 ::"l"(zx + i * 4096), "r"(sb + OFF_ZERO) : "memory");
                asm volatile("cp.async.bulk.commit_group;" ::: "memory");
            }
            if (lane == 0) asm volatile("cp.async.bulk.wait_group 0;" ::: "memory");
        }
    } else {
        asm volatile("setmaxnreg.inc.sync.aligned.u32 232;");
        const int wg = warp >> 2, w = warp & 3;
        const int g = lane >> 2, t = lane & 3;
        float acc[64];
        uint32_t xa[128];
        float rho0, rho1;
        RowScale r0, r1;
        unsigned par;

        TS(wg, 1);
        {
            const int row = wg * 64 + w * 16 + (lane & 7) + ((lane >> 3) & 1) * 8;
            const uint32_t rbase = sb + XST0 * STAGE_BYTES + row * 128;
            const int hi = lane >> 4, r7 = lane & 7;
            float sm[2][4], c0[2][4], c1[2][4];
#pragma unroll
            for (int i = 0; i < 8; i++) { sm[i >> 2][i & 3] = 0.f; c0[i >> 2][i & 3] = 0.f; c1[i >> 2][i & 3] = 0.f; }
            if (wg == 1) bar_arrive(7, 256);
#pragma unroll
            for (int kb = 0; kb < 8; kb++) {
                mbar_wait(sb + BAR_XFULL + 8 * kb, 0);
#pragma unroll
                for (int ks = 0; ks < 4; ks++) {
                    uint32_t* a = &xa[(kb * 4 + ks) * 4];
                    const uint32_t addr = rbase + kb * STAGE_BYTES + (((2 * ks + hi) ^ r7) << 4);
                    asm volatile("ldmatrix.sync.aligned.m8n8.x4.shared.b16 {%0,%1,%2,%3}, [%4];"
                                 : "=r"(a[0]), "=r"(a[1]), "=r"(a[2]), "=r"(a[3]) : "r"(addr) : "memory");
                    mma16816(sm[ks & 1], a, 0x3F803F80u, 0x3F803F80u);
                    mma16816(c0[ks & 1], a, a[0], a[2]);
                    mma16816(c1[ks & 1], a, a[1], a[3]);
                }
            }
            TS(wg, 2);
            const float mean0 = (sm[0][0] + sm[1][0]) * (1.f / 512.f);
            const float mean1 = (sm[0][2] + sm[1][2]) * (1.f / 512.f);
            __syncwarp();
            if (lane < 16) mbar_arrive_cta(sb + BAR_EMPTY + 8 * (XST0 + (lane >> 1)), lane & 1);
            const __nv_bfloat162 mb0 = __float2bfloat162_rn(mean0), mb1 = __float2bfloat162_rn(mean1);
#pragma unroll
            for (int i = 0; i < 128; i++) {
                __nv_bfloat162 v = *reinterpret_cast<__nv_bfloat162*>(&xa[i]);
                v = __hsub2(v, (i & 1) ? mb1 : mb0);
                xa[i] = *reinterpret_cast<uint32_t*>(&v);
            }
            const float d0 = (g & 1) ? c0[0][1] + c0[1][1] : c0[0][0] + c0[1][0];
            const float d1 = (g & 1) ? c1[0][3] + c1[1][3] : c1[0][2] + c1[1][2];
            const int src = (lane & ~3) | (g >> 1);
            const float var0 = fmaxf(__shfl_sync(0xffffffffu, d0, src) * (1.f / 512.f) - mean0 * mean0, 0.f);
            const float var1 = fmaxf(__shfl_sync(0xffffffffu, d1, src) * (1.f / 512.f) - mean1 * mean1, 0.f);
            const float sd0 = bf16_round(sqrt_fast(bf16_round(bf16_round(var0) + 1e-5f)));
            const float sd1 = bf16_round(sqrt_fast(bf16_round(bf16_round(var1) + 1e-5f)));
            rho0 = rcp_fast(sd0);
            rho1 = rcp_fast(sd1);
            r0.rho = rho0; r0.rl = rho0 * 1.4426950408889634f; r0.var = sd0 * sd0;
            r1.rho = rho1; r1.rl = rho1 * 1.4426950408889634f; r1.var = sd1 * sd1;
        }

        TS(wg, 3);
        const uint32_t desc128 = ((sb & 0x3FFFF) >> 4) | ((8192u >> 4) << 16);
        const int cc = c & 3;

        {
            mainloop128(acc, xa, 0, sb, desc128, lane, wg);
            TS(wg, 4);
            {
                TS(wg, 24);
                const uint32_t pkb = sb + (SCR0 + wg) * STAGE_BYTES;
                mbar_wait(sb + BAR_FULL + 8 * (SCR0 + wg), 0);
                const uint32_t ra = pkb + (w * 16 + g) * 128 + t * 4;
#pragma unroll
                for (int nb = 0; nb < 8; nb++) {
                    const uint32_t off = (uint32_t)((nb ^ g) << 4);
                    uint32_t p0 = pack_bf16(phi_f(acc[nb * 4], r0), phi_f(acc[nb * 4 + 1], r0));
                    uint32_t p1 = pack_bf16(phi_f(acc[nb * 4 + 2], r1), phi_f(acc[nb * 4 + 3], r1));
                    uint32_t v0 = pack_bf16(acc[32 + nb * 4] * rho0, acc[32 + nb * 4 + 1] * rho0);
                    uint32_t v1 = pack_bf16(acc[32 + nb * 4 + 2] * rho1, acc[32 + nb * 4 + 3] * rho1);
                    asm volatile("st.shared.u32 [%0], %1;" ::"r"(ra + off), "r"(p0) : "memory");
                    asm volatile("st.shared.u32 [%0], %1;" ::"r"(ra + off + 1024), "r"(p1) : "memory");
                    asm volatile("st.shared.u32 [%0], %1;" ::"r"(ra + off + 8192), "r"(v0) : "memory");
                    asm volatile("st.shared.u32 [%0], %1;" ::"r"(ra + off + 8192 + 1024), "r"(v1) : "memory");
                }
                TS(wg, 25);
                asm volatile("fence.proxy.async.shared::cta;" ::: "memory");
                bar_sync(1 + wg, 128);
                TS(wg, 26);
                const uint64_t da = make_desc(pkb, 8192, 1024, 1);
                const uint64_t db = make_desc(pkb + 8192, 8192, 1024, 1);
                const uint64_t d1 = make_desc(sb + OFF_ONES, 128, 128, 0);
                float kva[32], za[4];
                wg_fence();
#pragma unroll
                for (int ks = 0; ks < 4; ks++) {
                    wgmma_n64_ss_tt(kva, da + ks * 128, db + ks * 128, ks != 0);
                    wgmma_n8_ss_tn(za, da + ks * 128, d1, ks != 0);
                }
                wg_commit();
                wg_wait<0>();
                acc_fence(kva);
                acc_fence(za);
                if (lane < 4) mbar_arrive_cta(sb + BAR_EMPTY + 8 * (SCR0 + (lane >> 1)), lane & 1);
                TS(wg, 27);
                float o[8];
#pragma unroll
                for (int i = 0; i < 8; i++)
                    o[i] = (w == 0) ? kva[i] : (w == 1) ? kva[8 + i] : (w == 2) ? kva[16 + i] : kva[24 + i];
                mbar_wait(sb + BAR_EPOCH, 0);
                par = *(volatile unsigned*)(smem + OFF_EPOCH) & 1;
                float* dst = (float*)(g_kvacc + (par * 8 + c) * 272) + w * 272 + g * 16 + 2 * t;
                red_add2(dst, o[0], o[1]);
                red_add2(dst + 128, o[2], o[3]);
                red_add2(dst + 8, o[4], o[5]);
                red_add2(dst + 136, o[6], o[7]);
                if (t == 0) {
                    atomicAdd(dst - g * 15 + 256, za[0]);
                    atomicAdd(dst - g * 15 + 264, za[2]);
                }
            }
            bar_arrive(3 + wg, 160);
            TS(wg, 5);
        }
        uint4* a2w = g_A2 + (size_t)par * A2_N + (size_t)((m * 2 + (c >> 2)) * 18) * 4 * 256 + warp * 32 + lane;
#pragma unroll
        for (int tile = 1; tile < 3; tile++) {
            mainloop128(acc, xa, 2 + 8 * tile, sb, desc128, lane, wg);
            TS(wg, 4 + 2 * tile);
            uint4* dst = a2w + (size_t)((4 * (tile - 1) + cc) * 4) * 256;
#pragma unroll
            for (int ks = 0; ks < 4; ks++) st_frag(dst + ks * 256, swiglu8(&acc[ks * 8], &acc[32 + ks * 8], r0, r1));
            TS(wg, 5 + 2 * tile);
        }
        {
            float qa[32], gu[32];
            mainloop64x2(qa, gu, xa, 26, sb, desc128, lane, wg);
            TS(wg, 10);
            uint4* dst = a2w + (size_t)((8 + (cc >> 1)) * 4 + 2 * (cc & 1)) * 256;
#pragma unroll
            for (int ks = 0; ks < 2; ks++) st_frag(dst + ks * 256, swiglu8(&gu[ks * 8], &gu[16 + ks * 8], r0, r1));
            TS(wg, 13);
            mbar_wait(sb + BAR_KVREADY, 0);
            TS(wg, 14);
            const uint2* kf = (const uint2*)(smem + OFF_KVFRAG);
            dst = a2w + (size_t)((10 + cc) * 4) * 256;
#pragma unroll
            for (int hh = 0; hh < 4; hh++) {
                const float* q = &qa[hh * 8];
                uint32_t a[4];
                a[0] = pack_bf16(phi_f(q[0], r0), phi_f(q[1], r0));
                a[1] = pack_bf16(phi_f(q[2], r1), phi_f(q[3], r1));
                a[2] = pack_bf16(phi_f(q[4], r0), phi_f(q[5], r0));
                a[3] = pack_bf16(phi_f(q[6], r1), phi_f(q[7], r1));
                float n0[4] = {0.f, 0.f, 0.f, 0.f}, n1[4] = {0.f, 0.f, 0.f, 0.f}, dn[4] = {0.f, 0.f, 0.f, 0.f};
                const uint2 b0 = kf[(hh * 3 + 0) * 32 + lane], b1 = kf[(hh * 3 + 1) * 32 + lane],
                            bz = kf[(hh * 3 + 2) * 32 + lane];
                mma16816(n0, a, b0.x, b0.y);
                mma16816(n1, a, b1.x, b1.y);
                mma16816(dn, a, bz.x, bz.y);
                const float i0 = rcp_fast(dn[0] + 1e-6f), i1 = rcp_fast(dn[2] + 1e-6f);
                uint4 v;
                v.x = pack_bf16(n0[0] * i0, n0[1] * i0);
                v.y = pack_bf16(n0[2] * i1, n0[3] * i1);
                v.z = pack_bf16(n1[0] * i0, n1[1] * i0);
                v.w = pack_bf16(n1[2] * i1, n1[3] * i1);
                v.y = v.y ? v.y : 0x8000u;
                v.w = v.w ? v.w : 0x8000u;
                st_frag(dst + hh * 256, v);
            }
            TS(wg, 11);
        }
        const uint4* a2r = g_A2 + (size_t)par * A2_N + (size_t)((m * 2 + kh) * 18) * 4 * 256 + warp * 32 + lane;
        uint4 af[2][12];
        {
            mainloop128(acc, xa, 34, sb, desc128, lane, wg);
            TS(wg, 12);
            uint4* dst = a2w + (size_t)((14 + cc) * 4) * 256;
#pragma unroll
            for (int ks = 0; ks < 4; ks++) st_frag(dst + ks * 256, swiglu8(&acc[ks * 8], &acc[32 + ks * 8], r0, r1));
            TS(wg, 15);
        }

        {
            float ao[32], ap[32];
            const uint32_t dso = desc128 + kh * 512, dsp = desc128 + (kh ^ 1) * 512;
            TS(wg, 16);
#pragma unroll
            for (int gi = 0; gi < 6; gi++) {
                if (gi == 5) TS(wg, 17);
                uint4(&f)[12] = af[gi & 1];
#pragma unroll
                for (int bb = 0; bb < 3; bb++) {
                    const int ub = p2_useB(gi * 3 + bb);
                    if (p2_id(gi * 3 + bb) < 8) {
                        mbar_wait(sb + BAR_FULL + 8 * ring_slot(ub - 1), ring_lap(ub - 1) & 1);
                        const uint4* src = (const uint4*)(smem + ring_slot(ub - 1) * STAGE_BYTES) + tid;
#pragma unroll
                        for (int ks = 0; ks < 4; ks++) f[bb * 4 + ks] = src[ks * 256];
                    }
                    mbar_wait(sb + BAR_FULL + 8 * ring_slot(ub), ring_lap(ub) & 1);
                }
                {
                    unsigned n = 0;
                    while (frag_stale(f)) {
#pragma unroll
                        for (int i = 0; i < 12; i++) f[i] = ld_frag(a2r + (p2_id(gi * 3 + (i >> 2)) * 4 + (i & 3)) * 256);
                        if (++n > SPIN_LIMIT) asm volatile("trap;");
                    }
                }
                bar_sync(7 + wg, 256);
                wg_fence();
#pragma unroll
                for (int i = 0; i < 12; i++) {
                    const uint32_t so = ring_slot(p2_useB(gi * 3 + (i >> 2))) * (STAGE_BYTES >> 4) + (i & 3) * 128;
                    const uint32_t* a = reinterpret_cast<const uint32_t*>(&f[i]);
                    wgmma_n64_rs<DHI128>(ap, a, dsp + so, (gi | i) != 0);
                    if (gi < 4) wgmma_n64_rs<DHI128>(ao, a, dso + so, (gi | i) != 0);
                }
                wg_commit();
                bar_arrive(8 - wg, 256);
                if (gi < 5) {
#pragma unroll
                    for (int i = 0; i < 12; i++)
                        if (p2_id(gi * 3 + 3 + (i >> 2)) >= 8)
                            af[(gi + 1) & 1][i] = ld_frag(a2r + (p2_id(gi * 3 + 3 + (i >> 2)) * 4 + (i & 3)) * 256);
                    wg_wait<0>();
                    if (gi < 3 && lane < (gi == 0 ? 12 : gi == 1 ? 10 : 4)) {
                        const int u = (gi == 0 ? 42 : gi == 1 ? 48 : 53) + (lane >> 1);
                        const bool isA = (0xA55u >> (u - 42)) & 1;
                        mbar_arrive_cta(sb + BAR_EMPTY + 8 * ring_slot(u), isA ? rank : (lane & 1));
                    }
                }
            }
            wg_wait<0>();
            acc_fence(ap);
            TS(wg, 18);
            {
                uint4* xo = g_xch + (size_t)(par * 128 + (blockIdx.x ^ 2)) * 2048 + tid;
#pragma unroll
                for (int i = 0; i < 8; i++) {
                    uint4 v = make_uint4(__float_as_uint(ap[4 * i]), __float_as_uint(ap[4 * i + 1]),
                                         __float_as_uint(ap[4 * i + 2]), __float_as_uint(ap[4 * i + 3]));
                    v.y = v.y ? v.y : 0x80000000u;
                    v.w = v.w ? v.w : 0x80000000u;
                    st_frag(xo + i * 256, v);
                }
            }
            bar_sync(7 + wg, 256);
            wg_fence();
#pragma unroll
            for (int i = 0; i < 24; i++)
                wgmma_n64_rs<DHI128>(ao, reinterpret_cast<const uint32_t*>(&af[i / 12][i % 12]),
                                     dso + ring_slot(p2_useB(12 + (i >> 2))) * (STAGE_BYTES >> 4) + (i & 3) * 128, 1);
            wg_commit();
            if (wg == 0) bar_arrive(8, 256);
            const int row0 = m * 128 + wg * 64 + w * 16 + g;
            const int col0 = j2 * 128 + kh * 64 + 2 * t;
            uint32_t xr[16];
#pragma unroll
            for (int nb = 0; nb < 8; nb++) {
                xr[2 * nb] = __ldg((const uint32_t*)(xg + (size_t)row0 * 512 + col0 + nb * 8));
                xr[2 * nb + 1] = __ldg((const uint32_t*)(xg + (size_t)(row0 + 8) * 512 + col0 + nb * 8));
            }
            wg_wait<0>();
            acc_fence(ao);
            const uint4* xi = g_xch + (size_t)(par * 128 + blockIdx.x) * 2048 + tid;
            uint4 pin[8];
            {
                unsigned n = 0;
                while (true) {
#pragma unroll
                    for (int i = 0; i < 8; i++) pin[i] = ld_frag(xi + i * 256);
                    unsigned v = min(pin[0].y, pin[0].w);
#pragma unroll
                    for (int i = 1; i < 8; i++) v = min(v, min(pin[i].y, pin[i].w));
                    if (!__any_sync(0xffffffffu, v == 0u)) break;
                    if (++n > SPIN_LIMIT) asm volatile("trap;");
                }
            }
            TS(wg, 19);
#pragma unroll
            for (int nb = 0; nb < 8; nb++) {
                const uint4 p = pin[nb];
                const uint32_t o0 = pack_bf16(ao[4 * nb] + __uint_as_float(p.x) + bf_lo(xr[2 * nb]),
                                              ao[4 * nb + 1] + __uint_as_float(p.y) + bf_hi(xr[2 * nb]));
                const uint32_t o1 = pack_bf16(ao[4 * nb + 2] + __uint_as_float(p.z) + bf_lo(xr[2 * nb + 1]),
                                              ao[4 * nb + 3] + __uint_as_float(p.w) + bf_hi(xr[2 * nb + 1]));
                *(uint32_t*)(outg + (size_t)row0 * 512 + col0 + nb * 8) = o0;
                *(uint32_t*)(outg + (size_t)(row0 + 8) * 512 + col0 + nb * 8) = o1;
            }
        }
        asm volatile("barrier.cluster.arrive.relaxed.aligned;\nbarrier.cluster.wait.aligned;" ::: "memory");
        TS(wg, 20);
    }
}

typedef CUresult (*EncodeFn)(CUtensorMap*, CUtensorMapDataType, cuuint32_t, void*, const cuuint64_t*, const cuuint64_t*,
                             const cuuint32_t*, const cuuint32_t*, CUtensorMapInterleave, CUtensorMapSwizzle,
                             CUtensorMapL2promotion, CUtensorMapFloatOOBfill);

void make_map(EncodeFn enc, CUtensorMap* tm, const void* ptr, int rows, int cols, int box_rows, int box_cols,
              CUtensorMapSwizzle swz) {
    cuuint64_t dims[2] = {(cuuint64_t)cols, (cuuint64_t)rows};
    cuuint64_t strides[1] = {(cuuint64_t)cols * 2};
    cuuint32_t box[2] = {(cuuint32_t)box_cols, (cuuint32_t)box_rows};
    cuuint32_t es[2] = {1, 1};
    enc(tm, CU_TENSOR_MAP_DATA_TYPE_BFLOAT16, 2, const_cast<void*>(ptr), dims, strides, box, es,
        CU_TENSOR_MAP_INTERLEAVE_NONE, swz, CU_TENSOR_MAP_L2_PROMOTION_L2_256B, CU_TENSOR_MAP_FLOAT_OOB_FILL_NONE);
}

}

extern "C" void kernel_launch(void* const* d_in, const int* in_sizes, int n_in, void* d_out, int out_size) {
    (void)in_sizes; (void)n_in; (void)out_size;
    static EncodeFn enc = nullptr;
    if (!enc) {
        void* fn = nullptr;
        cudaDriverEntryPointQueryResult qr;
        cudaGetDriverEntryPoint("cuTensorMapEncodeTiled", &fn, cudaEnableDefault, &qr);
        enc = (EncodeFn)fn;
        cudaFuncSetAttribute(fused_kernel, cudaFuncAttributeMaxDynamicSharedMemorySize, SMEM_BYTES);
    }
    const void* x = d_in[0];
    const void* wqkv = d_in[1];
    const void* wo = d_in[2];
    const void* w1 = d_in[4];
    const void* w3 = d_in[5];
    const void* w2 = d_in[6];
    CUtensorMap tx, tqkv, t1, t3, t1h, t3h, t2, t2h, two;
    make_map(enc, &tx, x, 2048, 512, 128, 64, CU_TENSOR_MAP_SWIZZLE_128B);
    make_map(enc, &tqkv, wqkv, 512, 1536, 64, 64, CU_TENSOR_MAP_SWIZZLE_128B);
    make_map(enc, &t1, w1, 512, 1792, 64, 64, CU_TENSOR_MAP_SWIZZLE_128B);
    make_map(enc, &t3, w3, 512, 1792, 64, 64, CU_TENSOR_MAP_SWIZZLE_128B);
    make_map(enc, &t1h, w1, 512, 1792, 64, 32, CU_TENSOR_MAP_SWIZZLE_64B);
    make_map(enc, &t3h, w3, 512, 1792, 64, 32, CU_TENSOR_MAP_SWIZZLE_64B);
    make_map(enc, &t2, w2, 1792, 512, 64, 64, CU_TENSOR_MAP_SWIZZLE_128B);
    make_map(enc, &t2h, w2, 1792, 512, 32, 64, CU_TENSOR_MAP_SWIZZLE_128B);
    make_map(enc, &two, wo, 512, 512, 64, 64, CU_TENSOR_MAP_SWIZZLE_128B);
    fused_kernel<<<128, 384, SMEM_BYTES>>>(tx, tqkv, t1, t3, t1h, t3h, t2, t2h, two, (const __nv_bfloat16*)x,
                                           (__nv_bfloat16*)d_out, (const char*)wqkv, (const char*)w1, (const char*)w3,
                                           (const char*)w2, (const char*)wo);
}
```

```cpp
#include <cuda_runtime.h>
#include <cuda_bf16.h>
#include <cuda.h>
#include <stdint.h>

namespace {

constexpr int NST = 13;
constexpr int STAGE_BYTES = 16384;
constexpr int XST0 = 5;
constexpr int SCR0 = 8;
constexpr int XCH0 = 0;
constexpr int OFF_MISC = NST * STAGE_BYTES;
constexpr int OFF_KVFRAG = OFF_MISC;
constexpr int OFF_ONES = OFF_MISC + 3072;
constexpr int OFF_BARS = OFF_MISC + 3328;
constexpr int BAR_FULL = OFF_BARS;
constexpr int BAR_EMPTY = BAR_FULL + 8 * NST;
constexpr int BAR_XFULL = BAR_EMPTY + 8 * NST;
constexpr int BAR_KVREADY = BAR_XFULL + 64;
constexpr int BAR_XCHG = BAR_KVREADY + 8;
constexpr int BAR_EPOCH = BAR_XCHG + 8;
constexpr int BAR_XRDY = BAR_EPOCH + 8;
constexpr int OFF_EPOCH = BAR_XRDY + 8;
constexpr int OFF_ZERO = OFF_MISC + 4096;
constexpr int SMEM_BYTES = OFF_MISC + 8192;

constexpr unsigned SPIN_LIMIT = 1u << 24;

constexpr int A2_N = 16 * 2 * 18 * 4 * 256;
__device__ uint4 g_A2[2 * A2_N];
__device__ float4 g_kvacc[2 * 8 * 272];
__device__ unsigned g_kvcnt[8];
__device__ unsigned g_epoch;
__device__ unsigned g_ticket;

#define TS(role, i)
#define TSW(role, i)

__device__ __forceinline__ uint32_t smem_u32(const void* p) { return (uint32_t)__cvta_generic_to_shared(p); }
__device__ __forceinline__ void mbar_init(uint32_t bar, uint32_t cnt) {
    asm volatile("mbarrier.init.shared::cta.b64 [%0], %1;" ::"r"(bar), "r"(cnt) : "memory");
}
__device__ __forceinline__ void mbar_expect_tx(uint32_t bar, uint32_t bytes) {
    asm volatile("mbarrier.arrive.expect_tx.shared::cta.b64 _, [%0], %1;" ::"r"(bar), "r"(bytes) : "memory");
}
__device__ __forceinline__ void mbar_arrive(uint32_t bar) {
    asm volatile("mbarrier.arrive.shared::cta.b64 _, [%0];" ::"r"(bar) : "memory");
}
__device__ __forceinline__ void mbar_arrive_cta(uint32_t bar, uint32_t cta) {
    asm volatile(
        "{\n.reg .b32 ra;\nmapa.shared::cluster.u32 ra, %0, %1;\n"
        "mbarrier.arrive.shared::cluster.b64 _, [ra];\n}" ::"r"(bar), "r"(cta) : "memory");
}
__device__ __forceinline__ void mbar_wait(uint32_t bar, uint32_t parity) {
    asm volatile(
        "{\n.reg .pred p, q;\n.reg .u32 n;\nmov.u32 n, 0;\n"
        "WAIT_%=:\n"
        "mbarrier.try_wait.parity.shared::cta.b64 p, [%0], %1;\n"
        "@p bra.uni DONE_%=;\n"
        "add.u32 n, n, 1;\n"
        "setp.gt.u32 q, n, %2;\n"
        "@q trap;\n"
        "bra.uni WAIT_%=;\n"
        "DONE_%=:\n}"
        ::"r"(bar), "r"(parity), "n"(SPIN_LIMIT) : "memory");
}
__device__ __forceinline__ unsigned ld_acquire(const unsigned* p) {
    unsigned v;
    asm volatile("ld.acquire.gpu.global.u32 %0, [%1];" : "=r"(v) : "l"(p) : "memory");
    return v;
}
__device__ __forceinline__ void st_release(unsigned* p, unsigned v) {
    asm volatile("st.release.gpu.global.u32 [%0], %1;" ::"l"(p), "r"(v) : "memory");
}
__device__ __forceinline__ unsigned read_epoch() {
    return __shfl_sync(0xffffffffu, *(volatile unsigned*)&g_epoch, 0) + 1;
}
__device__ __forceinline__ void tma_load(uint32_t dst, const CUtensorMap* tm, uint32_t bar, int x, int y) {
    asm volatile(
        "cp.async.bulk.tensor.2d.shared::cluster.global.mbarrier::complete_tx::bytes [%0], [%1, {%3, %4}], [%2];"
        ::"r"(dst), "l"(tm), "r"(bar), "r"(x), "r"(y) : "memory");
}
__device__ __forceinline__ void tma_load_mc(uint32_t dst, const CUtensorMap* tm, uint32_t bar, int x, int y) {
    asm volatile(
        "cp.async.bulk.tensor.2d.shared::cluster.global.mbarrier::complete_tx::bytes.multicast::cluster "
        "[%0], [%1, {%3, %4}], [%2], %5;"
        ::"r"(dst), "l"(tm), "r"(bar), "r"(x), "r"(y), "h"((uint16_t)3) : "memory");
}
__device__ __forceinline__ void prefetch_tm(const CUtensorMap* tm) {
    asm volatile("prefetch.tensormap [%0];" ::"l"(tm) : "memory");
}
__device__ __forceinline__ void l2_prefetch(const void* p, uint32_t bytes) {
    asm volatile("cp.async.bulk.prefetch.L2.global [%0], %1;" ::"l"(p), "r"(bytes) : "memory");
}
__device__ __forceinline__ void bar_sync(int id, int n) { asm volatile("bar.sync %0, %1;" ::"r"(id), "r"(n) : "memory"); }
__device__ __forceinline__ void bar_arrive(int id, int n) { asm volatile("bar.arrive %0, %1;" ::"r"(id), "r"(n) : "memory"); }
__device__ __forceinline__ void wg_fence() { asm volatile("wgmma.fence.sync.aligned;" ::: "memory"); }
__device__ __forceinline__ void wg_commit() { asm volatile("wgmma.commit_group.sync.aligned;" ::: "memory"); }
template <int N>
__device__ __forceinline__ void wg_wait() { asm volatile("wgmma.wait_group.sync.aligned %0;" ::"n"(N) : "memory"); }

__device__ __forceinline__ uint64_t make_desc(uint32_t addr, uint32_t lbo, uint32_t sbo, uint64_t swz) {
    return (uint64_t)((addr & 0x3FFFF) >> 4) | ((uint64_t)(lbo >> 4) << 16) | ((uint64_t)(sbo >> 4) << 32) | (swz << 62);
}

#define ACC8(a, o) "+f"(a[o]), "+f"(a[o + 1]), "+f"(a[o + 2]), "+f"(a[o + 3]), "+f"(a[o + 4]), "+f"(a[o + 5]), "+f"(a[o + 6]), "+f"(a[o + 7])
constexpr uint32_t DHI128 = (1024u >> 4) | (1u << 30);
constexpr uint32_t DHI64 = (512u >> 4) | (2u << 30);
__device__ __forceinline__ void wgmma_n128_rs(float (&d)[64], const uint32_t* a, uint32_t db, int scale_d) {
    asm volatile(
        "{\n.reg .pred p;\n.reg .b64 dd;\nsetp.ne.b32 p, %69, 0;\nmov.b64 dd, {%68, %70};\n"
        "wgmma.mma_async.sync.aligned.m64n128k16.f32.bf16.bf16 "
        "{%0,%1,%2,%3,%4,%5,%6,%7,%8,%9,%10,%11,%12,%13,%14,%15,%16,%17,%18,%19,%20,%21,%22,%23,%24,%25,%26,%27,%28,%29,%30,%31,"
        "%32,%33,%34,%35,%36,%37,%38,%39,%40,%41,%42,%43,%44,%45,%46,%47,%48,%49,%50,%51,%52,%53,%54,%55,%56,%57,%58,%59,%60,%61,%62,%63},"
        "{%64,%65,%66,%67}, dd, p, 1, 1, 1;\n}"
        : ACC8(d, 0), ACC8(d, 8), ACC8(d, 16), ACC8(d, 24), ACC8(d, 32), ACC8(d, 40), ACC8(d, 48), ACC8(d, 56)
        : "r"(a[0]), "r"(a[1]), "r"(a[2]), "r"(a[3]), "r"(db), "r"(scale_d), "n"(DHI128));
}
template <uint32_t HI>
__device__ __forceinline__ void wgmma_n64_rs(float (&d)[32], const uint32_t* a, uint32_t db, int scale_d) {
    asm volatile(
        "{\n.reg .pred p;\n.reg .b64 dd;\nsetp.ne.b32 p, %37, 0;\nmov.b64 dd, {%36, %38};\n"
        "wgmma.mma_async.sync.aligned.m64n64k16.f32.bf16.bf16 "
        "{%0,%1,%2,%3,%4,%5,%6,%7,%8,%9,%10,%11,%12,%13,%14,%15,%16,%17,%18,%19,%20,%21,%22,%23,%24,%25,%26,%27,%28,%29,%30,%31},"
        "{%32,%33,%34,%35}, dd, p, 1, 1, 1;\n}"
        : ACC8(d, 0), ACC8(d, 8), ACC8(d, 16), ACC8(d, 24)
        : "r"(a[0]), "r"(a[1]), "r"(a[2]), "r"(a[3]), "r"(db), "r"(scale_d), "n"(HI));
}
__device__ __forceinline__ void wgmma_n64_ss_tt(float (&d)[32], uint64_t da, uint64_t db, int scale_d) {
    asm volatile(
        "{\n.reg .pred p;\nsetp.ne.b32 p, %34, 0;\n"
        "wgmma.mma_async.sync.aligned.m64n64k16.f32.bf16.bf16 "
        "{%0,%1,%2,%3,%4,%5,%6,%7,%8,%9,%10,%11,%12,%13,%14,%15,%16,%17,%18,%19,%20,%21,%22,%23,%24,%25,%26,%27,%28,%29,%30,%31},"
        "%32, %33, p, 1, 1, 1, 1;\n}"
        : ACC8(d, 0), ACC8(d, 8), ACC8(d, 16), ACC8(d, 24)
        : "l"(da), "l"(db), "r"(scale_d));
}
__device__ __forceinline__ void wgmma_n8_ss_tn(float (&d)[4], uint64_t da, uint64_t db, int scale_d) {
    asm volatile(
        "{\n.reg .pred p;\nsetp.ne.b32 p, %6, 0;\n"
        "wgmma.mma_async.sync.aligned.m64n8k16.f32.bf16.bf16 {%0,%1,%2,%3}, %4, %5, p, 1, 1, 1, 0;\n}"
        : "+f"(d[0]), "+f"(d[1]), "+f"(d[2]), "+f"(d[3])
        : "l"(da), "l"(db), "r"(scale_d));
}
template <int N>
__device__ __forceinline__ void acc_fence(float (&d)[N]) {
#pragma unroll
    for (int i = 0; i < N; i++) asm volatile("" : "+f"(d[i])::"memory");
}
__device__ __forceinline__ void mma16816(float (&c)[4], const uint32_t* a, uint32_t b0, uint32_t b1) {
    asm volatile(
        "mma.sync.aligned.m16n8k16.row.col.f32.bf16.bf16.f32 {%0,%1,%2,%3}, {%4,%5,%6,%7}, {%8,%9}, {%0,%1,%2,%3};"
        : "+f"(c[0]), "+f"(c[1]), "+f"(c[2]), "+f"(c[3])
        : "r"(a[0]), "r"(a[1]), "r"(a[2]), "r"(a[3]), "r"(b0), "r"(b1));
}
__device__ __forceinline__ uint32_t pack_bf16(float lo, float hi) {
    uint32_t r;
    asm("cvt.rn.bf16x2.f32 %0, %1, %2;" : "=r"(r) : "f"(hi), "f"(lo));
    return r;
}
__device__ __forceinline__ float bf_lo(uint32_t v) { return __uint_as_float(v << 16); }
__device__ __forceinline__ float bf_hi(uint32_t v) { return __uint_as_float(v & 0xffff0000u); }
__device__ __forceinline__ float bf16_round(float v) { return __bfloat162float(__float2bfloat16_rn(v)); }
__device__ __forceinline__ float sqrt_fast(float v) {
    float r;
    asm("sqrt.approx.ftz.f32 %0, %1;" : "=f"(r) : "f"(v));
    return r;
}
__device__ __forceinline__ float rcp_fast(float v) {
    float r;
    asm("rcp.approx.ftz.f32 %0, %1;" : "=f"(r) : "f"(v));
    return r;
}
__device__ __forceinline__ float ex2_fast(float v) {
    float r;
    asm("ex2.approx.ftz.f32 %0, %1;" : "=f"(r) : "f"(v));
    return r;
}
struct RowScale { float rho, rl, var; };
__device__ __forceinline__ float phi_f(float a, const RowScale& r) {
    return fmaf(fmaxf(a, 0.f), r.rho, ex2_fast(fminf(a, 0.f) * r.rl) + 1e-6f);
}
__device__ __forceinline__ float swiglu_f(float ga, float ua, const RowScale& r) {
    return (ga * ua) * rcp_fast(fmaf(ex2_fast(-ga * r.rl), r.var, r.var));
}
__device__ __forceinline__ uint4 swiglu8(const float* gp, const float* up, const RowScale& r0, const RowScale& r1) {
    uint4 v;
    v.x = pack_bf16(swiglu_f(gp[0], up[0], r0), swiglu_f(gp[1], up[1], r0));
    v.y = pack_bf16(swiglu_f(gp[2], up[2], r1), swiglu_f(gp[3], up[3], r1));
    v.z = pack_bf16(swiglu_f(gp[4], up[4], r0), swiglu_f(gp[5], up[5], r0));
    v.w = pack_bf16(swiglu_f(gp[6], up[6], r1), swiglu_f(gp[7], up[7], r1));
    v.y = v.y ? v.y : 0x8000u;
    v.w = v.w ? v.w : 0x8000u;
    return v;
}
__device__ __forceinline__ bool frag_stale(const uint4 (&f)[8]) {
    unsigned v = min(f[0].y, f[0].w);
#pragma unroll
    for (int i = 1; i < 8; i++) v = min(v, min(f[i].y, f[i].w));
    return __any_sync(0xffffffffu, v == 0u);
}
__device__ __forceinline__ void st_frag(uint4* p, uint4 v) {
    asm volatile("st.relaxed.gpu.global.v4.u32 [%0], {%1,%2,%3,%4};" ::"l"(p), "r"(v.x), "r"(v.y), "r"(v.z), "r"(v.w) : "memory");
}
__device__ __forceinline__ uint4 ld_frag(const uint4* p) {
    uint4 v;
    asm volatile("ld.relaxed.gpu.global.v4.u32 {%0,%1,%2,%3}, [%4];" : "=r"(v.x), "=r"(v.y), "=r"(v.z), "=r"(v.w) : "l"(p) : "memory");
    return v;
}
__device__ __forceinline__ void red_add2(float* p, float a, float b) {
    asm volatile("red.global.add.v2.f32 [%0], {%1, %2};" ::"l"(p), "f"(a), "f"(b) : "memory");
}
__device__ __forceinline__ void cp_async16(uint32_t dst, const void* src) {
    asm volatile("cp.async.cg.shared.global [%0], [%1], 16;" ::"r"(dst), "l"(src) : "memory");
}

__host__ __device__ constexpr int ring_lap(int u) { return (u * 79) >> 10; }
__host__ __device__ constexpr int ring_slot(int u) { return u - NST * ring_lap(u); }

__device__ __forceinline__ void mainloop128(float (&acc)[64], const uint32_t (&xa)[128], int u0, uint32_t sb,
                                            uint32_t desc128, int lane, int wg, bool last = false) {
    bar_sync(7 + wg, 256);
#pragma unroll
    for (int kb = 0; kb < 8; kb++) {
        const int st = ring_slot(u0 + kb);
        mbar_wait(sb + BAR_FULL + 8 * st, ring_lap(u0 + kb) & 1);
        wg_fence();
        const uint32_t d = desc128 + st * (STAGE_BYTES >> 4);
#pragma unroll
        for (int ks = 0; ks < 4; ks++) wgmma_n128_rs(acc, &xa[(kb * 4 + ks) * 4], d + ks * 128, (kb | ks) != 0);
        wg_commit();
        if (kb == 7 && !(last && wg == 1)) bar_arrive(8 - wg, 256);
        if (kb > 0) {
            wg_wait<1>();
            if (lane < 2) mbar_arrive_cta(sb + BAR_EMPTY + 8 * ring_slot(u0 + kb - 1), lane);
        }
    }
    wg_wait<0>();
    acc_fence(acc);
    if (lane < 2) mbar_arrive_cta(sb + BAR_EMPTY + 8 * ring_slot(u0 + 7), lane);
}
__device__ __forceinline__ void mainloop64x2(float (&a0)[32], float (&a1)[32], const uint32_t (&xa)[128], int u0,
                                             uint32_t sb, uint32_t desc128, int lane, int wg) {
    bar_sync(7 + wg, 256);
#pragma unroll
    for (int kb = 0; kb < 8; kb++) {
        const int st = ring_slot(u0 + kb);
        mbar_wait(sb + BAR_FULL + 8 * st, ring_lap(u0 + kb) & 1);
        wg_fence();
        const uint32_t d = desc128 + st * (STAGE_BYTES >> 4);
        const uint32_t d2 = d + (8192 >> 4) - ((4096u >> 4) << 16);
#pragma unroll
        for (int ks = 0; ks < 4; ks++) {
            wgmma_n64_rs<DHI128>(a0, &xa[(kb * 4 + ks) * 4], d + ks * 128, (kb | ks) != 0);
            wgmma_n64_rs<DHI64>(a1, &xa[(kb * 4 + ks) * 4], d2 + ks * 64, (kb | ks) != 0);
        }
        wg_commit();
        if (kb == 7) bar_arrive(8 - wg, 256);
        if (kb > 0) {
            wg_wait<1>();
            if (lane < 2) mbar_arrive_cta(sb + BAR_EMPTY + 8 * ring_slot(u0 + kb - 1), lane);
        }
    }
    wg_wait<0>();
    acc_fence(a0);
    acc_fence(a1);
    if (lane < 2) mbar_arrive_cta(sb + BAR_EMPTY + 8 * ring_slot(u0 + 7), lane);
}

__global__ void __cluster_dims__(2, 1, 1) __launch_bounds__(384, 1)
fused_kernel(const __grid_constant__ CUtensorMap tm_x, const __grid_constant__ CUtensorMap tm_qkv,
             const __grid_constant__ CUtensorMap tm_w1, const __grid_constant__ CUtensorMap tm_w3,
             const __grid_constant__ CUtensorMap tm_w1h, const __grid_constant__ CUtensorMap tm_w3h,
             const __grid_constant__ CUtensorMap tm_w2, const __grid_constant__ CUtensorMap tm_w2h,
             const __grid_constant__ CUtensorMap tm_wo, const __nv_bfloat16* __restrict__ xg,
             __nv_bfloat16* __restrict__ outg, const char* __restrict__ p_qkv, const char* __restrict__ p_w1,
             const char* __restrict__ p_w3, const char* __restrict__ p_w2, const char* __restrict__ p_wo) {
    extern __shared__ __align__(1024) uint8_t smem[];
    const uint32_t sb = smem_u32(smem);
    const int tid = threadIdx.x;
    const int warp = tid >> 5, lane = tid & 31;
    const int rank = blockIdx.x & 1;
    const int pair = blockIdx.x >> 1;
    const int c = pair & 7;
    const int m = (pair >> 3) * 2 + rank;
    const int m2 = (pair >> 3) * 2 + (c & 1);
    const int j2 = c >> 1;

    TS(tid >> 7, 0);
    if (tid == 256) {
#pragma unroll
        for (int i = 0; i < 8; i++) mbar_init(sb + BAR_XFULL + 8 * i, 1);
        asm volatile("fence.proxy.async.shared::cta;" ::: "memory");
#pragma unroll
        for (int kb = 0; kb < 8; kb++) {
            mbar_expect_tx(sb + BAR_XFULL + 8 * kb, 16384);
            tma_load(sb + (XST0 + kb) * STAGE_BYTES, &tm_x, sb + BAR_XFULL + 8 * kb, kb * 64, m * 128);
        }
        TS(2, 21);
    } else if (tid == 0) {
#pragma unroll
        for (int i = 0; i < NST; i++) mbar_init(sb + BAR_FULL + 8 * i, 1);
        asm volatile("fence.mbarrier_init.release.cluster;" ::: "memory");
    } else if (tid == 32) {
#pragma unroll
        for (int i = 0; i < NST; i++) mbar_init(sb + BAR_EMPTY + 8 * i, 16);
        asm volatile("fence.mbarrier_init.release.cluster;" ::: "memory");
    } else if (tid == 64) {
#pragma unroll
        for (int i = 0; i < 4; i++) mbar_init(sb + BAR_KVREADY + 8 * i, 1);
        mbar_expect_tx(sb + BAR_XCHG, 32768);
        asm volatile("fence.mbarrier_init.release.cluster;" ::: "memory");
    } else if (tid >= 128 && tid < 256) {
        ((uint4*)(smem + OFF_ZERO))[tid - 128] = make_uint4(0, 0, 0, 0);
        ((uint4*)(smem + OFF_ZERO))[tid] = make_uint4(0, 0, 0, 0);
        asm volatile("fence.proxy.async.shared::cta;" ::: "memory");
    } else if (tid == 288) {
        prefetch_tm(&tm_qkv);
        prefetch_tm(rank ? &tm_w3 : &tm_w1);
        prefetch_tm(&tm_w1h);
        prefetch_tm(&tm_w3h);
        prefetch_tm(&tm_w2);
        prefetch_tm(&tm_w2h);
        prefetch_tm(&tm_wo);
    } else if (tid >= 320) {
        ((uint32_t*)(smem + OFF_ONES))[tid - 320] = 0x3F803F80u;
        asm volatile("fence.proxy.async.shared::cta;" ::: "memory");
    }
    __syncthreads();
    TS(tid >> 7, 22);
    asm volatile("barrier.cluster.arrive.relaxed.aligned;\nbarrier.cluster.wait.acquire.aligned;" ::: "memory");

    if (warp >= 8) {
        asm volatile("setmaxnreg.dec.sync.aligned.u32 40;");
        if (warp == 8) {
            if (lane == 0) {
                int st = 0;
                uint32_t lap = 0;
                for (int it = 0; it < 40; it++) {
                    const int tile = it >> 3, kb = it & 7;
                    const uint32_t full = sb + BAR_FULL + 8 * st;
                    mbar_wait(sb + BAR_EMPTY + 8 * st, (st >= XST0) ? (lap & 1) : ((lap & 1) ^ 1));
                    mbar_expect_tx(full, STAGE_BYTES);
                    const uint32_t dst = sb + st * STAGE_BYTES;
                    if (tile == 0) {
                        tma_load_mc(dst + rank * 8192, &tm_qkv, full, 512 + 512 * rank + 64 * c, kb * 64);
                    } else if (tile != 3) {
                        tma_load_mc(dst + rank * 8192, rank ? &tm_w3 : &tm_w1, full, 224 * c + 64 * (tile == 4 ? 2 : tile - 1), kb * 64);
                    } else if (rank == 0) {
                        tma_load_mc(dst, &tm_qkv, full, 64 * c, kb * 64);
                    } else {
                        tma_load_mc(dst + 8192, &tm_w1h, full, 224 * c + 192, kb * 64);
                        tma_load_mc(dst + 12288, &tm_w3h, full, 224 * c + 192, kb * 64);
                    }
                    if (++st == NST) { st = 0; lap++; }
                    if (it == 7) {
                        mbar_wait(sb + BAR_EMPTY + 8 * SCR0, 0);
                        mbar_arrive(sb + BAR_FULL + 8 * SCR0);
                        mbar_wait(sb + BAR_EMPTY + 8 * (SCR0 + 1), 0);
                        mbar_arrive(sb + BAR_FULL + 8 * (SCR0 + 1));
                        st += 2;
                    }
                }
                TS(2, 1);
                mbar_wait(sb + BAR_EPOCH, 0);
                const char* a2b = (const char*)(g_A2 + (size_t)(*(volatile unsigned*)(smem + OFF_EPOCH) & 1) * A2_N +
                                                (size_t)((m2 * 2 + rank) * 18) * 4 * 256);
#pragma unroll 1
                for (int b = 0; b < 18; b++) {
                    {
                        mbar_wait(sb + BAR_EMPTY + 8 * st, (st >= XST0) ? (lap & 1) : ((lap & 1) ^ 1));
                        if (b >= 8) {
                            const char* q = a2b + b * 16384 + 508;
                            unsigned n = 0;
                            while (true) {
                                unsigned v = 0xffffffffu;
#pragma unroll
                                for (int k = 0; k < 8; k++) {
                                    const int off = (b < 10) ? ((k & 1) * 8192 + 4096 + (k | 1) * 512) : (12288 + k * 512);
                                    unsigned x;
                                    asm volatile("ld.relaxed.gpu.global.u32 %0, [%1];" : "=r"(x) : "l"(q + off) : "memory");
                                    v = min(v, x);
                                }
                                if (v != 0u || ++n > 4096) break;
                            }
                        }
                        mbar_expect_tx(sb + BAR_FULL + 8 * st, STAGE_BYTES);
                        asm volatile("cp.async.bulk.shared::cluster.global.mbarrier::complete_tx::bytes [%0], [%1], 16384, [%2];"
                                     ::"r"(sb + st * STAGE_BYTES), "l"(a2b + b * 16384), "r"(sb + BAR_FULL + 8 * st) : "memory");
                        if (++st == NST) { st = 0; lap++; }
                    }
                    const uint32_t full = sb + BAR_FULL + 8 * st;
                    const uint32_t dst = sb + st * STAGE_BYTES;
                    mbar_wait(sb + BAR_EMPTY + 8 * st, (st >= XST0) ? (lap & 1) : ((lap & 1) ^ 1));
                    mbar_expect_tx(full, STAGE_BYTES);
                    if (b < 8 || b >= 14) {
                        const int row = (b < 8) ? 224 * (4 * rank + (b & 3)) + 64 * (b >> 2) : 224 * (4 * rank + b - 14) + 128;
                        tma_load(dst, &tm_w2, full, 128 * j2, row);
                        tma_load(dst + 8192, &tm_w2, full, 128 * j2 + 64, row);
                    } else if (b < 10) {
                        const int row = 224 * (4 * rank + 2 * (b - 8)) + 192;
                        tma_load(dst, &tm_w2h, full, 128 * j2, row);
                        tma_load(dst + 4096, &tm_w2h, full, 128 * j2, row + 224);
                        tma_load(dst + 8192, &tm_w2h, full, 128 * j2 + 64, row);
                        tma_load(dst + 12288, &tm_w2h, full, 128 * j2 + 64, row + 224);
                    } else {
                        const int row = 64 * (4 * rank + (b - 10));
                        tma_load(dst, &tm_wo, full, 128 * j2, row);
                        tma_load(dst + 8192, &tm_wo, full, 128 * j2 + 64, row);
                    }
                    TS(2, 2 + b);
                    if (++st == NST) { st = 0; lap++; }
                }
                mbar_wait(sb + BAR_EMPTY + 8 * XCH0, (lap & 1) ^ 1);
                mbar_wait(sb + BAR_EMPTY + 8 * (XCH0 + 1), (lap & 1) ^ 1);
                mbar_arrive_cta(sb + BAR_XRDY, rank ^ 1);
            }
        } else if (warp < 11) {
            const int wg = warp - 9;
            bar_sync(3 + wg, 160);
            if (lane == 0) asm volatile("red.release.gpu.global.add.u32 [%0], 1;" ::"l"(&g_kvcnt[c]) : "memory");
            TSW(3, wg);
        } else {
            const unsigned epoch = read_epoch();
            if (lane == 0) {
                const unsigned tk = atomicInc(&g_ticket, 127u);
                if (tk == 127u) *(volatile unsigned*)&g_epoch = epoch;
            }
            if (lane == 0) *(volatile unsigned*)(smem + OFF_EPOCH) = epoch;
            __syncwarp();
            if (lane == 0) mbar_arrive(sb + BAR_EPOCH);
            if (lane < 17) g_kvacc[(((epoch & 1) ^ 1) * 8 + c) * 272 + 17 * m + lane] = make_float4(0.f, 0.f, 0.f, 0.f);
            {
                unsigned n = 0;
                while ((int)(ld_acquire(&g_kvcnt[c]) - 32u * epoch) < 0) {
                    __nanosleep(200);
                    if (++n > SPIN_LIMIT) asm volatile("trap;");
                }
            }
            TSW(4, 0);
            const int g = lane >> 2, t = lane & 3;
            const float* ks = (const float*)(g_kvacc + ((epoch & 1) * 8 + c) * 272) + 32 * t + g;
            uint2* kf = (uint2*)(smem + OFF_KVFRAG) + lane;
#pragma unroll 2
            for (int hh = 0; hh < 4; hh++) {
                const float* k = ks + hh * 272;
                const float a0 = __ldcg(k), a1 = __ldcg(k + 16), a2 = __ldcg(k + 128), a3 = __ldcg(k + 144);
                const float b0 = __ldcg(k + 8), b1 = __ldcg(k + 24), b2 = __ldcg(k + 136), b3 = __ldcg(k + 152);
                const float2 z0 = __ldcg((const float2*)(k - g - 30 * t + 256)), z1 = __ldcg((const float2*)(k - g - 30 * t + 264));
                kf[(hh * 3 + 0) * 32] = make_uint2(pack_bf16(a0, a1), pack_bf16(a2, a3));
                kf[(hh * 3 + 1) * 32] = make_uint2(pack_bf16(b0, b1), pack_bf16(b2, b3));
                kf[(hh * 3 + 2) * 32] = make_uint2(pack_bf16(z0.x, z0.y), pack_bf16(z1.x, z1.y));
            }
            __syncwarp();
            if (lane == 0) mbar_arrive(sb + BAR_KVREADY);
            TSW(4, 4);
            if (lane == 0) {
                char* z = (char*)(g_A2 + (size_t)((epoch & 1) ^ 1) * A2_N + (size_t)((m * 2 + (c >> 2)) * 18) * 4 * 256);
                const int cc = c & 3;
#pragma unroll 1
                for (int i = 0; i < 18; i++) {
                    const int blk = (i < 8) ? ((i >> 2) * 4 + cc) * 4 + (i & 3)
                                  : (i < 10) ? (8 + (cc >> 1)) * 4 + 2 * (cc & 1) + (i - 8)
                                  : (i < 14) ? (10 + cc) * 4 + (i - 10) : (14 + cc) * 4 + (i - 14);
                    asm volatile("cp.async.bulk.global.shared::cta.bulk_group [%0], [%1], 4096;"
                                 ::"l"(z + (size_t)blk * 4096), "r"(sb + OFF_ZERO) : "memory");
                }
                asm volatile("cp.async.bulk.commit_group;" ::: "memory");
            }
            if (lane == 0) asm volatile("cp.async.bulk.wait_group 0;" ::: "memory");
        }
    } else {
        asm volatile("setmaxnreg.inc.sync.aligned.u32 232;");
        const int wg = warp >> 2, w = warp & 3;
        const int g = lane >> 2, t = lane & 3;
        float acc[64];
        uint32_t xa[128];
        float rho0, rho1;
        RowScale r0, r1;
        unsigned par;

        TS(wg, 1);
        {
            const int row = wg * 64 + w * 16 + (lane & 7) + ((lane >> 3) & 1) * 8;
            const uint32_t rbase = sb + XST0 * STAGE_BYTES + row * 128;
            const int hi = lane >> 4, r7 = lane & 7;
            float sm[2][4], c0[2][4], c1[2][4];
#pragma unroll
            for (int i = 0; i < 8; i++) { sm[i >> 2][i & 3] = 0.f; c0[i >> 2][i & 3] = 0.f; c1[i >> 2][i & 3] = 0.f; }
            if (wg == 1) bar_arrive(7, 256);
#pragma unroll
            for (int kb = 0; kb < 8; kb++) {
                mbar_wait(sb + BAR_XFULL + 8 * kb, 0);
#pragma unroll
                for (int ks = 0; ks < 4; ks++) {
                    uint32_t* a = &xa[(kb * 4 + ks) * 4];
                    const uint32_t addr = rbase + kb * STAGE_BYTES + (((2 * ks + hi) ^ r7) << 4);
                    asm volatile("ldmatrix.sync.aligned.m8n8.x4.shared.b16 {%0,%1,%2,%3}, [%4];"
                                 : "=r"(a[0]), "=r"(a[1]), "=r"(a[2]), "=r"(a[3]) : "r"(addr) : "memory");
                    mma16816(sm[ks & 1], a, 0x3F803F80u, 0x3F803F80u);
                    mma16816(c0[ks & 1], a, a[0], a[2]);
                    mma16816(c1[ks & 1], a, a[1], a[3]);
                }
            }
            TS(wg, 2);
            const float mean0 = (sm[0][0] + sm[1][0]) * (1.f / 512.f);
            const float mean1 = (sm[0][2] + sm[1][2]) * (1.f / 512.f);
            __syncwarp();
            if (lane < 16) mbar_arrive_cta(sb + BAR_EMPTY + 8 * (XST0 + (lane >> 1)), lane & 1);
            const __nv_bfloat162 mb0 = __float2bfloat162_rn(mean0), mb1 = __float2bfloat162_rn(mean1);
#pragma unroll
            for (int i = 0; i < 128; i++) {
                __nv_bfloat162 v = *reinterpret_cast<__nv_bfloat162*>(&xa[i]);
                v = __hsub2(v, (i & 1) ? mb1 : mb0);
                xa[i] = *reinterpret_cast<uint32_t*>(&v);
            }
            const float d0 = (g & 1) ? c0[0][1] + c0[1][1] : c0[0][0] + c0[1][0];
            const float d1 = (g & 1) ? c1[0][3] + c1[1][3] : c1[0][2] + c1[1][2];
            const int src = (lane & ~3) | (g >> 1);
            const float var0 = fmaxf(__shfl_sync(0xffffffffu, d0, src) * (1.f / 512.f) - mean0 * mean0, 0.f);
            const float var1 = fmaxf(__shfl_sync(0xffffffffu, d1, src) * (1.f / 512.f) - mean1 * mean1, 0.f);
            const float sd0 = bf16_round(sqrt_fast(bf16_round(bf16_round(var0) + 1e-5f)));
            const float sd1 = bf16_round(sqrt_fast(bf16_round(bf16_round(var1) + 1e-5f)));
            rho0 = rcp_fast(sd0);
            rho1 = rcp_fast(sd1);
            r0.rho = rho0; r0.rl = rho0 * 1.4426950408889634f; r0.var = sd0 * sd0;
            r1.rho = rho1; r1.rl = rho1 * 1.4426950408889634f; r1.var = sd1 * sd1;
        }

        TS(wg, 3);
        const uint32_t desc128 = ((sb & 0x3FFFF) >> 4) | ((8192u >> 4) << 16);
        const int cc = c & 3;

        {
            mainloop128(acc, xa, 0, sb, desc128, lane, wg);
            TS(wg, 4);
            {
                TS(wg, 24);
                const uint32_t pkb = sb + (SCR0 + wg) * STAGE_BYTES;
                mbar_wait(sb + BAR_FULL + 8 * (SCR0 + wg), 0);
                const uint32_t ra = pkb + (w * 16 + g) * 128 + t * 4;
#pragma unroll
                for (int nb = 0; nb < 8; nb++) {
                    const uint32_t off = (uint32_t)((nb ^ g) << 4);
                    uint32_t p0 = pack_bf16(phi_f(acc[nb * 4], r0), phi_f(acc[nb * 4 + 1], r0));
                    uint32_t p1 = pack_bf16(phi_f(acc[nb * 4 + 2], r1), phi_f(acc[nb * 4 + 3], r1));
                    uint32_t v0 = pack_bf16(acc[32 + nb * 4] * rho0, acc[32 + nb * 4 + 1] * rho0);
                    uint32_t v1 = pack_bf16(acc[32 + nb * 4 + 2] * rho1, acc[32 + nb * 4 + 3] * rho1);
                    asm volatile("st.shared.u32 [%0], %1;" ::"r"(ra + off), "r"(p0) : "memory");
                    asm volatile("st.shared.u32 [%0], %1;" ::"r"(ra + off + 1024), "r"(p1) : "memory");
                    asm volatile("st.shared.u32 [%0], %1;" ::"r"(ra + off + 8192), "r"(v0) : "memory");
                    asm volatile("st.shared.u32 [%0], %1;" ::"r"(ra + off + 8192 + 1024), "r"(v1) : "memory");
                }
                TS(wg, 25);
                asm volatile("fence.proxy.async.shared::cta;" ::: "memory");
                bar_sync(1 + wg, 128);
                TS(wg, 26);
                const uint64_t da = make_desc(pkb, 8192, 1024, 1);
                const uint64_t db = make_desc(pkb + 8192, 8192, 1024, 1);
                const uint64_t d1 = make_desc(sb + OFF_ONES, 128, 128, 0);
                float kva[32], za[4];
                wg_fence();
#pragma unroll
                for (int ks = 0; ks < 4; ks++) {
                    wgmma_n64_ss_tt(kva, da + ks * 128, db + ks * 128, ks != 0);
                    wgmma_n8_ss_tn(za, da + ks * 128, d1, ks != 0);
                }
                wg_commit();
                wg_wait<0>();
                acc_fence(kva);
                acc_fence(za);
                if (lane < 4) mbar_arrive_cta(sb + BAR_EMPTY + 8 * (SCR0 + (lane >> 1)), lane & 1);
                TS(wg, 27);
                float o[8];
#pragma unroll
                for (int i = 0; i < 8; i++)
                    o[i] = (w == 0) ? kva[i] : (w == 1) ? kva[8 + i] : (w == 2) ? kva[16 + i] : kva[24 + i];
                mbar_wait(sb + BAR_EPOCH, 0);
                par = *(volatile unsigned*)(smem + OFF_EPOCH) & 1;
                float* dst = (float*)(g_kvacc + (par * 8 + c) * 272) + w * 272 + g * 16 + 2 * t;
                red_add2(dst, o[0], o[1]);
                red_add2(dst + 128, o[2], o[3]);
                red_add2(dst + 8, o[4], o[5]);
                red_add2(dst + 136, o[6], o[7]);
                if (t == 0) {
                    atomicAdd(dst - g * 15 + 256, za[0]);
                    atomicAdd(dst - g * 15 + 264, za[2]);
                }
            }
            bar_arrive(3 + wg, 160);
            TS(wg, 5);
        }
        uint4* a2w = g_A2 + (size_t)par * A2_N + (size_t)((m * 2 + (c >> 2)) * 18) * 4 * 256 + warp * 32 + lane;
#pragma unroll
        for (int tile = 1; tile < 3; tile++) {
            mainloop128(acc, xa, 2 + 8 * tile, sb, desc128, lane, wg);
            TS(wg, 4 + 2 * tile);
            uint4* dst = a2w + (size_t)((4 * (tile - 1) + cc) * 4) * 256;
#pragma unroll
            for (int ks = 0; ks < 4; ks++) st_frag(dst + ks * 256, swiglu8(&acc[ks * 8], &acc[32 + ks * 8], r0, r1));
            TS(wg, 5 + 2 * tile);
        }
        {
            float qa[32], gu[32];
            mainloop64x2(qa, gu, xa, 26, sb, desc128, lane, wg);
            TS(wg, 10);
            uint4* dst = a2w + (size_t)((8 + (cc >> 1)) * 4 + 2 * (cc & 1)) * 256;
#pragma unroll
            for (int ks = 0; ks < 2; ks++) st_frag(dst + ks * 256, swiglu8(&gu[ks * 8], &gu[16 + ks * 8], r0, r1));
            TS(wg, 13);
            mbar_wait(sb + BAR_KVREADY, 0);
            TS(wg, 14);
            const uint2* kf = (const uint2*)(smem + OFF_KVFRAG);
            dst = a2w + (size_t)((10 + cc) * 4) * 256;
#pragma unroll
            for (int hh = 0; hh < 4; hh++) {
                const float* q = &qa[hh * 8];
                uint32_t a[4];
                a[0] = pack_bf16(phi_f(q[0], r0), phi_f(q[1], r0));
                a[1] = pack_bf16(phi_f(q[2], r1), phi_f(q[3], r1));
                a[2] = pack_bf16(phi_f(q[4], r0), phi_f(q[5], r0));
                a[3] = pack_bf16(phi_f(q[6], r1), phi_f(q[7], r1));
                float n0[4] = {0.f, 0.f, 0.f, 0.f}, n1[4] = {0.f, 0.f, 0.f, 0.f}, dn[4] = {0.f, 0.f, 0.f, 0.f};
                const uint2 b0 = kf[(hh * 3 + 0) * 32 + lane], b1 = kf[(hh * 3 + 1) * 32 + lane],
                            bz = kf[(hh * 3 + 2) * 32 + lane];
                mma16816(n0, a, b0.x, b0.y);
                mma16816(n1, a, b1.x, b1.y);
                mma16816(dn, a, bz.x, bz.y);
                const float i0 = rcp_fast(dn[0] + 1e-6f), i1 = rcp_fast(dn[2] + 1e-6f);
                uint4 v;
                v.x = pack_bf16(n0[0] * i0, n0[1] * i0);
                v.y = pack_bf16(n0[2] * i1, n0[3] * i1);
                v.z = pack_bf16(n1[0] * i0, n1[1] * i0);
                v.w = pack_bf16(n1[2] * i1, n1[3] * i1);
                v.y = v.y ? v.y : 0x8000u;
                v.w = v.w ? v.w : 0x8000u;
                st_frag(dst + hh * 256, v);
            }
            TS(wg, 11);
        }
        const uint4* a2r = g_A2 + (size_t)par * A2_N + (size_t)((m2 * 2 + rank) * 18) * 4 * 256 + warp * 32 + lane;
        uint4 af[2][8];
        {
            mainloop128(acc, xa, 34, sb, desc128, lane, wg, true);
            TS(wg, 12);
            uint4* dst = a2w + (size_t)((14 + cc) * 4) * 256;
#pragma unroll
            for (int ks = 0; ks < 4; ks++) st_frag(dst + ks * 256, swiglu8(&acc[ks * 8], &acc[32 + ks * 8], r0, r1));
            TS(wg, 15);
        }

        {
            float ao[32], ap[32];
            const uint32_t dso = desc128 + rank * 512, dsp = desc128 + (rank ^ 1) * 512;
            TS(wg, 16);
#pragma unroll
            for (int gi = 0; gi < 9; gi++) {
                if (gi == 7) TS(wg, 17);
                uint4(&f)[8] = af[gi & 1];
                const int u0 = 42 + 4 * gi;
#pragma unroll
                for (int bb = 0; bb < 2; bb++) {
                    mbar_wait(sb + BAR_FULL + 8 * ring_slot(u0 + 2 * bb), ring_lap(u0 + 2 * bb) & 1);
                    const uint4* src = (const uint4*)(smem + ring_slot(u0 + 2 * bb) * STAGE_BYTES) + tid;
#pragma unroll
                    for (int ks = 0; ks < 4; ks++) f[bb * 4 + ks] = src[ks * 256];
                }
                {
                    unsigned n = 0;
                    while (frag_stale(f)) {
#pragma unroll
                        for (int i = 0; i < 8; i++) f[i] = ld_frag(a2r + (gi * 8 + i) * 256);
                        if (++n > SPIN_LIMIT) asm volatile("trap;");
                    }
                }
                if (u0 + 2 <= 66 && lane < 4) mbar_arrive(sb + BAR_EMPTY + 8 * ring_slot(u0 + (lane & 2)));
                else if (u0 <= 66 && lane < 2) mbar_arrive(sb + BAR_EMPTY + 8 * ring_slot(u0));
                mbar_wait(sb + BAR_FULL + 8 * ring_slot(u0 + 1), ring_lap(u0 + 1) & 1);
                mbar_wait(sb + BAR_FULL + 8 * ring_slot(u0 + 3), ring_lap(u0 + 3) & 1);
                wg_fence();
#pragma unroll
                for (int i = 0; i < 8; i++) {
                    const uint32_t so = ring_slot(u0 + 1 + 2 * (i >> 2)) * (STAGE_BYTES >> 4) + (i & 3) * 128;
                    const uint32_t* a = reinterpret_cast<const uint32_t*>(&f[i]);
                    wgmma_n64_rs<DHI128>(ap, a, dsp + so, (gi | i) != 0);
                    if (gi < 7) wgmma_n64_rs<DHI128>(ao, a, dso + so, (gi | i) != 0);
                }
                wg_commit();
                if (gi > 0 && gi < 8) {
                    wg_wait<1>();
                    if (u0 - 1 <= 66 && lane < 4) mbar_arrive(sb + BAR_EMPTY + 8 * ring_slot(u0 - 3 + (lane & 2)));
                }
            }
#pragma unroll
            for (int i = 0; i < 16; i++)
                wgmma_n64_rs<DHI128>(ao, reinterpret_cast<const uint32_t*>(&af[(7 + (i >> 3)) & 1][i & 7]),
                                     dso + ring_slot(71 + 2 * (i >> 2)) * (STAGE_BYTES >> 4) + (i & 3) * 128, 1);
            wg_commit();
            const int row0 = m2 * 128 + wg * 64 + w * 16 + g;
            const int col0 = j2 * 128 + rank * 64 + 2 * t;
            uint32_t xr[16];
#pragma unroll
            for (int nb = 0; nb < 8; nb++) {
                xr[2 * nb] = __ldg((const uint32_t*)(xg + (size_t)row0 * 512 + col0 + nb * 8));
                xr[2 * nb + 1] = __ldg((const uint32_t*)(xg + (size_t)(row0 + 8) * 512 + col0 + nb * 8));
            }
            uint32_t rdst, rbar;
            asm volatile("mapa.shared::cluster.u32 %0, %1, %2;"
                         : "=r"(rdst) : "r"(sb + (XCH0 + wg) * STAGE_BYTES + (tid & 127) * 16), "r"(rank ^ 1));
            asm volatile("mapa.shared::cluster.u32 %0, %1, %2;" : "=r"(rbar) : "r"(sb + BAR_XCHG), "r"(rank ^ 1));
            mbar_wait(sb + BAR_XRDY, 0);
            wg_wait<1>();
            acc_fence(ap);
            TS(wg, 18);
#pragma unroll
            for (int i = 0; i < 8; i++)
                asm volatile("st.async.shared::cluster.mbarrier::complete_tx::bytes.v4.f32 [%0], {%1,%2,%3,%4}, [%5];"
                             ::"r"(rdst + i * 2048), "f"(ap[4 * i]), "f"(ap[4 * i + 1]), "f"(ap[4 * i + 2]), "f"(ap[4 * i + 3]),
                             "r"(rbar) : "memory");
            wg_wait<0>();
            acc_fence(ao);
            mbar_wait(sb + BAR_XCHG, 0);
            TS(wg, 19);
            const float4* rx = (const float4*)(smem + (XCH0 + wg) * STAGE_BYTES) + (tid & 127);
#pragma unroll
            for (int nb = 0; nb < 8; nb++) {
                const float4 p = rx[nb * 128];
                const uint32_t o0 = pack_bf16(ao[4 * nb] + p.x + bf_lo(xr[2 * nb]), ao[4 * nb + 1] + p.y + bf_hi(xr[2 * nb]));
                const uint32_t o1 = pack_bf16(ao[4 * nb + 2] + p.z + bf_lo(xr[2 * nb + 1]), ao[4 * nb + 3] + p.w + bf_hi(xr[2 * nb + 1]));
                *(uint32_t*)(outg + (size_t)row0 * 512 + col0 + nb * 8) = o0;
                *(uint32_t*)(outg + (size_t)(row0 + 8) * 512 + col0 + nb * 8) = o1;
            }
        }
        TS(wg, 20);
    }
}

typedef CUresult (*EncodeFn)(CUtensorMap*, CUtensorMapDataType, cuuint32_t, void*, const cuuint64_t*, const cuuint64_t*,
                             const cuuint32_t*, const cuuint32_t*, CUtensorMapInterleave, CUtensorMapSwizzle,
                             CUtensorMapL2promotion, CUtensorMapFloatOOBfill);

void make_map(EncodeFn enc, CUtensorMap* tm, const void* ptr, int rows, int cols, int box_rows, int box_cols,
              CUtensorMapSwizzle swz) {
    cuuint64_t dims[2] = {(cuuint64_t)cols, (cuuint64_t)rows};
    cuuint64_t strides[1] = {(cuuint64_t)cols * 2};
    cuuint32_t box[2] = {(cuuint32_t)box_cols, (cuuint32_t)box_rows};
    cuuint32_t es[2] = {1, 1};
    enc(tm, CU_TENSOR_MAP_DATA_TYPE_BFLOAT16, 2, const_cast<void*>(ptr), dims, strides, box, es,
        CU_TENSOR_MAP_INTERLEAVE_NONE, swz, CU_TENSOR_MAP_L2_PROMOTION_L2_256B, CU_TENSOR_MAP_FLOAT_OOB_FILL_NONE);
}

}

extern "C" void kernel_launch(void* const* d_in, const int* in_sizes, int n_in, void* d_out, int out_size) {
    (void)in_sizes; (void)n_in; (void)out_size;
    static EncodeFn enc = nullptr;
    if (!enc) {
        void* fn = nullptr;
        cudaDriverEntryPointQueryResult qr;
        cudaGetDriverEntryPoint("cuTensorMapEncodeTiled", &fn, cudaEnableDefault, &qr);
        enc = (EncodeFn)fn;
        cudaFuncSetAttribute(fused_kernel, cudaFuncAttributeMaxDynamicSharedMemorySize, SMEM_BYTES);
    }
    const void* x = d_in[0];
    const void* wqkv = d_in[1];
    const void* wo = d_in[2];
    const void* w1 = d_in[4];
    const void* w3 = d_in[5];
    const void* w2 = d_in[6];
    CUtensorMap tx, tqkv, t1, t3, t1h, t3h, t2, t2h, two;
    make_map(enc, &tx, x, 2048, 512, 128, 64, CU_TENSOR_MAP_SWIZZLE_128B);
    make_map(enc, &tqkv, wqkv, 512, 1536, 64, 64, CU_TENSOR_MAP_SWIZZLE_128B);
    make_map(enc, &t1, w1, 512, 1792, 64, 64, CU_TENSOR_MAP_SWIZZLE_128B);
    make_map(enc, &t3, w3, 512, 1792, 64, 64, CU_TENSOR_MAP_SWIZZLE_128B);
    make_map(enc, &t1h, w1, 512, 1792, 64, 32, CU_TENSOR_MAP_SWIZZLE_64B);
    make_map(enc, &t3h, w3, 512, 1792, 64, 32, CU_TENSOR_MAP_SWIZZLE_64B);
    make_map(enc, &t2, w2, 1792, 512, 64, 64, CU_TENSOR_MAP_SWIZZLE_128B);
    make_map(enc, &t2h, w2, 1792, 512, 32, 64, CU_TENSOR_MAP_SWIZZLE_128B);
    make_map(enc, &two, wo, 512, 512, 64, 64, CU_TENSOR_MAP_SWIZZLE_128B);
    fused_kernel<<<128, 384, SMEM_BYTES>>>(tx, tqkv, t1, t3, t1h, t3h, t2, t2h, two, (const __nv_bfloat16*)x,
                                           (__nv_bfloat16*)d_out, (const char*)wqkv, (const char*)w1, (const char*)w3,
                                           (const char*)w2, (const char*)wo);
}
```

```cpp
#include <cuda_runtime.h>
#include <cuda_bf16.h>
#include <cuda.h>
#include <stdint.h>

namespace {

constexpr int NST = 13;
constexpr int STAGE_BYTES = 16384;
constexpr int XST0 = 5;
constexpr int SCR0 = 8;
constexpr int XCH0 = 0;
constexpr int OFF_MISC = NST * STAGE_BYTES;
constexpr int OFF_KVFRAG = OFF_MISC;
constexpr int OFF_ONES = OFF_MISC + 3072;
constexpr int OFF_BARS = OFF_MISC + 3328;
constexpr int BAR_FULL = OFF_BARS;
constexpr int BAR_EMPTY = BAR_FULL + 8 * NST;
constexpr int BAR_XFULL = BAR_EMPTY + 8 * NST;
constexpr int BAR_KVREADY = BAR_XFULL + 64;
constexpr int BAR_XCHG = BAR_KVREADY + 8;
constexpr int BAR_EPOCH = BAR_XCHG + 8;
constexpr int BAR_XRDY = BAR_EPOCH + 8;
constexpr int BAR_HINT = BAR_XRDY + 8;
constexpr int OFF_EPOCH = BAR_HINT + 80;
constexpr int OFF_ZERO = OFF_MISC + 4096;
constexpr int SMEM_BYTES = OFF_MISC + 8192;

constexpr unsigned SPIN_LIMIT = 1u << 24;

constexpr int A2_N = 16 * 2 * 18 * 4 * 256;
__device__ uint4 g_A2[2 * A2_N];
__device__ float4 g_kvacc[2 * 8 * 272];
__device__ unsigned g_kvcnt[8];
__device__ unsigned g_epoch;
__device__ unsigned g_ticket;

#define TS(role, i)
#define TSW(role, i)

__device__ __forceinline__ uint32_t smem_u32(const void* p) { return (uint32_t)__cvta_generic_to_shared(p); }
__device__ __forceinline__ void mbar_init(uint32_t bar, uint32_t cnt) {
    asm volatile("mbarrier.init.shared::cta.b64 [%0], %1;" ::"r"(bar), "r"(cnt) : "memory");
}
__device__ __forceinline__ void mbar_expect_tx(uint32_t bar, uint32_t bytes) {
    asm volatile("mbarrier.arrive.expect_tx.shared::cta.b64 _, [%0], %1;" ::"r"(bar), "r"(bytes) : "memory");
}
__device__ __forceinline__ void mbar_arrive(uint32_t bar) {
    asm volatile("mbarrier.arrive.shared::cta.b64 _, [%0];" ::"r"(bar) : "memory");
}
__device__ __forceinline__ void mbar_arrive_cta(uint32_t bar, uint32_t cta) {
    asm volatile(
        "{\n.reg .b32 ra;\nmapa.shared::cluster.u32 ra, %0, %1;\n"
        "mbarrier.arrive.shared::cluster.b64 _, [ra];\n}" ::"r"(bar), "r"(cta) : "memory");
}
__device__ __forceinline__ void mbar_wait(uint32_t bar, uint32_t parity) {
    asm volatile(
        "{\n.reg .pred p, q;\n.reg .u32 n;\nmov.u32 n, 0;\n"
        "WAIT_%=:\n"
        "mbarrier.try_wait.parity.shared::cta.b64 p, [%0], %1;\n"
        "@p bra.uni DONE_%=;\n"
        "add.u32 n, n, 1;\n"
        "setp.gt.u32 q, n, %2;\n"
        "@q trap;\n"
        "bra.uni WAIT_%=;\n"
        "DONE_%=:\n}"
        ::"r"(bar), "r"(parity), "n"(SPIN_LIMIT) : "memory");
}
__device__ __forceinline__ unsigned ld_acquire(const unsigned* p) {
    unsigned v;
    asm volatile("ld.acquire.gpu.global.u32 %0, [%1];" : "=r"(v) : "l"(p) : "memory");
    return v;
}
__device__ __forceinline__ void st_release(unsigned* p, unsigned v) {
    asm volatile("st.release.gpu.global.u32 [%0], %1;" ::"l"(p), "r"(v) : "memory");
}
__device__ __forceinline__ unsigned read_epoch() {
    return __shfl_sync(0xffffffffu, *(volatile unsigned*)&g_epoch, 0) + 1;
}
__device__ __forceinline__ void tma_load(uint32_t dst, const CUtensorMap* tm, uint32_t bar, int x, int y) {
    asm volatile(
        "cp.async.bulk.tensor.2d.shared::cluster.global.mbarrier::complete_tx::bytes [%0], [%1, {%3, %4}], [%2];"
        ::"r"(dst), "l"(tm), "r"(bar), "r"(x), "r"(y) : "memory");
}
__device__ __forceinline__ void tma_load_mc(uint32_t dst, const CUtensorMap* tm, uint32_t bar, int x, int y) {
    asm volatile(
        "cp.async.bulk.tensor.2d.shared::cluster.global.mbarrier::complete_tx::bytes.multicast::cluster "
        "[%0], [%1, {%3, %4}], [%2], %5;"
        ::"r"(dst), "l"(tm), "r"(bar), "r"(x), "r"(y), "h"((uint16_t)3) : "memory");
}
__device__ __forceinline__ void prefetch_tm(const CUtensorMap* tm) {
    asm volatile("prefetch.tensormap [%0];" ::"l"(tm) : "memory");
}
__device__ __forceinline__ void l2_prefetch(const void* p, uint32_t bytes) {
    asm volatile("cp.async.bulk.prefetch.L2.global [%0], %1;" ::"l"(p), "r"(bytes) : "memory");
}
__device__ __forceinline__ void bar_sync(int id, int n) { asm volatile("bar.sync %0, %1;" ::"r"(id), "r"(n) : "memory"); }
__device__ __forceinline__ void bar_arrive(int id, int n) { asm volatile("bar.arrive %0, %1;" ::"r"(id), "r"(n) : "memory"); }
__device__ __forceinline__ void wg_fence() { asm volatile("wgmma.fence.sync.aligned;" ::: "memory"); }
__device__ __forceinline__ void wg_commit() { asm volatile("wgmma.commit_group.sync.aligned;" ::: "memory"); }
template <int N>
__device__ __forceinline__ void wg_wait() { asm volatile("wgmma.wait_group.sync.aligned %0;" ::"n"(N) : "memory"); }

__device__ __forceinline__ uint64_t make_desc(uint32_t addr, uint32_t lbo, uint32_t sbo, uint64_t swz) {
    return (uint64_t)((addr & 0x3FFFF) >> 4) | ((uint64_t)(lbo >> 4) << 16) | ((uint64_t)(sbo >> 4) << 32) | (swz << 62);
}

#define ACC8(a, o) "+f"(a[o]), "+f"(a[o + 1]), "+f"(a[o + 2]), "+f"(a[o + 3]), "+f"(a[o + 4]), "+f"(a[o + 5]), "+f"(a[o + 6]), "+f"(a[o + 7])
constexpr uint32_t DHI128 = (1024u >> 4) | (1u << 30);
constexpr uint32_t DHI64 = (512u >> 4) | (2u << 30);
__device__ __forceinline__ void wgmma_n128_rs(float (&d)[64], const uint32_t* a, uint32_t db, int scale_d) {
    asm volatile(
        "{\n.reg .pred p;\n.reg .b64 dd;\nsetp.ne.b32 p, %69, 0;\nmov.b64 dd, {%68, %70};\n"
        "wgmma.mma_async.sync.aligned.m64n128k16.f32.bf16.bf16 "
        "{%0,%1,%2,%3,%4,%5,%6,%7,%8,%9,%10,%11,%12,%13,%14,%15,%16,%17,%18,%19,%20,%21,%22,%23,%24,%25,%26,%27,%28,%29,%30,%31,"
        "%32,%33,%34,%35,%36,%37,%38,%39,%40,%41,%42,%43,%44,%45,%46,%47,%48,%49,%50,%51,%52,%53,%54,%55,%56,%57,%58,%59,%60,%61,%62,%63},"
        "{%64,%65,%66,%67}, dd, p, 1, 1, 1;\n}"
        : ACC8(d, 0), ACC8(d, 8), ACC8(d, 16), ACC8(d, 24), ACC8(d, 32), ACC8(d, 40), ACC8(d, 48), ACC8(d, 56)
        : "r"(a[0]), "r"(a[1]), "r"(a[2]), "r"(a[3]), "r"(db), "r"(scale_d), "n"(DHI128));
}
template <uint32_t HI>
__device__ __forceinline__ void wgmma_n64_rs(float (&d)[32], const uint32_t* a, uint32_t db, int scale_d) {
    asm volatile(
        "{\n.reg .pred p;\n.reg .b64 dd;\nsetp.ne.b32 p, %37, 0;\nmov.b64 dd, {%36, %38};\n"
        "wgmma.mma_async.sync.aligned.m64n64k16.f32.bf16.bf16 "
        "{%0,%1,%2,%3,%4,%5,%6,%7,%8,%9,%10,%11,%12,%13,%14,%15,%16,%17,%18,%19,%20,%21,%22,%23,%24,%25,%26,%27,%28,%29,%30,%31},"
        "{%32,%33,%34,%35}, dd, p, 1, 1, 1;\n}"
        : ACC8(d, 0), ACC8(d, 8), ACC8(d, 16), ACC8(d, 24)
        : "r"(a[0]), "r"(a[1]), "r"(a[2]), "r"(a[3]), "r"(db), "r"(scale_d), "n"(HI));
}
__device__ __forceinline__ void wgmma_n64_ss_tt(float (&d)[32], uint64_t da, uint64_t db, int scale_d) {
    asm volatile(
        "{\n.reg .pred p;\nsetp.ne.b32 p, %34, 0;\n"
        "wgmma.mma_async.sync.aligned.m64n64k16.f32.bf16.bf16 "
        "{%0,%1,%2,%3,%4,%5,%6,%7,%8,%9,%10,%11,%12,%13,%14,%15,%16,%17,%18,%19,%20,%21,%22,%23,%24,%25,%26,%27,%28,%29,%30,%31},"
        "%32, %33, p, 1, 1, 1, 1;\n}"
        : ACC8(d, 0), ACC8(d, 8), ACC8(d, 16), ACC8(d, 24)
        : "l"(da), "l"(db), "r"(scale_d));
}
__device__ __forceinline__ void wgmma_n8_ss_tn(float (&d)[4], uint64_t da, uint64_t db, int scale_d) {
    asm volatile(
        "{\n.reg .pred p;\nsetp.ne.b32 p, %6, 0;\n"
        "wgmma.mma_async.sync.aligned.m64n8k16.f32.bf16.bf16 {%0,%1,%2,%3}, %4, %5, p, 1, 1, 1, 0;\n}"
        : "+f"(d[0]), "+f"(d[1]), "+f"(d[2]), "+f"(d[3])
        : "l"(da), "l"(db), "r"(scale_d));
}
template <int N>
__device__ __forceinline__ void acc_fence(float (&d)[N]) {
#pragma unroll
    for (int i = 0; i < N; i++) asm volatile("" : "+f"(d[i])::"memory");
}
__device__ __forceinline__ void mma16816(float (&c)[4], const uint32_t* a, uint32_t b0, uint32_t b1) {
    asm volatile(
        "mma.sync.aligned.m16n8k16.row.col.f32.bf16.bf16.f32 {%0,%1,%2,%3}, {%4,%5,%6,%7}, {%8,%9}, {%0,%1,%2,%3};"
        : "+f"(c[0]), "+f"(c[1]), "+f"(c[2]), "+f"(c[3])
        : "r"(a[0]), "r"(a[1]), "r"(a[2]), "r"(a[3]), "r"(b0), "r"(b1));
}
__device__ __forceinline__ uint32_t pack_bf16(float lo, float hi) {
    uint32_t r;
    asm("cvt.rn.bf16x2.f32 %0, %1, %2;" : "=r"(r) : "f"(hi), "f"(lo));
    return r;
}
__device__ __forceinline__ float bf_lo(uint32_t v) { return __uint_as_float(v << 16); }
__device__ __forceinline__ float bf_hi(uint32_t v) { return __uint_as_float(v & 0xffff0000u); }
__device__ __forceinline__ float bf16_round(float v) { return __bfloat162float(__float2bfloat16_rn(v)); }
__device__ __forceinline__ float sqrt_fast(float v) {
    float r;
    asm("sqrt.approx.ftz.f32 %0, %1;" : "=f"(r) : "f"(v));
    return r;
}
__device__ __forceinline__ float rcp_fast(float v) {
    float r;
    asm("rcp.approx.ftz.f32 %0, %1;" : "=f"(r) : "f"(v));
    return r;
}
__device__ __forceinline__ float ex2_fast(float v) {
    float r;
    asm("ex2.approx.ftz.f32 %0, %1;" : "=f"(r) : "f"(v));
    return r;
}
struct RowScale { float rho, rl, var; };
__device__ __forceinline__ float phi_f(float a, const RowScale& r) {
    return fmaf(fmaxf(a, 0.f), r.rho, ex2_fast(fminf(a, 0.f) * r.rl) + 1e-6f);
}
__device__ __forceinline__ float swiglu_f(float ga, float ua, const RowScale& r) {
    return (ga * ua) * rcp_fast(fmaf(ex2_fast(-ga * r.rl), r.var, r.var));
}
__device__ __forceinline__ uint4 swiglu8(const float* gp, const float* up, const RowScale& r0, const RowScale& r1) {
    uint4 v;
    v.x = pack_bf16(swiglu_f(gp[0], up[0], r0), swiglu_f(gp[1], up[1], r0));
    v.y = pack_bf16(swiglu_f(gp[2], up[2], r1), swiglu_f(gp[3], up[3], r1));
    v.z = pack_bf16(swiglu_f(gp[4], up[4], r0), swiglu_f(gp[5], up[5], r0));
    v.w = pack_bf16(swiglu_f(gp[6], up[6], r1), swiglu_f(gp[7], up[7], r1));
    v.y = v.y ? v.y : 0x8000u;
    v.w = v.w ? v.w : 0x8000u;
    return v;
}
__device__ __forceinline__ bool frag_stale(const uint4 (&f)[8]) {
    unsigned v = min(f[0].y, f[0].w);
#pragma unroll
    for (int i = 1; i < 8; i++) v = min(v, min(f[i].y, f[i].w));
    return __any_sync(0xffffffffu, v == 0u);
}
__device__ __forceinline__ void st_frag(uint4* p, uint4 v) {
    asm volatile("st.relaxed.gpu.global.v4.u32 [%0], {%1,%2,%3,%4};" ::"l"(p), "r"(v.x), "r"(v.y), "r"(v.z), "r"(v.w) : "memory");
}
__device__ __forceinline__ uint4 ld_frag(const uint4* p) {
    uint4 v;
    asm volatile("ld.relaxed.gpu.global.v4.u32 {%0,%1,%2,%3}, [%4];" : "=r"(v.x), "=r"(v.y), "=r"(v.z), "=r"(v.w) : "l"(p) : "memory");
    return v;
}
__device__ __forceinline__ void red_add2(float* p, float a, float b) {
    asm volatile("red.global.add.v2.f32 [%0], {%1, %2};" ::"l"(p), "f"(a), "f"(b) : "memory");
}
__device__ __forceinline__ void cp_async16(uint32_t dst, const void* src) {
    asm volatile("cp.async.cg.shared.global [%0], [%1], 16;" ::"r"(dst), "l"(src) : "memory");
}

__host__ __device__ constexpr int ring_lap(int u) { return (u * 79) >> 10; }
__host__ __device__ constexpr int ring_slot(int u) { return u - NST * ring_lap(u); }

__device__ __forceinline__ void mainloop128(float (&acc)[64], const uint32_t (&xa)[128], int u0, uint32_t sb,
                                            uint32_t desc128, int lane, int wg, bool last = false) {
    bar_sync(7 + wg, 256);
#pragma unroll
    for (int kb = 0; kb < 8; kb++) {
        const int st = ring_slot(u0 + kb);
        mbar_wait(sb + BAR_FULL + 8 * st, ring_lap(u0 + kb) & 1);
        wg_fence();
        const uint32_t d = desc128 + st * (STAGE_BYTES >> 4);
#pragma unroll
        for (int ks = 0; ks < 4; ks++) wgmma_n128_rs(acc, &xa[(kb * 4 + ks) * 4], d + ks * 128, (kb | ks) != 0);
        wg_commit();
        if (kb == 7 && !(last && wg == 1)) bar_arrive(8 - wg, 256);
        if (kb > 0) {
            wg_wait<1>();
            if (lane < 2) mbar_arrive_cta(sb + BAR_EMPTY + 8 * ring_slot(u0 + kb - 1), lane);
        }
    }
    wg_wait<0>();
    acc_fence(acc);
    if (lane < 2) mbar_arrive_cta(sb + BAR_EMPTY + 8 * ring_slot(u0 + 7), lane);
}
__device__ __forceinline__ void mainloop64x2(float (&a0)[32], float (&a1)[32], const uint32_t (&xa)[128], int u0,
                                             uint32_t sb, uint32_t desc128, int lane, int wg) {
    bar_sync(7 + wg, 256);
#pragma unroll
    for (int kb = 0; kb < 8; kb++) {
        const int st = ring_slot(u0 + kb);
        mbar_wait(sb + BAR_FULL + 8 * st, ring_lap(u0 + kb) & 1);
        wg_fence();
        const uint32_t d = desc128 + st * (STAGE_BYTES >> 4);
        const uint32_t d2 = d + (8192 >> 4) - ((4096u >> 4) << 16);
#pragma unroll
        for (int ks = 0; ks < 4; ks++) {
            wgmma_n64_rs<DHI128>(a0, &xa[(kb * 4 + ks) * 4], d + ks * 128, (kb | ks) != 0);
            wgmma_n64_rs<DHI64>(a1, &xa[(kb * 4 + ks) * 4], d2 + ks * 64, (kb | ks) != 0);
        }
        wg_commit();
        if (kb == 7) bar_arrive(8 - wg, 256);
        if (kb > 0) {
            wg_wait<1>();
            if (lane < 2) mbar_arrive_cta(sb + BAR_EMPTY + 8 * ring_slot(u0 + kb - 1), lane);
        }
    }
    wg_wait<0>();
    acc_fence(a0);
    acc_fence(a1);
    if (lane < 2) mbar_arrive_cta(sb + BAR_EMPTY + 8 * ring_slot(u0 + 7), lane);
}

__global__ void __cluster_dims__(2, 1, 1) __launch_bounds__(384, 1)
fused_kernel(const __grid_constant__ CUtensorMap tm_x, const __grid_constant__ CUtensorMap tm_qkv,
             const __grid_constant__ CUtensorMap tm_w1, const __grid_constant__ CUtensorMap tm_w3,
             const __grid_constant__ CUtensorMap tm_w1h, const __grid_constant__ CUtensorMap tm_w3h,
             const __grid_constant__ CUtensorMap tm_w2, const __grid_constant__ CUtensorMap tm_w2h,
             const __grid_constant__ CUtensorMap tm_wo, const __nv_bfloat16* __restrict__ xg,
             __nv_bfloat16* __restrict__ outg, const char* __restrict__ p_qkv, const char* __restrict__ p_w1,
             const char* __restrict__ p_w3, const char* __restrict__ p_w2, const char* __restrict__ p_wo) {
    extern __shared__ __align__(1024) uint8_t smem[];
    const uint32_t sb = smem_u32(smem);
    const int tid = threadIdx.x;
    const int warp = tid >> 5, lane = tid & 31;
    const int rank = blockIdx.x & 1;
    const int pair = blockIdx.x >> 1;
    const int c = pair & 7;
    const int m = (pair >> 3) * 2 + rank;
    const int m2 = (pair >> 3) * 2 + (c & 1);
    const int j2 = c >> 1;

    TS(tid >> 7, 0);
    if (tid == 256) {
#pragma unroll
        for (int i = 0; i < 8; i++) mbar_init(sb + BAR_XFULL + 8 * i, 1);
        asm volatile("fence.proxy.async.shared::cta;" ::: "memory");
#pragma unroll
        for (int kb = 0; kb < 8; kb++) {
            mbar_expect_tx(sb + BAR_XFULL + 8 * kb, 16384);
            tma_load(sb + (XST0 + kb) * STAGE_BYTES, &tm_x, sb + BAR_XFULL + 8 * kb, kb * 64, m * 128);
        }
        TS(2, 21);
    } else if (tid == 0) {
#pragma unroll
        for (int i = 0; i < NST; i++) mbar_init(sb + BAR_FULL + 8 * i, 1);
        asm volatile("fence.mbarrier_init.release.cluster;" ::: "memory");
    } else if (tid == 32) {
#pragma unroll
        for (int i = 0; i < NST; i++) mbar_init(sb + BAR_EMPTY + 8 * i, 16);
        asm volatile("fence.mbarrier_init.release.cluster;" ::: "memory");
    } else if (tid == 64) {
#pragma unroll
        for (int i = 0; i < 14; i++) mbar_init(sb + BAR_KVREADY + 8 * i, 1);
        mbar_expect_tx(sb + BAR_XCHG, 32768);
        asm volatile("fence.mbarrier_init.release.cluster;" ::: "memory");
    } else if (tid >= 128 && tid < 256) {
        ((uint4*)(smem + OFF_ZERO))[tid - 128] = make_uint4(0, 0, 0, 0);
        ((uint4*)(smem + OFF_ZERO))[tid] = make_uint4(0, 0, 0, 0);
        asm volatile("fence.proxy.async.shared::cta;" ::: "memory");
    } else if (tid == 288) {
        prefetch_tm(&tm_qkv);
        prefetch_tm(rank ? &tm_w3 : &tm_w1);
        prefetch_tm(&tm_w1h);
        prefetch_tm(&tm_w3h);
        prefetch_tm(&tm_w2);
        prefetch_tm(&tm_w2h);
        prefetch_tm(&tm_wo);
    } else if (tid >= 320) {
        ((uint32_t*)(smem + OFF_ONES))[tid - 320] = 0x3F803F80u;
        asm volatile("fence.proxy.async.shared::cta;" ::: "memory");
    }
    __syncthreads();
    TS(tid >> 7, 22);
    asm volatile("barrier.cluster.arrive.relaxed.aligned;\nbarrier.cluster.wait.acquire.aligned;" ::: "memory");

    if (warp >= 8) {
        asm volatile("setmaxnreg.dec.sync.aligned.u32 40;");
        if (warp == 8) {
            if (lane == 0) {
                int st = 0;
                uint32_t lap = 0;
                for (int it = 0; it < 40; it++) {
                    const int tile = it >> 3, kb = it & 7;
                    const uint32_t full = sb + BAR_FULL + 8 * st;
                    mbar_wait(sb + BAR_EMPTY + 8 * st, (st >= XST0) ? (lap & 1) : ((lap & 1) ^ 1));
                    mbar_expect_tx(full, STAGE_BYTES);
                    const uint32_t dst = sb + st * STAGE_BYTES;
                    if (tile == 0) {
                        tma_load_mc(dst + rank * 8192, &tm_qkv, full, 512 + 512 * rank + 64 * c, kb * 64);
                    } else if (tile != 3) {
                        tma_load_mc(dst + rank * 8192, rank ? &tm_w3 : &tm_w1, full, 224 * c + 64 * (tile == 4 ? 2 : tile - 1), kb * 64);
                    } else if (rank == 0) {
                        tma_load_mc(dst, &tm_qkv, full, 64 * c, kb * 64);
                    } else {
                        tma_load_mc(dst + 8192, &tm_w1h, full, 224 * c + 192, kb * 64);
                        tma_load_mc(dst + 12288, &tm_w3h, full, 224 * c + 192, kb * 64);
                    }
                    if (++st == NST) { st = 0; lap++; }
                    if (it == 7) {
                        mbar_wait(sb + BAR_EMPTY + 8 * SCR0, 0);
                        mbar_arrive(sb + BAR_FULL + 8 * SCR0);
                        mbar_wait(sb + BAR_EMPTY + 8 * (SCR0 + 1), 0);
                        mbar_arrive(sb + BAR_FULL + 8 * (SCR0 + 1));
                        st += 2;
                    }
                }
                TS(2, 1);
                mbar_wait(sb + BAR_EPOCH, 0);
                const char* a2b = (const char*)(g_A2 + (size_t)(*(volatile unsigned*)(smem + OFF_EPOCH) & 1) * A2_N +
                                                (size_t)((m2 * 2 + rank) * 18) * 4 * 256);
#pragma unroll 1
                for (int b = 0; b < 18; b++) {
                    {
                        mbar_wait(sb + BAR_EMPTY + 8 * st, (st >= XST0) ? (lap & 1) : ((lap & 1) ^ 1));
                        if (b >= 8) mbar_wait(sb + BAR_HINT + 8 * (b - 8), 0);
                        mbar_expect_tx(sb + BAR_FULL + 8 * st, STAGE_BYTES);
                        asm volatile("cp.async.bulk.shared::cluster.global.mbarrier::complete_tx::bytes [%0], [%1], 16384, [%2];"
                                     ::"r"(sb + st * STAGE_BYTES), "l"(a2b + b * 16384), "r"(sb + BAR_FULL + 8 * st) : "memory");
                        if (++st == NST) { st = 0; lap++; }
                    }
                    const uint32_t full = sb + BAR_FULL + 8 * st;
                    const uint32_t dst = sb + st * STAGE_BYTES;
                    mbar_wait(sb + BAR_EMPTY + 8 * st, (st >= XST0) ? (lap & 1) : ((lap & 1) ^ 1));
                    mbar_expect_tx(full, STAGE_BYTES);
                    if (b < 8 || b >= 14) {
                        const int row = (b < 8) ? 224 * (4 * rank + (b & 3)) + 64 * (b >> 2) : 224 * (4 * rank + b - 14) + 128;
                        tma_load(dst, &tm_w2, full, 128 * j2, row);
                        tma_load(dst + 8192, &tm_w2, full, 128 * j2 + 64, row);
                    } else if (b < 10) {
                        const int row = 224 * (4 * rank + 2 * (b - 8)) + 192;
                        tma_load(dst, &tm_w2h, full, 128 * j2, row);
                        tma_load(dst + 4096, &tm_w2h, full, 128 * j2, row + 224);
                        tma_load(dst + 8192, &tm_w2h, full, 128 * j2 + 64, row);
                        tma_load(dst + 12288, &tm_w2h, full, 128 * j2 + 64, row + 224);
                    } else {
                        const int row = 64 * (4 * rank + (b - 10));
                        tma_load(dst, &tm_wo, full, 128 * j2, row);
                        tma_load(dst + 8192, &tm_wo, full, 128 * j2 + 64, row);
                    }
                    TS(2, 2 + b);
                    if (++st == NST) { st = 0; lap++; }
                }
                mbar_wait(sb + BAR_EMPTY + 8 * XCH0, (lap & 1) ^ 1);
                mbar_wait(sb + BAR_EMPTY + 8 * (XCH0 + 1), (lap & 1) ^ 1);
                mbar_arrive_cta(sb + BAR_XRDY, rank ^ 1);
            }
        } else if (warp < 11) {
            const int wg = warp - 9;
            bar_sync(3 + wg, 160);
            if (lane == 0) asm volatile("red.release.gpu.global.add.u32 [%0], 1;" ::"l"(&g_kvcnt[c]) : "memory");
            TSW(3, wg);
        } else {
            const unsigned epoch = read_epoch();
            if (lane == 0) {
                const unsigned tk = atomicInc(&g_ticket, 127u);
                if (tk == 127u) *(volatile unsigned*)&g_epoch = epoch;
            }
            if (lane == 0) *(volatile unsigned*)(smem + OFF_EPOCH) = epoch;
            __syncwarp();
            if (lane == 0) mbar_arrive(sb + BAR_EPOCH);
            if (lane < 17) g_kvacc[(((epoch & 1) ^ 1) * 8 + c) * 272 + 17 * m + lane] = make_float4(0.f, 0.f, 0.f, 0.f);
            {
                unsigned n = 0;
                while ((int)(ld_acquire(&g_kvcnt[c]) - 32u * epoch) < 0) {
                    __nanosleep(200);
                    if (++n > SPIN_LIMIT) asm volatile("trap;");
                }
            }
            TSW(4, 0);
            const int g = lane >> 2, t = lane & 3;
            const float* ks = (const float*)(g_kvacc + ((epoch & 1) * 8 + c) * 272) + 32 * t + g;
            uint2* kf = (uint2*)(smem + OFF_KVFRAG) + lane;
#pragma unroll 2
            for (int hh = 0; hh < 4; hh++) {
                const float* k = ks + hh * 272;
                const float a0 = __ldcg(k), a1 = __ldcg(k + 16), a2 = __ldcg(k + 128), a3 = __ldcg(k + 144);
                const float b0 = __ldcg(k + 8), b1 = __ldcg(k + 24), b2 = __ldcg(k + 136), b3 = __ldcg(k + 152);
                const float2 z0 = __ldcg((const float2*)(k - g - 30 * t + 256)), z1 = __ldcg((const float2*)(k - g - 30 * t + 264));
                kf[(hh * 3 + 0) * 32] = make_uint2(pack_bf16(a0, a1), pack_bf16(a2, a3));
                kf[(hh * 3 + 1) * 32] = make_uint2(pack_bf16(b0, b1), pack_bf16(b2, b3));
                kf[(hh * 3 + 2) * 32] = make_uint2(pack_bf16(z0.x, z0.y), pack_bf16(z1.x, z1.y));
            }
            __syncwarp();
            if (lane == 0) mbar_arrive(sb + BAR_KVREADY);
            TSW(4, 4);
            if (lane == 0) {
                char* z = (char*)(g_A2 + (size_t)((epoch & 1) ^ 1) * A2_N + (size_t)((m * 2 + (c >> 2)) * 18) * 4 * 256);
                const int cc = c & 3;
#pragma unroll 1
                for (int i = 0; i < 18; i++) {
                    const int blk = (i < 8) ? ((i >> 2) * 4 + cc) * 4 + (i & 3)
                                  : (i < 10) ? (8 + (cc >> 1)) * 4 + 2 * (cc & 1) + (i - 8)
                                  : (i < 14) ? (10 + cc) * 4 + (i - 10) : (14 + cc) * 4 + (i - 14);
                    asm volatile("cp.async.bulk.global.shared::cta.bulk_group [%0], [%1], 4096;"
                                 ::"l"(z + (size_t)blk * 4096), "r"(sb + OFF_ZERO) : "memory");
                }
                asm volatile("cp.async.bulk.commit_group;" ::: "memory");
            }
            {
                const char* a2b = (const char*)(g_A2 + (size_t)(epoch & 1) * A2_N + (size_t)((m2 * 2 + rank) * 18) * 4 * 256);
                const int k = lane & 7;
                const char* q0 = a2b + (8 + (lane >> 3)) * 16384 + 508 +
                                 ((lane < 16) ? ((k & 1) * 8192 + 4096 + (k | 1) * 512) : (12288 + k * 512));
                const char* q1 = a2b + (12 + (lane >> 3)) * 16384 + 508 + 12288 + k * 512;
                int nb = 0;
                unsigned n = 0;
                while (nb < 10) {
                    unsigned x0, x1, x2 = 1;
                    asm volatile("ld.relaxed.gpu.global.u32 %0, [%1];" : "=r"(x0) : "l"(q0) : "memory");
                    asm volatile("ld.relaxed.gpu.global.u32 %0, [%1];" : "=r"(x1) : "l"(q1) : "memory");
                    if (lane < 16) asm volatile("ld.relaxed.gpu.global.u32 %0, [%1];" : "=r"(x2) : "l"(q1 + 65536) : "memory");
                    const unsigned r0 = __ballot_sync(0xffffffffu, x0 != 0), r1 = __ballot_sync(0xffffffffu, x1 != 0),
                                   r2 = __ballot_sync(0xffffffffu, x2 != 0);
                    const bool give_up = ++n > 100000;
                    while (nb < 10) {
                        const unsigned r = (nb < 4) ? r0 : (nb < 8) ? r1 : r2;
                        if (((r >> ((nb & 3) * 8)) & 0xff) != 0xff && !give_up) break;
                        if (lane == 0) mbar_arrive(sb + BAR_HINT + 8 * nb);
                        nb++;
                    }
                    if (nb < 6) __nanosleep(100);
                }
            }
            if (lane == 0) asm volatile("cp.async.bulk.wait_group 0;" ::: "memory");
        }
    } else {
        asm volatile("setmaxnreg.inc.sync.aligned.u32 232;");
        const int wg = warp >> 2, w = warp & 3;
        const int g = lane >> 2, t = lane & 3;
        float acc[64];
        uint32_t xa[128];
        float rho0, rho1;
        RowScale r0, r1;
        unsigned par;

        TS(wg, 1);
        {
            const int row = wg * 64 + w * 16 + (lane & 7) + ((lane >> 3) & 1) * 8;
            const uint32_t rbase = sb + XST0 * STAGE_BYTES + row * 128;
            const int hi = lane >> 4, r7 = lane & 7;
            float sm[2][4], c0[2][4], c1[2][4];
#pragma unroll
            for (int i = 0; i < 8; i++) { sm[i >> 2][i & 3] = 0.f; c0[i >> 2][i & 3] = 0.f; c1[i >> 2][i & 3] = 0.f; }
            if (wg == 1) bar_arrive(7, 256);
#pragma unroll
            for (int kb = 0; kb < 8; kb++) {
                mbar_wait(sb + BAR_XFULL + 8 * kb, 0);
#pragma unroll
                for (int ks = 0; ks < 4; ks++) {
                    uint32_t* a = &xa[(kb * 4 + ks) * 4];
                    const uint32_t addr = rbase + kb * STAGE_BYTES + (((2 * ks + hi) ^ r7) << 4);
                    asm volatile("ldmatrix.sync.aligned.m8n8.x4.shared.b16 {%0,%1,%2,%3}, [%4];"
                                 : "=r"(a[0]), "=r"(a[1]), "=r"(a[2]), "=r"(a[3]) : "r"(addr) : "memory");
                    mma16816(sm[ks & 1], a, 0x3F803F80u, 0x3F803F80u);
                    mma16816(c0[ks & 1], a, a[0], a[2]);
                    mma16816(c1[ks & 1], a, a[1], a[3]);
                }
            }
            TS(wg, 2);
            const float mean0 = (sm[0][0] + sm[1][0]) * (1.f / 512.f);
            const float mean1 = (sm[0][2] + sm[1][2]) * (1.f / 512.f);
            __syncwarp();
            if (lane < 16) mbar_arrive_cta(sb + BAR_EMPTY + 8 * (XST0 + (lane >> 1)), lane & 1);
            const __nv_bfloat162 mb0 = __float2bfloat162_rn(mean0), mb1 = __float2bfloat162_rn(mean1);
#pragma unroll
            for (int i = 0; i < 128; i++) {
                __nv_bfloat162 v = *reinterpret_cast<__nv_bfloat162*>(&xa[i]);
                v = __hsub2(v, (i & 1) ? mb1 : mb0);
                xa[i] = *reinterpret_cast<uint32_t*>(&v);
            }
            const float d0 = (g & 1) ? c0[0][1] + c0[1][1] : c0[0][0] + c0[1][0];
            const float d1 = (g & 1) ? c1[0][3] + c1[1][3] : c1[0][2] + c1[1][2];
            const int src = (lane & ~3) | (g >> 1);
            const float var0 = fmaxf(__shfl_sync(0xffffffffu, d0, src) * (1.f / 512.f) - mean0 * mean0, 0.f);
            const float var1 = fmaxf(__shfl_sync(0xffffffffu, d1, src) * (1.f / 512.f) - mean1 * mean1, 0.f);
            const float sd0 = bf16_round(sqrt_fast(bf16_round(bf16_round(var0) + 1e-5f)));
            const float sd1 = bf16_round(sqrt_fast(bf16_round(bf16_round(var1) + 1e-5f)));
            rho0 = rcp_fast(sd0);
            rho1 = rcp_fast(sd1);
            r0.rho = rho0; r0.rl = rho0 * 1.4426950408889634f; r0.var = sd0 * sd0;
            r1.rho = rho1; r1.rl = rho1 * 1.4426950408889634f; r1.var = sd1 * sd1;
        }

        TS(wg, 3);
        const uint32_t desc128 = ((sb & 0x3FFFF) >> 4) | ((8192u >> 4) << 16);
        const int cc = c & 3;

        {
            mainloop128(acc, xa, 0, sb, desc128, lane, wg);
            TS(wg, 4);
            {
                TS(wg, 24);
                const uint32_t pkb = sb + (SCR0 + wg) * STAGE_BYTES;
                mbar_wait(sb + BAR_FULL + 8 * (SCR0 + wg), 0);
                const uint32_t ra = pkb + (w * 16 + g) * 128 + t * 4;
#pragma unroll
                for (int nb = 0; nb < 8; nb++) {
                    const uint32_t off = (uint32_t)((nb ^ g) << 4);
                    uint32_t p0 = pack_bf16(phi_f(acc[nb * 4], r0), phi_f(acc[nb * 4 + 1], r0));
                    uint32_t p1 = pack_bf16(phi_f(acc[nb * 4 + 2], r1), phi_f(acc[nb * 4 + 3], r1));
                    uint32_t v0 = pack_bf16(acc[32 + nb * 4] * rho0, acc[32 + nb * 4 + 1] * rho0);
                    uint32_t v1 = pack_bf16(acc[32 + nb * 4 + 2] * rho1, acc[32 + nb * 4 + 3] * rho1);
                    asm volatile("st.shared.u32 [%0], %1;" ::"r"(ra + off), "r"(p0) : "memory");
                    asm volatile("st.shared.u32 [%0], %1;" ::"r"(ra + off + 1024), "r"(p1) : "memory");
                    asm volatile("st.shared.u32 [%0], %1;" ::"r"(ra + off + 8192), "r"(v0) : "memory");
                    asm volatile("st.shared.u32 [%0], %1;" ::"r"(ra + off + 8192 + 1024), "r"(v1) : "memory");
                }
                TS(wg, 25);
                asm volatile("fence.proxy.async.shared::cta;" ::: "memory");
                bar_sync(1 + wg, 128);
                TS(wg, 26);
                const uint64_t da = make_desc(pkb, 8192, 1024, 1);
                const uint64_t db = make_desc(pkb + 8192, 8192, 1024, 1);
                const uint64_t d1 = make_desc(sb + OFF_ONES, 128, 128, 0);
                float kva[32], za[4];
                wg_fence();
#pragma unroll
                for (int ks = 0; ks < 4; ks++) {
                    wgmma_n64_ss_tt(kva, da + ks * 128, db + ks * 128, ks != 0);
                    wgmma_n8_ss_tn(za, da + ks * 128, d1, ks != 0);
                }
                wg_commit();
                wg_wait<0>();
                acc_fence(kva);
                acc_fence(za);
                if (lane < 4) mbar_arrive_cta(sb + BAR_EMPTY + 8 * (SCR0 + (lane >> 1)), lane & 1);
                TS(wg, 27);
                float o[8];
#pragma unroll
                for (int i = 0; i < 8; i++)
                    o[i] = (w == 0) ? kva[i] : (w == 1) ? kva[8 + i] : (w == 2) ? kva[16 + i] : kva[24 + i];
                mbar_wait(sb + BAR_EPOCH, 0);
                par = *(volatile unsigned*)(smem + OFF_EPOCH) & 1;
                float* dst = (float*)(g_kvacc + (par * 8 + c) * 272) + w * 272 + g * 16 + 2 * t;
                red_add2(dst, o[0], o[1]);
                red_add2(dst + 128, o[2], o[3]);
                red_add2(dst + 8, o[4], o[5]);
                red_add2(dst + 136, o[6], o[7]);
                if (t == 0) {
                    atomicAdd(dst - g * 15 + 256, za[0]);
                    atomicAdd(dst - g * 15 + 264, za[2]);
                }
            }
            bar_arrive(3 + wg, 160);
            TS(wg, 5);
        }
        uint4* a2w = g_A2 + (size_t)par * A2_N + (size_t)((m * 2 + (c >> 2)) * 18) * 4 * 256 + warp * 32 + lane;
#pragma unroll
        for (int tile = 1; tile < 3; tile++) {
            mainloop128(acc, xa, 2 + 8 * tile, sb, desc128, lane, wg);
            TS(wg, 4 + 2 * tile);
            uint4* dst = a2w + (size_t)((4 * (tile - 1) + cc) * 4) * 256;
#pragma unroll
            for (int ks = 0; ks < 4; ks++) st_frag(dst + ks * 256, swiglu8(&acc[ks * 8], &acc[32 + ks * 8], r0, r1));
            TS(wg, 5 + 2 * tile);
        }
        {
            float qa[32], gu[32];
            mainloop64x2(qa, gu, xa, 26, sb, desc128, lane, wg);
            TS(wg, 10);
            uint4* dst = a2w + (size_t)((8 + (cc >> 1)) * 4 + 2 * (cc & 1)) * 256;
#pragma unroll
            for (int ks = 0; ks < 2; ks++) st_frag(dst + ks * 256, swiglu8(&gu[ks * 8], &gu[16 + ks * 8], r0, r1));
            TS(wg, 13);
            mbar_wait(sb + BAR_KVREADY, 0);
            TS(wg, 14);
            const uint2* kf = (const uint2*)(smem + OFF_KVFRAG);
            dst = a2w + (size_t)((10 + cc) * 4) * 256;
#pragma unroll
            for (int hh = 0; hh < 4; hh++) {
                const float* q = &qa[hh * 8];
                uint32_t a[4];
                a[0] = pack_bf16(phi_f(q[0], r0), phi_f(q[1], r0));
                a[1] = pack_bf16(phi_f(q[2], r1), phi_f(q[3], r1));
                a[2] = pack_bf16(phi_f(q[4], r0), phi_f(q[5], r0));
                a[3] = pack_bf16(phi_f(q[6], r1), phi_f(q[7], r1));
                float n0[4] = {0.f, 0.f, 0.f, 0.f}, n1[4] = {0.f, 0.f, 0.f, 0.f}, dn[4] = {0.f, 0.f, 0.f, 0.f};
                const uint2 b0 = kf[(hh * 3 + 0) * 32 + lane], b1 = kf[(hh * 3 + 1) * 32 + lane],
                            bz = kf[(hh * 3 + 2) * 32 + lane];
                mma16816(n0, a, b0.x, b0.y);
                mma16816(n1, a, b1.x, b1.y);
                mma16816(dn, a, bz.x, bz.y);
                const float i0 = rcp_fast(dn[0] + 1e-6f), i1 = rcp_fast(dn[2] + 1e-6f);
                uint4 v;
                v.x = pack_bf16(n0[0] * i0, n0[1] * i0);
                v.y = pack_bf16(n0[2] * i1, n0[3] * i1);
                v.z = pack_bf16(n1[0] * i0, n1[1] * i0);
                v.w = pack_bf16(n1[2] * i1, n1[3] * i1);
                v.y = v.y ? v.y : 0x8000u;
                v.w = v.w ? v.w : 0x8000u;
                st_frag(dst + hh * 256, v);
            }
            TS(wg, 11);
        }
        const uint4* a2r = g_A2 + (size_t)par * A2_N + (size_t)((m2 * 2 + rank) * 18) * 4 * 256 + warp * 32 + lane;
        uint4 af[2][8];
        {
            mainloop128(acc, xa, 34, sb, desc128, lane, wg, true);
            TS(wg, 12);
            uint4* dst = a2w + (size_t)((14 + cc) * 4) * 256;
#pragma unroll
            for (int ks = 0; ks < 4; ks++) st_frag(dst + ks * 256, swiglu8(&acc[ks * 8], &acc[32 + ks * 8], r0, r1));
            TS(wg, 15);
        }

        {
            float ao[32], ap[32];
            const uint32_t dso = desc128 + rank * 512, dsp = desc128 + (rank ^ 1) * 512;
            TS(wg, 16);
#pragma unroll
            for (int gi = 0; gi < 9; gi++) {
                if (gi == 7) TS(wg, 17);
                uint4(&f)[8] = af[gi & 1];
                const int u0 = 42 + 4 * gi;
#pragma unroll
                for (int bb = 0; bb < 2; bb++) {
                    mbar_wait(sb + BAR_FULL + 8 * ring_slot(u0 + 2 * bb), ring_lap(u0 + 2 * bb) & 1);
                    const uint4* src = (const uint4*)(smem + ring_slot(u0 + 2 * bb) * STAGE_BYTES) + tid;
#pragma unroll
                    for (int ks = 0; ks < 4; ks++) f[bb * 4 + ks] = src[ks * 256];
                }
                {
                    unsigned n = 0;
                    while (frag_stale(f)) {
#pragma unroll
                        for (int i = 0; i < 8; i++) f[i] = ld_frag(a2r + (gi * 8 + i) * 256);
                        if (++n > SPIN_LIMIT) asm volatile("trap;");
                    }
                }
                if (u0 + 2 <= 66 && lane < 4) mbar_arrive(sb + BAR_EMPTY + 8 * ring_slot(u0 + (lane & 2)));
                else if (u0 <= 66 && lane < 2) mbar_arrive(sb + BAR_EMPTY + 8 * ring_slot(u0));
                mbar_wait(sb + BAR_FULL + 8 * ring_slot(u0 + 1), ring_lap(u0 + 1) & 1);
                mbar_wait(sb + BAR_FULL + 8 * ring_slot(u0 + 3), ring_lap(u0 + 3) & 1);
                wg_fence();
#pragma unroll
                for (int i = 0; i < 8; i++) {
                    const uint32_t so = ring_slot(u0 + 1 + 2 * (i >> 2)) * (STAGE_BYTES >> 4) + (i & 3) * 128;
                    const uint32_t* a = reinterpret_cast<const uint32_t*>(&f[i]);
                    wgmma_n64_rs<DHI128>(ap, a, dsp + so, (gi | i) != 0);
                    if (gi < 7) wgmma_n64_rs<DHI128>(ao, a, dso + so, (gi | i) != 0);
                }
                wg_commit();
                if (gi > 0 && gi < 8) {
                    wg_wait<1>();
                    if (u0 - 1 <= 66 && lane < 4) mbar_arrive(sb + BAR_EMPTY + 8 * ring_slot(u0 - 3 + (lane & 2)));
                }
            }
#pragma unroll
            for (int i = 0; i < 16; i++)
                wgmma_n64_rs<DHI128>(ao, reinterpret_cast<const uint32_t*>(&af[(7 + (i >> 3)) & 1][i & 7]),
                                     dso + ring_slot(71 + 2 * (i >> 2)) * (STAGE_BYTES >> 4) + (i & 3) * 128, 1);
            wg_commit();
            const int row0 = m2 * 128 + wg * 64 + w * 16 + g;
            const int col0 = j2 * 128 + rank * 64 + 2 * t;
            uint32_t xr[16];
#pragma unroll
            for (int nb = 0; nb < 8; nb++) {
                xr[2 * nb] = __ldg((const uint32_t*)(xg + (size_t)row0 * 512 + col0 + nb * 8));
                xr[2 * nb + 1] = __ldg((const uint32_t*)(xg + (size_t)(row0 + 8) * 512 + col0 + nb * 8));
            }
            uint32_t rdst, rbar;
            asm volatile("mapa.shared::cluster.u32 %0, %1, %2;"
                         : "=r"(rdst) : "r"(sb + (XCH0 + wg) * STAGE_BYTES + (tid & 127) * 16), "r"(rank ^ 1));
            asm volatile("mapa.shared::cluster.u32 %0, %1, %2;" : "=r"(rbar) : "r"(sb + BAR_XCHG), "r"(rank ^ 1));
            mbar_wait(sb + BAR_XRDY, 0);
            wg_wait<1>();
            acc_fence(ap);
            TS(wg, 18);
#pragma unroll
            for (int i = 0; i < 8; i++)
                asm volatile("st.async.shared::cluster.mbarrier::complete_tx::bytes.v4.f32 [%0], {%1,%2,%3,%4}, [%5];"
                             ::"r"(rdst + i * 2048), "f"(ap[4 * i]), "f"(ap[4 * i + 1]), "f"(ap[4 * i + 2]), "f"(ap[4 * i + 3]),
                             "r"(rbar) : "memory");
            wg_wait<0>();
            acc_fence(ao);
            mbar_wait(sb + BAR_XCHG, 0);
            TS(wg, 19);
            const float4* rx = (const float4*)(smem + (XCH0 + wg) * STAGE_BYTES) + (tid & 127);
#pragma unroll
            for (int nb = 0; nb < 8; nb++) {
                const float4 p = rx[nb * 128];
                const uint32_t o0 = pack_bf16(ao[4 * nb] + p.x + bf_lo(xr[2 * nb]), ao[4 * nb + 1] + p.y + bf_hi(xr[2 * nb]));
                const uint32_t o1 = pack_bf16(ao[4 * nb + 2] + p.z + bf_lo(xr[2 * nb + 1]), ao[4 * nb + 3] + p.w + bf_hi(xr[2 * nb + 1]));
                *(uint32_t*)(outg + (size_t)row0 * 512 + col0 + nb * 8) = o0;
                *(uint32_t*)(outg + (size_t)(row0 + 8) * 512 + col0 + nb * 8) = o1;
            }
        }
        TS(wg, 20);
    }
}

typedef CUresult (*EncodeFn)(CUtensorMap*, CUtensorMapDataType, cuuint32_t, void*, const cuuint64_t*, const cuuint64_t*,
                             const cuuint32_t*, const cuuint32_t*, CUtensorMapInterleave, CUtensorMapSwizzle,
                             CUtensorMapL2promotion, CUtensorMapFloatOOBfill);

void make_map(EncodeFn enc, CUtensorMap* tm, const void* ptr, int rows, int cols, int box_rows, int box_cols,
              CUtensorMapSwizzle swz) {
    cuuint64_t dims[2] = {(cuuint64_t)cols, (cuuint64_t)rows};
    cuuint64_t strides[1] = {(cuuint64_t)cols * 2};
    cuuint32_t box[2] = {(cuuint32_t)box_cols, (cuuint32_t)box_rows};
    cuuint32_t es[2] = {1, 1};
    enc(tm, CU_TENSOR_MAP_DATA_TYPE_BFLOAT16, 2, const_cast<void*>(ptr), dims, strides, box, es,
        CU_TENSOR_MAP_INTERLEAVE_NONE, swz, CU_TENSOR_MAP_L2_PROMOTION_L2_256B, CU_TENSOR_MAP_FLOAT_OOB_FILL_NONE);
}

}

extern "C" void kernel_launch(void* const* d_in, const int* in_sizes, int n_in, void* d_out, int out_size) {
    (void)in_sizes; (void)n_in; (void)out_size;
    static EncodeFn enc = nullptr;
    if (!enc) {
        void* fn = nullptr;
        cudaDriverEntryPointQueryResult qr;
        cudaGetDriverEntryPoint("cuTensorMapEncodeTiled", &fn, cudaEnableDefault, &qr);
        enc = (EncodeFn)fn;
        cudaFuncSetAttribute(fused_kernel, cudaFuncAttributeMaxDynamicSharedMemorySize, SMEM_BYTES);
    }
    const void* x = d_in[0];
    const void* wqkv = d_in[1];
    const void* wo = d_in[2];
    const void* w1 = d_in[4];
    const void* w3 = d_in[5];
    const void* w2 = d_in[6];
    CUtensorMap tx, tqkv, t1, t3, t1h, t3h, t2, t2h, two;
    make_map(enc, &tx, x, 2048, 512, 128, 64, CU_TENSOR_MAP_SWIZZLE_128B);
    make_map(enc, &tqkv, wqkv, 512, 1536, 64, 64, CU_TENSOR_MAP_SWIZZLE_128B);
    make_map(enc, &t1, w1, 512, 1792, 64, 64, CU_TENSOR_MAP_SWIZZLE_128B);
    make_map(enc, &t3, w3, 512, 1792, 64, 64, CU_TENSOR_MAP_SWIZZLE_128B);
    make_map(enc, &t1h, w1, 512, 1792, 64, 32, CU_TENSOR_MAP_SWIZZLE_64B);
    make_map(enc, &t3h, w3, 512, 1792, 64, 32, CU_TENSOR_MAP_SWIZZLE_64B);
    make_map(enc, &t2, w2, 1792, 512, 64, 64, CU_TENSOR_MAP_SWIZZLE_128B);
    make_map(enc, &t2h, w2, 1792, 512, 32, 64, CU_TENSOR_MAP_SWIZZLE_128B);
    make_map(enc, &two, wo, 512, 512, 64, 64, CU_TENSOR_MAP_SWIZZLE_128B);
    fused_kernel<<<128, 384, SMEM_BYTES>>>(tx, tqkv, t1, t3, t1h, t3h, t2, t2h, two, (const __nv_bfloat16*)x,
                                           (__nv_bfloat16*)d_out, (const char*)wqkv, (const char*)w1, (const char*)w3,
                                           (const char*)w2, (const char*)wo);
}
```

```cpp
#include <cuda_runtime.h>
#include <cuda_bf16.h>
#include <cuda.h>
#include <stdint.h>

namespace {

constexpr int NST = 13;
constexpr int STAGE_BYTES = 16384;
constexpr int XST0 = 5;
constexpr int SCR0 = 8;
constexpr int OFF_MISC = NST * STAGE_BYTES;
constexpr int OFF_KVFRAG = OFF_MISC;
constexpr int OFF_ONES = OFF_MISC + 3072;
constexpr int OFF_BARS = OFF_MISC + 3328;
constexpr int BAR_FULL = OFF_BARS;
constexpr int BAR_EMPTY = BAR_FULL + 8 * NST;
constexpr int BAR_XFULL = BAR_EMPTY + 8 * NST;
constexpr int BAR_KVREADY = BAR_XFULL + 64;
constexpr int BAR_XCHG = BAR_KVREADY + 8;
constexpr int BAR_EPOCH = BAR_XCHG + 8;
constexpr int BAR_XRDY = BAR_EPOCH + 8;
constexpr int BAR_HINT = BAR_XRDY + 8;
constexpr int OFF_EPOCH = BAR_HINT + 80;
constexpr int OFF_ZERO = OFF_MISC + 4096;
constexpr int SMEM_BYTES = OFF_MISC + 8192;

constexpr unsigned SPIN_LIMIT = 1u << 24;

constexpr int A2_N = 16 * 2 * 18 * 4 * 256;
__device__ uint4 g_A2[2 * A2_N];
__device__ uint4 g_xch[2 * 128 * 2048];
__device__ float4 g_kvacc[2 * 8 * 272];
__device__ unsigned g_kvcnt[8];
__device__ unsigned g_epoch;
__device__ unsigned g_ticket;

#define TS(role, i)
#define TSW(role, i)

__device__ __forceinline__ uint32_t smem_u32(const void* p) { return (uint32_t)__cvta_generic_to_shared(p); }
__device__ __forceinline__ void mbar_init(uint32_t bar, uint32_t cnt) {
    asm volatile("mbarrier.init.shared::cta.b64 [%0], %1;" ::"r"(bar), "r"(cnt) : "memory");
}
__device__ __forceinline__ void mbar_expect_tx(uint32_t bar, uint32_t bytes) {
    asm volatile("mbarrier.arrive.expect_tx.shared::cta.b64 _, [%0], %1;" ::"r"(bar), "r"(bytes) : "memory");
}
__device__ __forceinline__ void mbar_arrive(uint32_t bar) {
    asm volatile("mbarrier.arrive.shared::cta.b64 _, [%0];" ::"r"(bar) : "memory");
}
__device__ __forceinline__ void mbar_arrive_cta(uint32_t bar, uint32_t cta) {
    asm volatile(
        "{\n.reg .b32 ra;\nmapa.shared::cluster.u32 ra, %0, %1;\n"
        "mbarrier.arrive.shared::cluster.b64 _, [ra];\n}" ::"r"(bar), "r"(cta) : "memory");
}
__device__ __forceinline__ void mbar_wait(uint32_t bar, uint32_t parity) {
    asm volatile(
        "{\n.reg .pred p, q;\n.reg .u32 n;\nmov.u32 n, 0;\n"
        "WAIT_%=:\n"
        "mbarrier.try_wait.parity.shared::cta.b64 p, [%0], %1;\n"
        "@p bra.uni DONE_%=;\n"
        "add.u32 n, n, 1;\n"
        "setp.gt.u32 q, n, %2;\n"
        "@q trap;\n"
        "bra.uni WAIT_%=;\n"
        "DONE_%=:\n}"
        ::"r"(bar), "r"(parity), "n"(SPIN_LIMIT) : "memory");
}
__device__ __forceinline__ unsigned ld_acquire(const unsigned* p) {
    unsigned v;
    asm volatile("ld.acquire.gpu.global.u32 %0, [%1];" : "=r"(v) : "l"(p) : "memory");
    return v;
}
__device__ __forceinline__ void st_release(unsigned* p, unsigned v) {
    asm volatile("st.release.gpu.global.u32 [%0], %1;" ::"l"(p), "r"(v) : "memory");
}
__device__ __forceinline__ unsigned read_epoch() {
    return __shfl_sync(0xffffffffu, *(volatile unsigned*)&g_epoch, 0) + 1;
}
__device__ __forceinline__ void tma_load(uint32_t dst, const CUtensorMap* tm, uint32_t bar, int x, int y) {
    asm volatile(
        "cp.async.bulk.tensor.2d.shared::cluster.global.mbarrier::complete_tx::bytes [%0], [%1, {%3, %4}], [%2];"
        ::"r"(dst), "l"(tm), "r"(bar), "r"(x), "r"(y) : "memory");
}
__device__ __forceinline__ void tma_load_mc(uint32_t dst, const CUtensorMap* tm, uint32_t bar, int x, int y) {
    asm volatile(
        "cp.async.bulk.tensor.2d.shared::cluster.global.mbarrier::complete_tx::bytes.multicast::cluster "
        "[%0], [%1, {%3, %4}], [%2], %5;"
        ::"r"(dst), "l"(tm), "r"(bar), "r"(x), "r"(y), "h"((uint16_t)3) : "memory");
}
__device__ __forceinline__ void prefetch_tm(const CUtensorMap* tm) {
    asm volatile("prefetch.tensormap [%0];" ::"l"(tm) : "memory");
}
__device__ __forceinline__ void l2_prefetch(const void* p, uint32_t bytes) {
    asm volatile("cp.async.bulk.prefetch.L2.global [%0], %1;" ::"l"(p), "r"(bytes) : "memory");
}
__device__ __forceinline__ void bar_sync(int id, int n) { asm volatile("bar.sync %0, %1;" ::"r"(id), "r"(n) : "memory"); }
__device__ __forceinline__ void bar_arrive(int id, int n) { asm volatile("bar.arrive %0, %1;" ::"r"(id), "r"(n) : "memory"); }
__device__ __forceinline__ void wg_fence() { asm volatile("wgmma.fence.sync.aligned;" ::: "memory"); }
__device__ __forceinline__ void wg_commit() { asm volatile("wgmma.commit_group.sync.aligned;" ::: "memory"); }
template <int N>
__device__ __forceinline__ void wg_wait() { asm volatile("wgmma.wait_group.sync.aligned %0;" ::"n"(N) : "memory"); }

__device__ __forceinline__ uint64_t make_desc(uint32_t addr, uint32_t lbo, uint32_t sbo, uint64_t swz) {
    return (uint64_t)((addr & 0x3FFFF) >> 4) | ((uint64_t)(lbo >> 4) << 16) | ((uint64_t)(sbo >> 4) << 32) | (swz << 62);
}

#define ACC8(a, o) "+f"(a[o]), "+f"(a[o + 1]), "+f"(a[o + 2]), "+f"(a[o + 3]), "+f"(a[o + 4]), "+f"(a[o + 5]), "+f"(a[o + 6]), "+f"(a[o + 7])
constexpr uint32_t DHI128 = (1024u >> 4) | (1u << 30);
constexpr uint32_t DHI64 = (512u >> 4) | (2u << 30);
__device__ __forceinline__ void wgmma_n128_rs(float (&d)[64], const uint32_t* a, uint32_t db, int scale_d) {
    asm volatile(
        "{\n.reg .pred p;\n.reg .b64 dd;\nsetp.ne.b32 p, %69, 0;\nmov.b64 dd, {%68, %70};\n"
        "wgmma.mma_async.sync.aligned.m64n128k16.f32.bf16.bf16 "
        "{%0,%1,%2,%3,%4,%5,%6,%7,%8,%9,%10,%11,%12,%13,%14,%15,%16,%17,%18,%19,%20,%21,%22,%23,%24,%25,%26,%27,%28,%29,%30,%31,"
        "%32,%33,%34,%35,%36,%37,%38,%39,%40,%41,%42,%43,%44,%45,%46,%47,%48,%49,%50,%51,%52,%53,%54,%55,%56,%57,%58,%59,%60,%61,%62,%63},"
        "{%64,%65,%66,%67}, dd, p, 1, 1, 1;\n}"
        : ACC8(d, 0), ACC8(d, 8), ACC8(d, 16), ACC8(d, 24), ACC8(d, 32), ACC8(d, 40), ACC8(d, 48), ACC8(d, 56)
        : "r"(a[0]), "r"(a[1]), "r"(a[2]), "r"(a[3]), "r"(db), "r"(scale_d), "n"(DHI128));
}
template <uint32_t HI>
__device__ __forceinline__ void wgmma_n64_rs(float (&d)[32], const uint32_t* a, uint32_t db, int scale_d) {
    asm volatile(
        "{\n.reg .pred p;\n.reg .b64 dd;\nsetp.ne.b32 p, %37, 0;\nmov.b64 dd, {%36, %38};\n"
        "wgmma.mma_async.sync.aligned.m64n64k16.f32.bf16.bf16 "
        "{%0,%1,%2,%3,%4,%5,%6,%7,%8,%9,%10,%11,%12,%13,%14,%15,%16,%17,%18,%19,%20,%21,%22,%23,%24,%25,%26,%27,%28,%29,%30,%31},"
        "{%32,%33,%34,%35}, dd, p, 1, 1, 1;\n}"
        : ACC8(d, 0), ACC8(d, 8), ACC8(d, 16), ACC8(d, 24)
        : "r"(a[0]), "r"(a[1]), "r"(a[2]), "r"(a[3]), "r"(db), "r"(scale_d), "n"(HI));
}
__device__ __forceinline__ void wgmma_n64_ss_tt(float (&d)[32], uint64_t da, uint64_t db, int scale_d) {
    asm volatile(
        "{\n.reg .pred p;\nsetp.ne.b32 p, %34, 0;\n"
        "wgmma.mma_async.sync.aligned.m64n64k16.f32.bf16.bf16 "
        "{%0,%1,%2,%3,%4,%5,%6,%7,%8,%9,%10,%11,%12,%13,%14,%15,%16,%17,%18,%19,%20,%21,%22,%23,%24,%25,%26,%27,%28,%29,%30,%31},"
        "%32, %33, p, 1, 1, 1, 1;\n}"
        : ACC8(d, 0), ACC8(d, 8), ACC8(d, 16), ACC8(d, 24)
        : "l"(da), "l"(db), "r"(scale_d));
}
__device__ __forceinline__ void wgmma_n8_ss_tn(float (&d)[4], uint64_t da, uint64_t db, int scale_d) {
    asm volatile(
        "{\n.reg .pred p;\nsetp.ne.b32 p, %6, 0;\n"
        "wgmma.mma_async.sync.aligned.m64n8k16.f32.bf16.bf16 {%0,%1,%2,%3}, %4, %5, p, 1, 1, 1, 0;\n}"
        : "+f"(d[0]), "+f"(d[1]), "+f"(d[2]), "+f"(d[3])
        : "l"(da), "l"(db), "r"(scale_d));
}
template <int N>
__device__ __forceinline__ void acc_fence(float (&d)[N]) {
#pragma unroll
    for (int i = 0; i < N; i++) asm volatile("" : "+f"(d[i])::"memory");
}
__device__ __forceinline__ void mma16816(float (&c)[4], const uint32_t* a, uint32_t b0, uint32_t b1) {
    asm volatile(
        "mma.sync.aligned.m16n8k16.row.col.f32.bf16.bf16.f32 {%0,%1,%2,%3}, {%4,%5,%6,%7}, {%8,%9}, {%0,%1,%2,%3};"
        : "+f"(c[0]), "+f"(c[1]), "+f"(c[2]), "+f"(c[3])
        : "r"(a[0]), "r"(a[1]), "r"(a[2]), "r"(a[3]), "r"(b0), "r"(b1));
}
__device__ __forceinline__ uint32_t pack_bf16(float lo, float hi) {
    uint32_t r;
    asm("cvt.rn.bf16x2.f32 %0, %1, %2;" : "=r"(r) : "f"(hi), "f"(lo));
    return r;
}
__device__ __forceinline__ float bf_lo(uint32_t v) { return __uint_as_float(v << 16); }
__device__ __forceinline__ float bf_hi(uint32_t v) { return __uint_as_float(v & 0xffff0000u); }
__device__ __forceinline__ float bf16_round(float v) { return __bfloat162float(__float2bfloat16_rn(v)); }
__device__ __forceinline__ float sqrt_fast(float v) {
    float r;
    asm("sqrt.approx.ftz.f32 %0, %1;" : "=f"(r) : "f"(v));
    return r;
}
__device__ __forceinline__ float rcp_fast(float v) {
    float r;
    asm("rcp.approx.ftz.f32 %0, %1;" : "=f"(r) : "f"(v));
    return r;
}
__device__ __forceinline__ float ex2_fast(float v) {
    float r;
    asm("ex2.approx.ftz.f32 %0, %1;" : "=f"(r) : "f"(v));
    return r;
}
struct RowScale { float rho, rl, var; };
__device__ __forceinline__ float phi_f(float a, const RowScale& r) {
    return fmaf(fmaxf(a, 0.f), r.rho, ex2_fast(fminf(a, 0.f) * r.rl) + 1e-6f);
}
__device__ __forceinline__ float swiglu_f(float ga, float ua, const RowScale& r) {
    return (ga * ua) * rcp_fast(fmaf(ex2_fast(-ga * r.rl), r.var, r.var));
}
__device__ __forceinline__ uint4 swiglu8(const float* gp, const float* up, const RowScale& r0, const RowScale& r1) {
    uint4 v;
    v.x = pack_bf16(swiglu_f(gp[0], up[0], r0), swiglu_f(gp[1], up[1], r0));
    v.y = pack_bf16(swiglu_f(gp[2], up[2], r1), swiglu_f(gp[3], up[3], r1));
    v.z = pack_bf16(swiglu_f(gp[4], up[4], r0), swiglu_f(gp[5], up[5], r0));
    v.w = pack_bf16(swiglu_f(gp[6], up[6], r1), swiglu_f(gp[7], up[7], r1));
    v.y = v.y ? v.y : 0x8000u;
    v.w = v.w ? v.w : 0x8000u;
    return v;
}
__device__ __forceinline__ bool frag_stale(const uint4 (&f)[8]) {
    unsigned v = min(f[0].y, f[0].w);
#pragma unroll
    for (int i = 1; i < 8; i++) v = min(v, min(f[i].y, f[i].w));
    return __any_sync(0xffffffffu, v == 0u);
}
__device__ __forceinline__ void st_frag(uint4* p, uint4 v) {
    asm volatile("st.relaxed.gpu.global.v4.u32 [%0], {%1,%2,%3,%4};" ::"l"(p), "r"(v.x), "r"(v.y), "r"(v.z), "r"(v.w) : "memory");
}
__device__ __forceinline__ uint4 ld_frag(const uint4* p) {
    uint4 v;
    asm volatile("ld.relaxed.gpu.global.v4.u32 {%0,%1,%2,%3}, [%4];" : "=r"(v.x), "=r"(v.y), "=r"(v.z), "=r"(v.w) : "l"(p) : "memory");
    return v;
}
__device__ __forceinline__ void red_add2(float* p, float a, float b) {
    asm volatile("red.global.add.v2.f32 [%0], {%1, %2};" ::"l"(p), "f"(a), "f"(b) : "memory");
}
__device__ __forceinline__ void cp_async16(uint32_t dst, const void* src) {
    asm volatile("cp.async.cg.shared.global [%0], [%1], 16;" ::"r"(dst), "l"(src) : "memory");
}

__host__ __device__ constexpr int ring_lap(int u) { return (u * 79) >> 10; }
__host__ __device__ constexpr int ring_slot(int u) { return u - NST * ring_lap(u); }

__device__ __forceinline__ void mainloop128(float (&acc)[64], const uint32_t (&xa)[128], int u0, uint32_t sb,
                                            uint32_t desc128, int lane, int wg, bool last = false) {
    bar_sync(7 + wg, 256);
#pragma unroll
    for (int kb = 0; kb < 8; kb++) {
        const int st = ring_slot(u0 + kb);
        mbar_wait(sb + BAR_FULL + 8 * st, ring_lap(u0 + kb) & 1);
        wg_fence();
        const uint32_t d = desc128 + st * (STAGE_BYTES >> 4);
#pragma unroll
        for (int ks = 0; ks < 4; ks++) wgmma_n128_rs(acc, &xa[(kb * 4 + ks) * 4], d + ks * 128, (kb | ks) != 0);
        wg_commit();
        if (kb == 7 && !(last && wg == 1)) bar_arrive(8 - wg, 256);
        if (kb > 0) {
            wg_wait<1>();
            if (lane < 2) mbar_arrive_cta(sb + BAR_EMPTY + 8 * ring_slot(u0 + kb - 1), lane);
        }
    }
    wg_wait<0>();
    acc_fence(acc);
    if (lane < 2) mbar_arrive_cta(sb + BAR_EMPTY + 8 * ring_slot(u0 + 7), lane);
}
__device__ __forceinline__ void mainloop64x2(float (&a0)[32], float (&a1)[32], const uint32_t (&xa)[128], int u0,
                                             uint32_t sb, uint32_t desc128, int lane, int wg) {
    bar_sync(7 + wg, 256);
#pragma unroll
    for (int kb = 0; kb < 8; kb++) {
        const int st = ring_slot(u0 + kb);
        mbar_wait(sb + BAR_FULL + 8 * st, ring_lap(u0 + kb) & 1);
        wg_fence();
        const uint32_t d = desc128 + st * (STAGE_BYTES >> 4);
        const uint32_t d2 = d + (8192 >> 4) - ((4096u >> 4) << 16);
#pragma unroll
        for (int ks = 0; ks < 4; ks++) {
            wgmma_n64_rs<DHI128>(a0, &xa[(kb * 4 + ks) * 4], d + ks * 128, (kb | ks) != 0);
            wgmma_n64_rs<DHI64>(a1, &xa[(kb * 4 + ks) * 4], d2 + ks * 64, (kb | ks) != 0);
        }
        wg_commit();
        if (kb == 7) bar_arrive(8 - wg, 256);
        if (kb > 0) {
            wg_wait<1>();
            if (lane < 2) mbar_arrive_cta(sb + BAR_EMPTY + 8 * ring_slot(u0 + kb - 1), lane);
        }
    }
    wg_wait<0>();
    acc_fence(a0);
    acc_fence(a1);
    if (lane < 2) mbar_arrive_cta(sb + BAR_EMPTY + 8 * ring_slot(u0 + 7), lane);
}

__global__ void __cluster_dims__(2, 1, 1) __launch_bounds__(384, 1)
fused_kernel(const __grid_constant__ CUtensorMap tm_x, const __grid_constant__ CUtensorMap tm_qkv,
             const __grid_constant__ CUtensorMap tm_w1, const __grid_constant__ CUtensorMap tm_w3,
             const __grid_constant__ CUtensorMap tm_w1h, const __grid_constant__ CUtensorMap tm_w3h,
             const __grid_constant__ CUtensorMap tm_w2, const __grid_constant__ CUtensorMap tm_w2h,
             const __grid_constant__ CUtensorMap tm_wo, const __nv_bfloat16* __restrict__ xg,
             __nv_bfloat16* __restrict__ outg, const char* __restrict__ p_qkv, const char* __restrict__ p_w1,
             const char* __restrict__ p_w3, const char* __restrict__ p_w2, const char* __restrict__ p_wo) {
    extern __shared__ __align__(1024) uint8_t smem[];
    const uint32_t sb = smem_u32(smem);
    const int tid = threadIdx.x;
    const int warp = tid >> 5, lane = tid & 31;
    const int rank = blockIdx.x & 1;
    const int pair = blockIdx.x >> 1;
    const int c = pair & 7;
    const int m = (pair >> 3) * 2 + rank;
    const int j2 = c >> 1, kh = c & 1;

    TS(tid >> 7, 0);
    if (tid == 256) {
#pragma unroll
        for (int i = 0; i < 8; i++) mbar_init(sb + BAR_XFULL + 8 * i, 1);
        asm volatile("fence.proxy.async.shared::cta;" ::: "memory");
#pragma unroll
        for (int kb = 0; kb < 8; kb++) {
            mbar_expect_tx(sb + BAR_XFULL + 8 * kb, 16384);
            tma_load(sb + (XST0 + kb) * STAGE_BYTES, &tm_x, sb + BAR_XFULL + 8 * kb, kb * 64, m * 128);
        }
        TS(2, 21);
    } else if (tid == 0) {
#pragma unroll
        for (int i = 0; i < NST; i++) mbar_init(sb + BAR_FULL + 8 * i, 1);
        asm volatile("fence.mbarrier_init.release.cluster;" ::: "memory");
    } else if (tid == 32) {
#pragma unroll
        for (int i = 0; i < NST; i++) mbar_init(sb + BAR_EMPTY + 8 * i, 16);
        asm volatile("fence.mbarrier_init.release.cluster;" ::: "memory");
    } else if (tid == 64) {
#pragma unroll
        for (int i = 0; i < 14; i++) mbar_init(sb + BAR_KVREADY + 8 * i, 1);
        asm volatile("fence.mbarrier_init.release.cluster;" ::: "memory");
    } else if (tid >= 128 && tid < 256) {
        ((uint4*)(smem + OFF_ZERO))[tid - 128] = make_uint4(0, 0, 0, 0);
        ((uint4*)(smem + OFF_ZERO))[tid] = make_uint4(0, 0, 0, 0);
        asm volatile("fence.proxy.async.shared::cta;" ::: "memory");
    } else if (tid == 288) {
        prefetch_tm(&tm_qkv);
        prefetch_tm(rank ? &tm_w3 : &tm_w1);
        prefetch_tm(&tm_w1h);
        prefetch_tm(&tm_w3h);
        prefetch_tm(&tm_w2);
        prefetch_tm(&tm_w2h);
        prefetch_tm(&tm_wo);
    } else if (tid >= 320) {
        ((uint32_t*)(smem + OFF_ONES))[tid - 320] = 0x3F803F80u;
        asm volatile("fence.proxy.async.shared::cta;" ::: "memory");
    }
    __syncthreads();
    TS(tid >> 7, 22);
    asm volatile("barrier.cluster.arrive.relaxed.aligned;\nbarrier.cluster.wait.acquire.aligned;" ::: "memory");

    if (warp >= 8) {
        asm volatile("setmaxnreg.dec.sync.aligned.u32 40;");
        if (warp == 8) {
            if (lane == 0) {
                int st = 0;
                uint32_t lap = 0;
                for (int it = 0; it < 40; it++) {
                    const int tile = it >> 3, kb = it & 7;
                    const uint32_t full = sb + BAR_FULL + 8 * st;
                    mbar_wait(sb + BAR_EMPTY + 8 * st, (st >= XST0) ? (lap & 1) : ((lap & 1) ^ 1));
                    mbar_expect_tx(full, STAGE_BYTES);
                    const uint32_t dst = sb + st * STAGE_BYTES;
                    if (tile == 0) {
                        tma_load_mc(dst + rank * 8192, &tm_qkv, full, 512 + 512 * rank + 64 * c, kb * 64);
                    } else if (tile != 3) {
                        tma_load_mc(dst + rank * 8192, rank ? &tm_w3 : &tm_w1, full, 224 * c + 64 * (tile == 4 ? 2 : tile - 1), kb * 64);
                    } else if (rank == 0) {
                        tma_load_mc(dst, &tm_qkv, full, 64 * c, kb * 64);
                    } else {
                        tma_load_mc(dst + 8192, &tm_w1h, full, 224 * c + 192, kb * 64);
                        tma_load_mc(dst + 12288, &tm_w3h, full, 224 * c + 192, kb * 64);
                    }
                    if (++st == NST) { st = 0; lap++; }
                    if (it == 7) {
                        mbar_wait(sb + BAR_EMPTY + 8 * SCR0, 0);
                        mbar_arrive(sb + BAR_FULL + 8 * SCR0);
                        mbar_wait(sb + BAR_EMPTY + 8 * (SCR0 + 1), 0);
                        mbar_arrive(sb + BAR_FULL + 8 * (SCR0 + 1));
                        st += 2;
                    }
                }
                TS(2, 1);
                mbar_wait(sb + BAR_EPOCH, 0);
                const char* a2b = (const char*)(g_A2 + (size_t)(*(volatile unsigned*)(smem + OFF_EPOCH) & 1) * A2_N +
                                                (size_t)((m * 2 + kh) * 18) * 4 * 256);
#pragma unroll 1
                for (int b = 0; b < 18; b++) {
                    {
                        mbar_wait(sb + BAR_EMPTY + 8 * st, (st >= XST0) ? (lap & 1) : ((lap & 1) ^ 1));
                        if (b >= 8) mbar_wait(sb + BAR_HINT + 8 * (b - 8), 0);
                        mbar_expect_tx(sb + BAR_FULL + 8 * st, STAGE_BYTES);
                        asm volatile("cp.async.bulk.shared::cluster.global.mbarrier::complete_tx::bytes [%0], [%1], 16384, [%2];"
                                     ::"r"(sb + st * STAGE_BYTES), "l"(a2b + b * 16384), "r"(sb + BAR_FULL + 8 * st) : "memory");
                        if (++st == NST) { st = 0; lap++; }
                    }
                    const uint32_t full = sb + BAR_FULL + 8 * st;
                    const uint32_t dst = sb + st * STAGE_BYTES;
                    mbar_wait(sb + BAR_EMPTY + 8 * st, (st >= XST0) ? (lap & 1) : ((lap & 1) ^ 1));
                    mbar_expect_tx(full, STAGE_BYTES);
                    const int col = 128 * j2 + 64 * rank;
                    if (b < 8 || b >= 14) {
                        const int row = (b < 8) ? 224 * (4 * kh + (b & 3)) + 64 * (b >> 2) : 224 * (4 * kh + b - 14) + 128;
                        tma_load_mc(dst + rank * 8192, &tm_w2, full, col, row);
                    } else if (b < 10) {
                        const int row = 224 * (4 * kh + 2 * (b - 8)) + 192;
                        tma_load_mc(dst + rank * 8192, &tm_w2h, full, col, row);
                        tma_load_mc(dst + rank * 8192 + 4096, &tm_w2h, full, col, row + 224);
                    } else {
                        tma_load_mc(dst + rank * 8192, &tm_wo, full, col, 64 * (4 * kh + (b - 10)));
                    }
                    TS(2, 2 + b);
                    if (++st == NST) { st = 0; lap++; }
                }
            }
        } else if (warp < 11) {
            const int wg = warp - 9;
            bar_sync(3 + wg, 160);
            if (lane == 0) asm volatile("red.release.gpu.global.add.u32 [%0], 1;" ::"l"(&g_kvcnt[c]) : "memory");
            TSW(3, wg);
        } else {
            const unsigned epoch = read_epoch();
            if (lane == 0) {
                const unsigned tk = atomicInc(&g_ticket, 127u);
                if (tk == 127u) *(volatile unsigned*)&g_epoch = epoch;
            }
            if (lane == 0) *(volatile unsigned*)(smem + OFF_EPOCH) = epoch;
            __syncwarp();
            if (lane == 0) mbar_arrive(sb + BAR_EPOCH);
            if (lane < 17) g_kvacc[(((epoch & 1) ^ 1) * 8 + c) * 272 + 17 * m + lane] = make_float4(0.f, 0.f, 0.f, 0.f);
            {
                unsigned n = 0;
                while ((int)(ld_acquire(&g_kvcnt[c]) - 32u * epoch) < 0) {
                    __nanosleep(200);
                    if (++n > SPIN_LIMIT) asm volatile("trap;");
                }
            }
            TSW(4, 0);
            const int g = lane >> 2, t = lane & 3;
            const float* ks = (const float*)(g_kvacc + ((epoch & 1) * 8 + c) * 272) + 32 * t + g;
            uint2* kf = (uint2*)(smem + OFF_KVFRAG) + lane;
#pragma unroll 2
            for (int hh = 0; hh < 4; hh++) {
                const float* k = ks + hh * 272;
                const float a0 = __ldcg(k), a1 = __ldcg(k + 16), a2 = __ldcg(k + 128), a3 = __ldcg(k + 144);
                const float b0 = __ldcg(k + 8), b1 = __ldcg(k + 24), b2 = __ldcg(k + 136), b3 = __ldcg(k + 152);
                const float2 z0 = __ldcg((const float2*)(k - g - 30 * t + 256)), z1 = __ldcg((const float2*)(k - g - 30 * t + 264));
                kf[(hh * 3 + 0) * 32] = make_uint2(pack_bf16(a0, a1), pack_bf16(a2, a3));
                kf[(hh * 3 + 1) * 32] = make_uint2(pack_bf16(b0, b1), pack_bf16(b2, b3));
                kf[(hh * 3 + 2) * 32] = make_uint2(pack_bf16(z0.x, z0.y), pack_bf16(z1.x, z1.y));
            }
            __syncwarp();
            if (lane == 0) mbar_arrive(sb + BAR_KVREADY);
            TSW(4, 4);
            if (lane == 0) {
                char* z = (char*)(g_A2 + (size_t)((epoch & 1) ^ 1) * A2_N + (size_t)((m * 2 + (c >> 2)) * 18) * 4 * 256);
                const int cc = c & 3;
#pragma unroll 1
                for (int i = 0; i < 18; i++) {
                    const int blk = (i < 8) ? ((i >> 2) * 4 + cc) * 4 + (i & 3)
                                  : (i < 10) ? (8 + (cc >> 1)) * 4 + 2 * (cc & 1) + (i - 8)
                                  : (i < 14) ? (10 + cc) * 4 + (i - 10) : (14 + cc) * 4 + (i - 14);
                    asm volatile("cp.async.bulk.global.shared::cta.bulk_group [%0], [%1], 4096;"
                                 ::"l"(z + (size_t)blk * 4096), "r"(sb + OFF_ZERO) : "memory");
                }
                char* zx = (char*)(g_xch + (size_t)(((epoch & 1) ^ 1) * 128 + blockIdx.x) * 2048);
#pragma unroll 1
                for (int i = 0; i < 8; i++)
                    asm volatile("cp.async.bulk.global.shared::cta.bulk_group [%0], [%1], 4096;"
                                 ::"l"(zx + i * 4096), "r"(sb + OFF_ZERO) : "memory");
                asm volatile("cp.async.bulk.commit_group;" ::: "memory");
            }
            {
                const char* a2b = (const char*)(g_A2 + (size_t)(epoch & 1) * A2_N + (size_t)((m * 2 + kh) * 18) * 4 * 256);
                const int k = lane & 7;
                const char* q0 = a2b + (8 + (lane >> 3)) * 16384 + 508 +
                                 ((lane < 16) ? ((k & 1) * 8192 + 4096 + (k | 1) * 512) : (12288 + k * 512));
                const char* q1 = a2b + (12 + (lane >> 3)) * 16384 + 508 + 12288 + k * 512;
                int nb = 0;
                unsigned n = 0;
                while (nb < 10) {
                    unsigned x0, x1, x2 = 1;
                    asm volatile("ld.relaxed.gpu.global.u32 %0, [%1];" : "=r"(x0) : "l"(q0) : "memory");
                    asm volatile("ld.relaxed.gpu.global.u32 %0, [%1];" : "=r"(x1) : "l"(q1) : "memory");
                    if (lane < 16) asm volatile("ld.relaxed.gpu.global.u32 %0, [%1];" : "=r"(x2) : "l"(q1 + 65536) : "memory");
                    const unsigned r0 = __ballot_sync(0xffffffffu, x0 != 0), r1 = __ballot_sync(0xffffffffu, x1 != 0),
                                   r2 = __ballot_sync(0xffffffffu, x2 != 0);
                    const bool give_up = ++n > 100000;
                    while (nb < 10) {
                        const unsigned r = (nb < 4) ? r0 : (nb < 8) ? r1 : r2;
                        if (((r >> ((nb & 3) * 8)) & 0xff) != 0xff && !give_up) break;
                        if (lane == 0) mbar_arrive(sb + BAR_HINT + 8 * nb);
                        nb++;
                    }
                    if (nb < 6) __nanosleep(100);
                }
            }
            if (lane == 0) asm volatile("cp.async.bulk.wait_group 0;" ::: "memory");
        }
    } else {
        asm volatile("setmaxnreg.inc.sync.aligned.u32 232;");
        const int wg = warp >> 2, w = warp & 3;
        const int g = lane >> 2, t = lane & 3;
        float acc[64];
        uint32_t xa[128];
        float rho0, rho1;
        RowScale r0, r1;
        unsigned par;

        TS(wg, 1);
        {
            const int row = wg * 64 + w * 16 + (lane & 7) + ((lane >> 3) & 1) * 8;
            const uint32_t rbase = sb + XST0 * STAGE_BYTES + row * 128;
            const int hi = lane >> 4, r7 = lane & 7;
            float sm[2][4], c0[2][4], c1[2][4];
#pragma unroll
            for (int i = 0; i < 8; i++) { sm[i >> 2][i & 3] = 0.f; c0[i >> 2][i & 3] = 0.f; c1[i >> 2][i & 3] = 0.f; }
            if (wg == 1) bar_arrive(7, 256);
#pragma unroll
            for (int kb = 0; kb < 8; kb++) {
                mbar_wait(sb + BAR_XFULL + 8 * kb, 0);
#pragma unroll
                for (int ks = 0; ks < 4; ks++) {
                    uint32_t* a = &xa[(kb * 4 + ks) * 4];
                    const uint32_t addr = rbase + kb * STAGE_BYTES + (((2 * ks + hi) ^ r7) << 4);
                    asm volatile("ldmatrix.sync.aligned.m8n8.x4.shared.b16 {%0,%1,%2,%3}, [%4];"
                                 : "=r"(a[0]), "=r"(a[1]), "=r"(a[2]), "=r"(a[3]) : "r"(addr) : "memory");
                    mma16816(sm[ks & 1], a, 0x3F803F80u, 0x3F803F80u);
                    mma16816(c0[ks & 1], a, a[0], a[2]);
                    mma16816(c1[ks & 1], a, a[1], a[3]);
                }
            }
            TS(wg, 2);
            const float mean0 = (sm[0][0] + sm[1][0]) * (1.f / 512.f);
            const float mean1 = (sm[0][2] + sm[1][2]) * (1.f / 512.f);
            __syncwarp();
            if (lane < 16) mbar_arrive_cta(sb + BAR_EMPTY + 8 * (XST0 + (lane >> 1)), lane & 1);
            const __nv_bfloat162 mb0 = __float2bfloat162_rn(mean0), mb1 = __float2bfloat162_rn(mean1);
#pragma unroll
            for (int i = 0; i < 128; i++) {
                __nv_bfloat162 v = *reinterpret_cast<__nv_bfloat162*>(&xa[i]);
                v = __hsub2(v, (i & 1) ? mb1 : mb0);
                xa[i] = *reinterpret_cast<uint32_t*>(&v);
            }
            const float d0 = (g & 1) ? c0[0][1] + c0[1][1] : c0[0][0] + c0[1][0];
            const float d1 = (g & 1) ? c1[0][3] + c1[1][3] : c1[0][2] + c1[1][2];
            const int src = (lane & ~3) | (g >> 1);
            const float var0 = fmaxf(__shfl_sync(0xffffffffu, d0, src) * (1.f / 512.f) - mean0 * mean0, 0.f);
            const float var1 = fmaxf(__shfl_sync(0xffffffffu, d1, src) * (1.f / 512.f) - mean1 * mean1, 0.f);
            const float sd0 = bf16_round(sqrt_fast(bf16_round(bf16_round(var0) + 1e-5f)));
            const float sd1 = bf16_round(sqrt_fast(bf16_round(bf16_round(var1) + 1e-5f)));
            rho0 = rcp_fast(sd0);
            rho1 = rcp_fast(sd1);
            r0.rho = rho0; r0.rl = rho0 * 1.4426950408889634f; r0.var = sd0 * sd0;
            r1.rho = rho1; r1.rl = rho1 * 1.4426950408889634f; r1.var = sd1 * sd1;
        }

        TS(wg, 3);
        const uint32_t desc128 = ((sb & 0x3FFFF) >> 4) | ((8192u >> 4) << 16);
        const int cc = c & 3;

        {
            mainloop128(acc, xa, 0, sb, desc128, lane, wg);
            TS(wg, 4);
            {
                TS(wg, 24);
                const uint32_t pkb = sb + (SCR0 + wg) * STAGE_BYTES;
                mbar_wait(sb + BAR_FULL + 8 * (SCR0 + wg), 0);
                const uint32_t ra = pkb + (w * 16 + g) * 128 + t * 4;
#pragma unroll
                for (int nb = 0; nb < 8; nb++) {
                    const uint32_t off = (uint32_t)((nb ^ g) << 4);
                    uint32_t p0 = pack_bf16(phi_f(acc[nb * 4], r0), phi_f(acc[nb * 4 + 1], r0));
                    uint32_t p1 = pack_bf16(phi_f(acc[nb * 4 + 2], r1), phi_f(acc[nb * 4 + 3], r1));
                    uint32_t v0 = pack_bf16(acc[32 + nb * 4] * rho0, acc[32 + nb * 4 + 1] * rho0);
                    uint32_t v1 = pack_bf16(acc[32 + nb * 4 + 2] * rho1, acc[32 + nb * 4 + 3] * rho1);
                    asm volatile("st.shared.u32 [%0], %1;" ::"r"(ra + off), "r"(p0) : "memory");
                    asm volatile("st.shared.u32 [%0], %1;" ::"r"(ra + off + 1024), "r"(p1) : "memory");
                    asm volatile("st.shared.u32 [%0], %1;" ::"r"(ra + off + 8192), "r"(v0) : "memory");
                    asm volatile("st.shared.u32 [%0], %1;" ::"r"(ra + off + 8192 + 1024), "r"(v1) : "memory");
                }
                TS(wg, 25);
                asm volatile("fence.proxy.async.shared::cta;" ::: "memory");
                bar_sync(1 + wg, 128);
                TS(wg, 26);
                const uint64_t da = make_desc(pkb, 8192, 1024, 1);
                const uint64_t db = make_desc(pkb + 8192, 8192, 1024, 1);
                const uint64_t d1 = make_desc(sb + OFF_ONES, 128, 128, 0);
                float kva[32], za[4];
                wg_fence();
#pragma unroll
                for (int ks = 0; ks < 4; ks++) {
                    wgmma_n64_ss_tt(kva, da + ks * 128, db + ks * 128, ks != 0);
                    wgmma_n8_ss_tn(za, da + ks * 128, d1, ks != 0);
                }
                wg_commit();
                wg_wait<0>();
                acc_fence(kva);
                acc_fence(za);
                if (lane < 4) mbar_arrive_cta(sb + BAR_EMPTY + 8 * (SCR0 + (lane >> 1)), lane & 1);
                TS(wg, 27);
                float o[8];
#pragma unroll
                for (int i = 0; i < 8; i++)
                    o[i] = (w == 0) ? kva[i] : (w == 1) ? kva[8 + i] : (w == 2) ? kva[16 + i] : kva[24 + i];
                mbar_wait(sb + BAR_EPOCH, 0);
                par = *(volatile unsigned*)(smem + OFF_EPOCH) & 1;
                float* dst = (float*)(g_kvacc + (par * 8 + c) * 272) + w * 272 + g * 16 + 2 * t;
                red_add2(dst, o[0], o[1]);
                red_add2(dst + 128, o[2], o[3]);
                red_add2(dst + 8, o[4], o[5]);
                red_add2(dst + 136, o[6], o[7]);
                if (t == 0) {
                    atomicAdd(dst - g * 15 + 256, za[0]);
                    atomicAdd(dst - g * 15 + 264, za[2]);
                }
            }
            bar_arrive(3 + wg, 160);
            TS(wg, 5);
        }
        uint4* a2w = g_A2 + (size_t)par * A2_N + (size_t)((m * 2 + (c >> 2)) * 18) * 4 * 256 + warp * 32 + lane;
#pragma unroll
        for (int tile = 1; tile < 3; tile++) {
            mainloop128(acc, xa, 2 + 8 * tile, sb, desc128, lane, wg);
            TS(wg, 4 + 2 * tile);
            uint4* dst = a2w + (size_t)((4 * (tile - 1) + cc) * 4) * 256;
#pragma unroll
            for (int ks = 0; ks < 4; ks++) st_frag(dst + ks * 256, swiglu8(&acc[ks * 8], &acc[32 + ks * 8], r0, r1));
            TS(wg, 5 + 2 * tile);
        }
        {
            float qa[32], gu[32];
            mainloop64x2(qa, gu, xa, 26, sb, desc128, lane, wg);
            TS(wg, 10);
            uint4* dst = a2w + (size_t)((8 + (cc >> 1)) * 4 + 2 * (cc & 1)) * 256;
#pragma unroll
            for (int ks = 0; ks < 2; ks++) st_frag(dst + ks * 256, swiglu8(&gu[ks * 8], &gu[16 + ks * 8], r0, r1));
            TS(wg, 13);
            mbar_wait(sb + BAR_KVREADY, 0);
            TS(wg, 14);
            const uint2* kf = (const uint2*)(smem + OFF_KVFRAG);
            dst = a2w + (size_t)((10 + cc) * 4) * 256;
#pragma unroll
            for (int hh = 0; hh < 4; hh++) {
                const float* q = &qa[hh * 8];
                uint32_t a[4];
                a[0] = pack_bf16(phi_f(q[0], r0), phi_f(q[1], r0));
                a[1] = pack_bf16(phi_f(q[2], r1), phi_f(q[3], r1));
                a[2] = pack_bf16(phi_f(q[4], r0), phi_f(q[5], r0));
                a[3] = pack_bf16(phi_f(q[6], r1), phi_f(q[7], r1));
                float n0[4] = {0.f, 0.f, 0.f, 0.f}, n1[4] = {0.f, 0.f, 0.f, 0.f}, dn[4] = {0.f, 0.f, 0.f, 0.f};
                const uint2 b0 = kf[(hh * 3 + 0) * 32 + lane], b1 = kf[(hh * 3 + 1) * 32 + lane],
                            bz = kf[(hh * 3 + 2) * 32 + lane];
                mma16816(n0, a, b0.x, b0.y);
                mma16816(n1, a, b1.x, b1.y);
                mma16816(dn, a, bz.x, bz.y);
                const float i0 = rcp_fast(dn[0] + 1e-6f), i1 = rcp_fast(dn[2] + 1e-6f);
                uint4 v;
                v.x = pack_bf16(n0[0] * i0, n0[1] * i0);
                v.y = pack_bf16(n0[2] * i1, n0[3] * i1);
                v.z = pack_bf16(n1[0] * i0, n1[1] * i0);
                v.w = pack_bf16(n1[2] * i1, n1[3] * i1);
                v.y = v.y ? v.y : 0x8000u;
                v.w = v.w ? v.w : 0x8000u;
                st_frag(dst + hh * 256, v);
            }
            TS(wg, 11);
        }
        const uint4* a2r = g_A2 + (size_t)par * A2_N + (size_t)((m * 2 + kh) * 18) * 4 * 256 + warp * 32 + lane;
        uint4 af[3][8];
        {
            mainloop128(acc, xa, 34, sb, desc128, lane, wg, true);
            TS(wg, 12);
            uint4* dst = a2w + (size_t)((14 + cc) * 4) * 256;
#pragma unroll
            for (int ks = 0; ks < 4; ks++) st_frag(dst + ks * 256, swiglu8(&acc[ks * 8], &acc[32 + ks * 8], r0, r1));
            TS(wg, 15);
        }

        {
            float ao[32], ap[32];
            const uint32_t dso = desc128 + kh * 512, dsp = desc128 + (kh ^ 1) * 512;
            TS(wg, 16);
#pragma unroll
            for (int gi = 0; gi < 9; gi++) {
                if (gi == 7) TS(wg, 17);
                uint4(&f)[8] = af[gi % 3];
                const int u0 = 42 + 4 * gi;
#pragma unroll
                for (int bb = 0; bb < 2; bb++) {
                    mbar_wait(sb + BAR_FULL + 8 * ring_slot(u0 + 2 * bb), ring_lap(u0 + 2 * bb) & 1);
                    const uint4* src = (const uint4*)(smem + ring_slot(u0 + 2 * bb) * STAGE_BYTES) + tid;
#pragma unroll
                    for (int ks = 0; ks < 4; ks++) f[bb * 4 + ks] = src[ks * 256];
                }
                {
                    unsigned n = 0;
                    while (frag_stale(f)) {
#pragma unroll
                        for (int i = 0; i < 8; i++) f[i] = ld_frag(a2r + (gi * 8 + i) * 256);
                        if (++n > SPIN_LIMIT) asm volatile("trap;");
                    }
                }
                if (u0 + 2 <= 64 && lane < 4) mbar_arrive_cta(sb + BAR_EMPTY + 8 * ring_slot(u0 + (lane & 2)), lane & 1);
                mbar_wait(sb + BAR_FULL + 8 * ring_slot(u0 + 1), ring_lap(u0 + 1) & 1);
                mbar_wait(sb + BAR_FULL + 8 * ring_slot(u0 + 3), ring_lap(u0 + 3) & 1);
                wg_fence();
#pragma unroll
                for (int i = 0; i < 8; i++) {
                    const uint32_t so = ring_slot(u0 + 1 + 2 * (i >> 2)) * (STAGE_BYTES >> 4) + (i & 3) * 128;
                    const uint32_t* a = reinterpret_cast<const uint32_t*>(&f[i]);
                    wgmma_n64_rs<DHI128>(ap, a, dsp + so, (gi | i) != 0);
                    if (gi < 6) wgmma_n64_rs<DHI128>(ao, a, dso + so, (gi | i) != 0);
                }
                wg_commit();
                if (gi > 0 && gi < 7) {
                    wg_wait<1>();
                    if (lane < 4) mbar_arrive_cta(sb + BAR_EMPTY + 8 * ring_slot(u0 - 3 + (lane & 2)), lane & 1);
                }
            }
#pragma unroll
            for (int i = 0; i < 24; i++)
                wgmma_n64_rs<DHI128>(ao, reinterpret_cast<const uint32_t*>(&af[i >> 3][i & 7]),
                                     dso + ring_slot(67 + 2 * (i >> 2)) * (STAGE_BYTES >> 4) + (i & 3) * 128, 1);
            wg_commit();
            wg_wait<1>();
            acc_fence(ap);
            TS(wg, 18);
            {
                uint4* xo = g_xch + (size_t)(par * 128 + (blockIdx.x ^ 2)) * 2048 + tid;
#pragma unroll
                for (int i = 0; i < 8; i++) {
                    uint4 v = make_uint4(__float_as_uint(ap[4 * i]), __float_as_uint(ap[4 * i + 1]),
                                         __float_as_uint(ap[4 * i + 2]), __float_as_uint(ap[4 * i + 3]));
                    v.y = v.y ? v.y : 0x80000000u;
                    v.w = v.w ? v.w : 0x80000000u;
                    st_frag(xo + i * 256, v);
                }
            }
            const int row0 = m * 128 + wg * 64 + w * 16 + g;
            const int col0 = j2 * 128 + kh * 64 + 2 * t;
            uint32_t xr[16];
#pragma unroll
            for (int nb = 0; nb < 8; nb++) {
                xr[2 * nb] = __ldg((const uint32_t*)(xg + (size_t)row0 * 512 + col0 + nb * 8));
                xr[2 * nb + 1] = __ldg((const uint32_t*)(xg + (size_t)(row0 + 8) * 512 + col0 + nb * 8));
            }
            const uint4* xi = g_xch + (size_t)(par * 128 + blockIdx.x) * 2048 + tid;
            uint4 pin[8];
            {
                unsigned n = 0;
                while (true) {
#pragma unroll
                    for (int i = 0; i < 8; i++) pin[i] = ld_frag(xi + i * 256);
                    if (!frag_stale(pin)) break;
                    if (++n > SPIN_LIMIT) asm volatile("trap;");
                }
            }
            TS(wg, 19);
            wg_wait<0>();
            acc_fence(ao);
#pragma unroll
            for (int nb = 0; nb < 8; nb++) {
                const uint4 p = pin[nb];
                const uint32_t o0 = pack_bf16(ao[4 * nb] + __uint_as_float(p.x) + bf_lo(xr[2 * nb]),
                                              ao[4 * nb + 1] + __uint_as_float(p.y) + bf_hi(xr[2 * nb]));
                const uint32_t o1 = pack_bf16(ao[4 * nb + 2] + __uint_as_float(p.z) + bf_lo(xr[2 * nb + 1]),
                                              ao[4 * nb + 3] + __uint_as_float(p.w) + bf_hi(xr[2 * nb + 1]));
                *(uint32_t*)(outg + (size_t)row0 * 512 + col0 + nb * 8) = o0;
                *(uint32_t*)(outg + (size_t)(row0 + 8) * 512 + col0 + nb * 8) = o1;
            }
        }
        asm volatile("barrier.cluster.arrive.relaxed.aligned;\nbarrier.cluster.wait.aligned;" ::: "memory");
        TS(wg, 20);
    }
}

typedef CUresult (*EncodeFn)(CUtensorMap*, CUtensorMapDataType, cuuint32_t, void*, const cuuint64_t*, const cuuint64_t*,
                             const cuuint32_t*, const cuuint32_t*, CUtensorMapInterleave, CUtensorMapSwizzle,
                             CUtensorMapL2promotion, CUtensorMapFloatOOBfill);

void make_map(EncodeFn enc, CUtensorMap* tm, const void* ptr, int rows, int cols, int box_rows, int box_cols,
              CUtensorMapSwizzle swz) {
    cuuint64_t dims[2] = {(cuuint64_t)cols, (cuuint64_t)rows};
    cuuint64_t strides[1] = {(cuuint64_t)cols * 2};
    cuuint32_t box[2] = {(cuuint32_t)box_cols, (cuuint32_t)box_rows};
    cuuint32_t es[2] = {1, 1};
    enc(tm, CU_TENSOR_MAP_DATA_TYPE_BFLOAT16, 2, const_cast<void*>(ptr), dims, strides, box, es,
        CU_TENSOR_MAP_INTERLEAVE_NONE, swz, CU_TENSOR_MAP_L2_PROMOTION_L2_256B, CU_TENSOR_MAP_FLOAT_OOB_FILL_NONE);
}

}

extern "C" void kernel_launch(void* const* d_in, const int* in_sizes, int n_in, void* d_out, int out_size) {
    (void)in_sizes; (void)n_in; (void)out_size;
    static EncodeFn enc = nullptr;
    if (!enc) {
        void* fn = nullptr;
        cudaDriverEntryPointQueryResult qr;
        cudaGetDriverEntryPoint("cuTensorMapEncodeTiled", &fn, cudaEnableDefault, &qr);
        enc = (EncodeFn)fn;
        cudaFuncSetAttribute(fused_kernel, cudaFuncAttributeMaxDynamicSharedMemorySize, SMEM_BYTES);
    }
    const void* x = d_in[0];
    const void* wqkv = d_in[1];
    const void* wo = d_in[2];
    const void* w1 = d_in[4];
    const void* w3 = d_in[5];
    const void* w2 = d_in[6];
    CUtensorMap tx, tqkv, t1, t3, t1h, t3h, t2, t2h, two;
    make_map(enc, &tx, x, 2048, 512, 128, 64, CU_TENSOR_MAP_SWIZZLE_128B);
    make_map(enc, &tqkv, wqkv, 512, 1536, 64, 64, CU_TENSOR_MAP_SWIZZLE_128B);
    make_map(enc, &t1, w1, 512, 1792, 64, 64, CU_TENSOR_MAP_SWIZZLE_128B);
    make_map(enc, &t3, w3, 512, 1792, 64, 64, CU_TENSOR_MAP_SWIZZLE_128B);
    make_map(enc, &t1h, w1, 512, 1792, 64, 32, CU_TENSOR_MAP_SWIZZLE_64B);
    make_map(enc, &t3h, w3, 512, 1792, 64, 32, CU_TENSOR_MAP_SWIZZLE_64B);
    make_map(enc, &t2, w2, 1792, 512, 64, 64, CU_TENSOR_MAP_SWIZZLE_128B);
    make_map(enc, &t2h, w2, 1792, 512, 32, 64, CU_TENSOR_MAP_SWIZZLE_128B);
    make_map(enc, &two, wo, 512, 512, 64, 64, CU_TENSOR_MAP_SWIZZLE_128B);
    fused_kernel<<<128, 384, SMEM_BYTES>>>(tx, tqkv, t1, t3, t1h, t3h, t2, t2h, two, (const __nv_bfloat16*)x,
                                           (__nv_bfloat16*)d_out, (const char*)wqkv, (const char*)w1, (const char*)w3,
                                           (const char*)w2, (const char*)wo);
}
```

```cpp
#include <cuda_runtime.h>
#include <cuda_bf16.h>
#include <cuda.h>
#include <stdint.h>

namespace {

constexpr int NST = 13;
constexpr int STAGE_BYTES = 16384;
constexpr int XST0 = 5;
constexpr int SCR0 = 8;
constexpr int XCH0 = 3;
__host__ __device__ constexpr int p2_id(int i) {
    constexpr int t[18] = {0, 1, 2, 3, 8, 4, 5, 9, 10, 6, 11, 12, 7, 13, 14, 15, 16, 17};
    return t[i];
}
__host__ __device__ constexpr int p2_useB(int i) {
    constexpr int t[18] = {43, 45, 47, 49, 50, 52, 54, 55, 56, 58, 59, 60, 62, 63, 64, 65, 66, 67};
    return t[i];
}
constexpr int OFF_MISC = NST * STAGE_BYTES;
constexpr int OFF_KVFRAG = OFF_MISC;
constexpr int OFF_ONES = OFF_MISC + 3072;
constexpr int OFF_BARS = OFF_MISC + 3328;
constexpr int BAR_FULL = OFF_BARS;
constexpr int BAR_EMPTY = BAR_FULL + 8 * NST;
constexpr int BAR_XFULL = BAR_EMPTY + 8 * NST;
constexpr int BAR_KVREADY = BAR_XFULL + 64;
constexpr int BAR_XCHG = BAR_KVREADY + 8;
constexpr int BAR_EPOCH = BAR_XCHG + 8;
constexpr int BAR_XRDY = BAR_EPOCH + 8;
constexpr int OFF_EPOCH = BAR_XRDY + 8;
constexpr int OFF_ZERO = OFF_MISC + 4096;
constexpr int SMEM_BYTES = OFF_MISC + 8192;

constexpr unsigned SPIN_LIMIT = 1u << 24;

constexpr int A2_N = 16 * 2 * 18 * 4 * 256;
__device__ uint4 g_A2[2 * A2_N];
__device__ float4 g_kvacc[2 * 8 * 272];
__device__ unsigned g_kvcnt[8];
__constant__ unsigned char P2_ID[18] = {0, 1, 2, 3, 8, 4, 5, 9, 10, 6, 11, 12, 7, 13, 14, 15, 16, 17};
__device__ unsigned g_epoch;
__device__ unsigned g_ticket;

#define TS(role, i)
#define TSW(role, i)

__device__ __forceinline__ uint32_t smem_u32(const void* p) { return (uint32_t)__cvta_generic_to_shared(p); }
__device__ __forceinline__ void mbar_init(uint32_t bar, uint32_t cnt) {
    asm volatile("mbarrier.init.shared::cta.b64 [%0], %1;" ::"r"(bar), "r"(cnt) : "memory");
}
__device__ __forceinline__ void mbar_expect_tx(uint32_t bar, uint32_t bytes) {
    asm volatile("mbarrier.arrive.expect_tx.shared::cta.b64 _, [%0], %1;" ::"r"(bar), "r"(bytes) : "memory");
}
__device__ __forceinline__ void mbar_arrive(uint32_t bar) {
    asm volatile("mbarrier.arrive.shared::cta.b64 _, [%0];" ::"r"(bar) : "memory");
}
__device__ __forceinline__ void mbar_arrive_cta(uint32_t bar, uint32_t cta) {
    asm volatile(
        "{\n.reg .b32 ra;\nmapa.shared::cluster.u32 ra, %0, %1;\n"
        "mbarrier.arrive.shared::cluster.b64 _, [ra];\n}" ::"r"(bar), "r"(cta) : "memory");
}
__device__ __forceinline__ void mbar_wait(uint32_t bar, uint32_t parity) {
    asm volatile(
        "{\n.reg .pred p, q;\n.reg .u32 n;\nmov.u32 n, 0;\n"
        "WAIT_%=:\n"
        "mbarrier.try_wait.parity.shared::cta.b64 p, [%0], %1;\n"
        "@p bra.uni DONE_%=;\n"
        "add.u32 n, n, 1;\n"
        "setp.gt.u32 q, n, %2;\n"
        "@q trap;\n"
        "bra.uni WAIT_%=;\n"
        "DONE_%=:\n}"
        ::"r"(bar), "r"(parity), "n"(SPIN_LIMIT) : "memory");
}
__device__ __forceinline__ unsigned ld_acquire(const unsigned* p) {
    unsigned v;
    asm volatile("ld.acquire.gpu.global.u32 %0, [%1];" : "=r"(v) : "l"(p) : "memory");
    return v;
}
__device__ __forceinline__ void st_release(unsigned* p, unsigned v) {
    asm volatile("st.release.gpu.global.u32 [%0], %1;" ::"l"(p), "r"(v) : "memory");
}
__device__ __forceinline__ unsigned read_epoch() {
    return __shfl_sync(0xffffffffu, *(volatile unsigned*)&g_epoch, 0) + 1;
}
__device__ __forceinline__ void tma_load(uint32_t dst, const CUtensorMap* tm, uint32_t bar, int x, int y) {
    asm volatile(
        "cp.async.bulk.tensor.2d.shared::cluster.global.mbarrier::complete_tx::bytes [%0], [%1, {%3, %4}], [%2];"
        ::"r"(dst), "l"(tm), "r"(bar), "r"(x), "r"(y) : "memory");
}
__device__ __forceinline__ void tma_load_mc(uint32_t dst, const CUtensorMap* tm, uint32_t bar, int x, int y) {
    asm volatile(
        "cp.async.bulk.tensor.2d.shared::cluster.global.mbarrier::complete_tx::bytes.multicast::cluster "
        "[%0], [%1, {%3, %4}], [%2], %5;"
        ::"r"(dst), "l"(tm), "r"(bar), "r"(x), "r"(y), "h"((uint16_t)3) : "memory");
}
__device__ __forceinline__ void prefetch_tm(const CUtensorMap* tm) {
    asm volatile("prefetch.tensormap [%0];" ::"l"(tm) : "memory");
}
__device__ __forceinline__ void l2_prefetch(const void* p, uint32_t bytes) {
    asm volatile("cp.async.bulk.prefetch.L2.global [%0], %1;" ::"l"(p), "r"(bytes) : "memory");
}
__device__ __forceinline__ void bar_sync(int id, int n) { asm volatile("bar.sync %0, %1;" ::"r"(id), "r"(n) : "memory"); }
__device__ __forceinline__ void bar_arrive(int id, int n) { asm volatile("bar.arrive %0, %1;" ::"r"(id), "r"(n) : "memory"); }
__device__ __forceinline__ void wg_fence() { asm volatile("wgmma.fence.sync.aligned;" ::: "memory"); }
__device__ __forceinline__ void wg_commit() { asm volatile("wgmma.commit_group.sync.aligned;" ::: "memory"); }
template <int N>
__device__ __forceinline__ void wg_wait() { asm volatile("wgmma.wait_group.sync.aligned %0;" ::"n"(N) : "memory"); }

__device__ __forceinline__ uint64_t make_desc(uint32_t addr, uint32_t lbo, uint32_t sbo, uint64_t swz) {
    return (uint64_t)((addr & 0x3FFFF) >> 4) | ((uint64_t)(lbo >> 4) << 16) | ((uint64_t)(sbo >> 4) << 32) | (swz << 62);
}

#define ACC8(a, o) "+f"(a[o]), "+f"(a[o + 1]), "+f"(a[o + 2]), "+f"(a[o + 3]), "+f"(a[o + 4]), "+f"(a[o + 5]), "+f"(a[o + 6]), "+f"(a[o + 7])
constexpr uint32_t DHI128 = (1024u >> 4) | (1u << 30);
constexpr uint32_t DHI64 = (512u >> 4) | (2u << 30);
__device__ __forceinline__ void wgmma_n128_rs(float (&d)[64], const uint32_t* a, uint32_t db, int scale_d) {
    asm volatile(
        "{\n.reg .pred p;\n.reg .b64 dd;\nsetp.ne.b32 p, %69, 0;\nmov.b64 dd, {%68, %70};\n"
        "wgmma.mma_async.sync.aligned.m64n128k16.f32.bf16.bf16 "
        "{%0,%1,%2,%3,%4,%5,%6,%7,%8,%9,%10,%11,%12,%13,%14,%15,%16,%17,%18,%19,%20,%21,%22,%23,%24,%25,%26,%27,%28,%29,%30,%31,"
        "%32,%33,%34,%35,%36,%37,%38,%39,%40,%41,%42,%43,%44,%45,%46,%47,%48,%49,%50,%51,%52,%53,%54,%55,%56,%57,%58,%59,%60,%61,%62,%63},"
        "{%64,%65,%66,%67}, dd, p, 1, 1, 1;\n}"
        : ACC8(d, 0), ACC8(d, 8), ACC8(d, 16), ACC8(d, 24), ACC8(d, 32), ACC8(d, 40), ACC8(d, 48), ACC8(d, 56)
        : "r"(a[0]), "r"(a[1]), "r"(a[2]), "r"(a[3]), "r"(db), "r"(scale_d), "n"(DHI128));
}
template <uint32_t HI>
__device__ __forceinline__ void wgmma_n64_rs(float (&d)[32], const uint32_t* a, uint32_t db, int scale_d) {
    asm volatile(
        "{\n.reg .pred p;\n.reg .b64 dd;\nsetp.ne.b32 p, %37, 0;\nmov.b64 dd, {%36, %38};\n"
        "wgmma.mma_async.sync.aligned.m64n64k16.f32.bf16.bf16 "
        "{%0,%1,%2,%3,%4,%5,%6,%7,%8,%9,%10,%11,%12,%13,%14,%15,%16,%17,%18,%19,%20,%21,%22,%23,%24,%25,%26,%27,%28,%29,%30,%31},"
        "{%32,%33,%34,%35}, dd, p, 1, 1, 1;\n}"
        : ACC8(d, 0), ACC8(d, 8), ACC8(d, 16), ACC8(d, 24)
        : "r"(a[0]), "r"(a[1]), "r"(a[2]), "r"(a[3]), "r"(db), "r"(scale_d), "n"(HI));
}
__device__ __forceinline__ void wgmma_n64_ss_tt(float (&d)[32], uint64_t da, uint64_t db, int scale_d) {
    asm volatile(
        "{\n.reg .pred p;\nsetp.ne.b32 p, %34, 0;\n"
        "wgmma.mma_async.sync.aligned.m64n64k16.f32.bf16.bf16 "
        "{%0,%1,%2,%3,%4,%5,%6,%7,%8,%9,%10,%11,%12,%13,%14,%15,%16,%17,%18,%19,%20,%21,%22,%23,%24,%25,%26,%27,%28,%29,%30,%31},"
        "%32, %33, p, 1, 1, 1, 1;\n}"
        : ACC8(d, 0), ACC8(d, 8), ACC8(d, 16), ACC8(d, 24)
        : "l"(da), "l"(db), "r"(scale_d));
}
__device__ __forceinline__ void wgmma_n8_ss_tn(float (&d)[4], uint64_t da, uint64_t db, int scale_d) {
    asm volatile(
        "{\n.reg .pred p;\nsetp.ne.b32 p, %6, 0;\n"
        "wgmma.mma_async.sync.aligned.m64n8k16.f32.bf16.bf16 {%0,%1,%2,%3}, %4, %5, p, 1, 1, 1, 0;\n}"
        : "+f"(d[0]), "+f"(d[1]), "+f"(d[2]), "+f"(d[3])
        : "l"(da), "l"(db), "r"(scale_d));
}
template <int N>
__device__ __forceinline__ void acc_fence(float (&d)[N]) {
#pragma unroll
    for (int i = 0; i < N; i++) asm volatile("" : "+f"(d[i])::"memory");
}
__device__ __forceinline__ void mma16816(float (&c)[4], const uint32_t* a, uint32_t b0, uint32_t b1) {
    asm volatile(
        "mma.sync.aligned.m16n8k16.row.col.f32.bf16.bf16.f32 {%0,%1,%2,%3}, {%4,%5,%6,%7}, {%8,%9}, {%0,%1,%2,%3};"
        : "+f"(c[0]), "+f"(c[1]), "+f"(c[2]), "+f"(c[3])
        : "r"(a[0]), "r"(a[1]), "r"(a[2]), "r"(a[3]), "r"(b0), "r"(b1));
}
__device__ __forceinline__ uint32_t pack_bf16(float lo, float hi) {
    uint32_t r;
    asm("cvt.rn.bf16x2.f32 %0, %1, %2;" : "=r"(r) : "f"(hi), "f"(lo));
    return r;
}
__device__ __forceinline__ float bf_lo(uint32_t v) { return __uint_as_float(v << 16); }
__device__ __forceinline__ float bf_hi(uint32_t v) { return __uint_as_float(v & 0xffff0000u); }
__device__ __forceinline__ float bf16_round(float v) { return __bfloat162float(__float2bfloat16_rn(v)); }
__device__ __forceinline__ float sqrt_fast(float v) {
    float r;
    asm("sqrt.approx.ftz.f32 %0, %1;" : "=f"(r) : "f"(v));
    return r;
}
__device__ __forceinline__ float rcp_fast(float v) {
    float r;
    asm("rcp.approx.ftz.f32 %0, %1;" : "=f"(r) : "f"(v));
    return r;
}
__device__ __forceinline__ float ex2_fast(float v) {
    float r;
    asm("ex2.approx.ftz.f32 %0, %1;" : "=f"(r) : "f"(v));
    return r;
}
struct RowScale { float rho, rl, var; };
__device__ __forceinline__ float phi_f(float a, const RowScale& r) {
    return fmaf(fmaxf(a, 0.f), r.rho, ex2_fast(fminf(a, 0.f) * r.rl) + 1e-6f);
}
__device__ __forceinline__ float swiglu_f(float ga, float ua, const RowScale& r) {
    return (ga * ua) * rcp_fast(fmaf(ex2_fast(-ga * r.rl), r.var, r.var));
}
__device__ __forceinline__ uint4 swiglu8(const float* gp, const float* up, const RowScale& r0, const RowScale& r1) {
    uint4 v;
    v.x = pack_bf16(swiglu_f(gp[0], up[0], r0), swiglu_f(gp[1], up[1], r0));
    v.y = pack_bf16(swiglu_f(gp[2], up[2], r1), swiglu_f(gp[3], up[3], r1));
    v.z = pack_bf16(swiglu_f(gp[4], up[4], r0), swiglu_f(gp[5], up[5], r0));
    v.w = pack_bf16(swiglu_f(gp[6], up[6], r1), swiglu_f(gp[7], up[7], r1));
    v.y = v.y ? v.y : 0x8000u;
    v.w = v.w ? v.w : 0x8000u;
    return v;
}
__device__ __forceinline__ bool frag_stale(const uint4 (&f)[12]) {
    unsigned v = min(f[0].y, f[0].w);
#pragma unroll
    for (int i = 1; i < 12; i++) v = min(v, min(f[i].y, f[i].w));
    return __any_sync(0xffffffffu, v == 0u);
}
__device__ __forceinline__ void st_frag(uint4* p, uint4 v) {
    asm volatile("st.relaxed.gpu.global.v4.u32 [%0], {%1,%2,%3,%4};" ::"l"(p), "r"(v.x), "r"(v.y), "r"(v.z), "r"(v.w) : "memory");
}
__device__ __forceinline__ uint4 ld_frag(const uint4* p) {
    uint4 v;
    asm volatile("ld.relaxed.gpu.global.v4.u32 {%0,%1,%2,%3}, [%4];" : "=r"(v.x), "=r"(v.y), "=r"(v.z), "=r"(v.w) : "l"(p) : "memory");
    return v;
}
__device__ __forceinline__ void red_add2(float* p, float a, float b) {
    asm volatile("red.global.add.v2.f32 [%0], {%1, %2};" ::"l"(p), "f"(a), "f"(b) : "memory");
}
__device__ __forceinline__ void cp_async16(uint32_t dst, const void* src) {
    asm volatile("cp.async.cg.shared.global [%0], [%1], 16;" ::"r"(dst), "l"(src) : "memory");
}

__host__ __device__ constexpr int ring_lap(int u) { return (u * 79) >> 10; }
__host__ __device__ constexpr int ring_slot(int u) { return u - NST * ring_lap(u); }

__device__ __forceinline__ void mainloop128(float (&acc)[64], const uint32_t (&xa)[128], int u0, uint32_t sb,
                                            uint32_t desc128, int lane, int wg, bool last = false) {
    bar_sync(7 + wg, 256);
#pragma unroll
    for (int kb = 0; kb < 8; kb++) {
        const int st = ring_slot(u0 + kb);
        mbar_wait(sb + BAR_FULL + 8 * st, ring_lap(u0 + kb) & 1);
        wg_fence();
        const uint32_t d = desc128 + st * (STAGE_BYTES >> 4);
#pragma unroll
        for (int ks = 0; ks < 4; ks++) wgmma_n128_rs(acc, &xa[(kb * 4 + ks) * 4], d + ks * 128, (kb | ks) != 0);
        wg_commit();
        if (kb == 7 && !(last && wg == 1)) bar_arrive(8 - wg, 256);
        if (kb > 0) {
            wg_wait<1>();
            if (lane == 0) mbar_arrive(sb + BAR_EMPTY + 8 * ring_slot(u0 + kb - 1));
        }
    }
    wg_wait<0>();
    acc_fence(acc);
    if (lane == 0) mbar_arrive(sb + BAR_EMPTY + 8 * ring_slot(u0 + 7));
}
__device__ __forceinline__ void mainloop64x2(float (&a0)[32], float (&a1)[32], const uint32_t (&xa)[128], int u0,
                                             uint32_t sb, uint32_t desc128, int lane, int wg) {
    bar_sync(7 + wg, 256);
#pragma unroll
    for (int kb = 0; kb < 8; kb++) {
        const int st = ring_slot(u0 + kb);
        mbar_wait(sb + BAR_FULL + 8 * st, ring_lap(u0 + kb) & 1);
        wg_fence();
        const uint32_t d = desc128 + st * (STAGE_BYTES >> 4);
        const uint32_t d2 = d + (8192 >> 4) - ((4096u >> 4) << 16);
#pragma unroll
        for (int ks = 0; ks < 4; ks++) {
            wgmma_n64_rs<DHI128>(a0, &xa[(kb * 4 + ks) * 4], d + ks * 128, (kb | ks) != 0);
            wgmma_n64_rs<DHI64>(a1, &xa[(kb * 4 + ks) * 4], d2 + ks * 64, (kb | ks) != 0);
        }
        wg_commit();
        if (kb == 7) bar_arrive(8 - wg, 256);
        if (kb > 0) {
            wg_wait<1>();
            if (lane == 0) mbar_arrive(sb + BAR_EMPTY + 8 * ring_slot(u0 + kb - 1));
        }
    }
    wg_wait<0>();
    acc_fence(a0);
    acc_fence(a1);
    if (lane == 0) mbar_arrive(sb + BAR_EMPTY + 8 * ring_slot(u0 + 7));
}

__global__ void __cluster_dims__(2, 1, 1) __launch_bounds__(384, 1)
fused_kernel(const __grid_constant__ CUtensorMap tm_x, const __grid_constant__ CUtensorMap tm_qkv,
             const __grid_constant__ CUtensorMap tm_w1, const __grid_constant__ CUtensorMap tm_w3,
             const __grid_constant__ CUtensorMap tm_w1h, const __grid_constant__ CUtensorMap tm_w3h,
             const __grid_constant__ CUtensorMap tm_w2, const __grid_constant__ CUtensorMap tm_w2h,
             const __grid_constant__ CUtensorMap tm_wo, const __nv_bfloat16* __restrict__ xg,
             __nv_bfloat16* __restrict__ outg, const char* __restrict__ p_qkv, const char* __restrict__ p_w1,
             const char* __restrict__ p_w3, const char* __restrict__ p_w2, const char* __restrict__ p_wo) {
    extern __shared__ __align__(1024) uint8_t smem[];
    const uint32_t sb = smem_u32(smem);
    const int tid = threadIdx.x;
    const int warp = tid >> 5, lane = tid & 31;
    const int rank = blockIdx.x & 1;
    const int pair = blockIdx.x >> 1;
    const int m = pair >> 2;
    const int j2 = pair & 3;
    const int c = 2 * j2 + rank;
    const int m2 = m;

    TS(tid >> 7, 0);
    if (tid == 256) {
        prefetch_tm(&tm_x);
#pragma unroll
        for (int i = 0; i < 8; i++) mbar_init(sb + BAR_XFULL + 8 * i, 1);
#pragma unroll
        for (int kb = 0; kb < 8; kb++) mbar_expect_tx(sb + BAR_XFULL + 8 * kb, 16384);
        asm volatile("fence.mbarrier_init.release.cluster;" ::: "memory");
        TS(2, 21);
    } else if (tid == 0) {
#pragma unroll
        for (int i = 0; i < NST; i++) mbar_init(sb + BAR_FULL + 8 * i, 1);
        asm volatile("fence.mbarrier_init.release.cluster;" ::: "memory");
    } else if (tid == 32) {
#pragma unroll
        for (int i = 0; i < NST; i++) mbar_init(sb + BAR_EMPTY + 8 * i, 8);
        asm volatile("fence.mbarrier_init.release.cluster;" ::: "memory");
    } else if (tid == 64) {
#pragma unroll
        for (int i = 0; i < 4; i++) mbar_init(sb + BAR_KVREADY + 8 * i, 1);
        mbar_expect_tx(sb + BAR_XCHG, 32768);
        asm volatile("fence.mbarrier_init.release.cluster;" ::: "memory");
    } else if (tid >= 128 && tid < 256) {
        ((uint4*)(smem + OFF_ZERO))[tid - 128] = make_uint4(0, 0, 0, 0);
        ((uint4*)(smem + OFF_ZERO))[tid] = make_uint4(0, 0, 0, 0);
        asm volatile("fence.proxy.async.shared::cta;" ::: "memory");
    } else if (tid == 288) {
        prefetch_tm(&tm_qkv);
        prefetch_tm(&tm_w1);
        prefetch_tm(&tm_w3);
        prefetch_tm(&tm_w1h);
        prefetch_tm(&tm_w3h);
        prefetch_tm(&tm_w2);
        prefetch_tm(&tm_w2h);
        prefetch_tm(&tm_wo);
    } else if (tid >= 320) {
        ((uint32_t*)(smem + OFF_ONES))[tid - 320] = 0x3F803F80u;
        asm volatile("fence.proxy.async.shared::cta;" ::: "memory");
    }
    __syncthreads();
    TS(tid >> 7, 22);
    asm volatile("barrier.cluster.arrive.relaxed.aligned;\nbarrier.cluster.wait.acquire.aligned;" ::: "memory");

    if (warp >= 8) {
        asm volatile("setmaxnreg.dec.sync.aligned.u32 40;");
        if (warp == 8) {
            if (lane == 0) {
                int st = 0;
                uint32_t lap = 0;
#pragma unroll
                for (int i = 0; i < 4; i++) {
                    const int kb = 2 * i + rank;
                    tma_load_mc(sb + (XST0 + kb) * STAGE_BYTES, &tm_x, sb + BAR_XFULL + 8 * kb, kb * 64, m * 128);
                }
                for (int it = 0; it < 40; it++) {
                    const int tile = it >> 3, kb = it & 7;
                    const uint32_t full = sb + BAR_FULL + 8 * st;
                    mbar_wait(sb + BAR_EMPTY + 8 * st, (st >= XST0) ? (lap & 1) : ((lap & 1) ^ 1));
                    mbar_expect_tx(full, STAGE_BYTES);
                    const uint32_t dst = sb + st * STAGE_BYTES;
                    if (tile == 0) {
                        tma_load(dst, &tm_qkv, full, 512 + 64 * c, kb * 64);
                        tma_load(dst + 8192, &tm_qkv, full, 1024 + 64 * c, kb * 64);
                    } else if (tile != 3) {
                        const int col = 224 * c + 64 * (tile == 4 ? 2 : tile - 1);
                        tma_load(dst, &tm_w1, full, col, kb * 64);
                        tma_load(dst + 8192, &tm_w3, full, col, kb * 64);
                    } else {
                        tma_load(dst, &tm_qkv, full, 64 * c, kb * 64);
                        tma_load(dst + 8192, &tm_w1h, full, 224 * c + 192, kb * 64);
                        tma_load(dst + 12288, &tm_w3h, full, 224 * c + 192, kb * 64);
                    }
                    if (++st == NST) { st = 0; lap++; }
                    if (it == 7) {
                        mbar_wait(sb + BAR_EMPTY + 8 * SCR0, 0);
                        mbar_arrive(sb + BAR_FULL + 8 * SCR0);
                        mbar_wait(sb + BAR_EMPTY + 8 * (SCR0 + 1), 0);
                        mbar_arrive(sb + BAR_FULL + 8 * (SCR0 + 1));
                        st += 2;
                    }
                }
                TS(2, 1);
                mbar_wait(sb + BAR_EPOCH, 0);
                const char* a2b = (const char*)(g_A2 + (size_t)(*(volatile unsigned*)(smem + OFF_EPOCH) & 1) * A2_N +
                                                (size_t)((m2 * 2 + rank) * 18) * 4 * 256);
#pragma unroll 1
                for (int i = 0; i < 18; i++) {
                    const int b = P2_ID[i];
                    if (b < 8) {
                        mbar_wait(sb + BAR_EMPTY + 8 * st, (st >= XST0) ? (lap & 1) : ((lap & 1) ^ 1));
                        mbar_expect_tx(sb + BAR_FULL + 8 * st, STAGE_BYTES);
                        asm volatile("cp.async.bulk.shared::cluster.global.mbarrier::complete_tx::bytes [%0], [%1], 16384, [%2];"
                                     ::"r"(sb + st * STAGE_BYTES), "l"(a2b + b * 16384), "r"(sb + BAR_FULL + 8 * st) : "memory");
                        if (++st == NST) { st = 0; lap++; }
                    }
                    const uint32_t full = sb + BAR_FULL + 8 * st;
                    const uint32_t dst = sb + st * STAGE_BYTES;
                    mbar_wait(sb + BAR_EMPTY + 8 * st, (st >= XST0) ? (lap & 1) : ((lap & 1) ^ 1));
                    mbar_expect_tx(full, STAGE_BYTES);
                    if (b < 8 || b >= 14) {
                        const int row = (b < 8) ? 224 * (4 * rank + (b & 3)) + 64 * (b >> 2) : 224 * (4 * rank + b - 14) + 128;
                        tma_load(dst, &tm_w2, full, 128 * j2, row);
                        tma_load(dst + 8192, &tm_w2, full, 128 * j2 + 64, row);
                    } else if (b < 10) {
                        const int row = 224 * (4 * rank + 2 * (b - 8)) + 192;
                        tma_load(dst, &tm_w2h, full, 128 * j2, row);
                        tma_load(dst + 4096, &tm_w2h, full, 128 * j2, row + 224);
                        tma_load(dst + 8192, &tm_w2h, full, 128 * j2 + 64, row);
                        tma_load(dst + 12288, &tm_w2h, full, 128 * j2 + 64, row + 224);
                    } else {
                        const int row = 64 * (4 * rank + (b - 10));
                        tma_load(dst, &tm_wo, full, 128 * j2, row);
                        tma_load(dst + 8192, &tm_wo, full, 128 * j2 + 64, row);
                    }
                    TS(2, 2 + i);
                    if (++st == NST) { st = 0; lap++; }
                }
                mbar_wait(sb + BAR_EMPTY + 8 * XCH0, (lap & 1) ^ 1);
                mbar_wait(sb + BAR_EMPTY + 8 * (XCH0 + 1), (lap & 1) ^ 1);
                mbar_arrive_cta(sb + BAR_XRDY, rank ^ 1);
            }
        } else if (warp < 11) {
            const int wg = warp - 9;
            bar_sync(3 + wg, 160);
            if (lane == 0) asm volatile("red.release.gpu.global.add.u32 [%0], 1;" ::"l"(&g_kvcnt[c]) : "memory");
            TSW(3, wg);
        } else {
            const unsigned epoch = read_epoch();
            if (lane == 0) {
                const unsigned tk = atomicInc(&g_ticket, 127u);
                if (tk == 127u) *(volatile unsigned*)&g_epoch = epoch;
            }
            if (lane == 0) *(volatile unsigned*)(smem + OFF_EPOCH) = epoch;
            __syncwarp();
            if (lane == 0) mbar_arrive(sb + BAR_EPOCH);
            if (lane < 17) g_kvacc[(((epoch & 1) ^ 1) * 8 + c) * 272 + 17 * m + lane] = make_float4(0.f, 0.f, 0.f, 0.f);
            {
                unsigned n = 0;
                while ((int)(ld_acquire(&g_kvcnt[c]) - 32u * epoch) < 0) {
                    __nanosleep(200);
                    if (++n > SPIN_LIMIT) asm volatile("trap;");
                }
            }
            TSW(4, 0);
            const int g = lane >> 2, t = lane & 3;
            const float* ks = (const float*)(g_kvacc + ((epoch & 1) * 8 + c) * 272) + 32 * t + g;
            uint2* kf = (uint2*)(smem + OFF_KVFRAG) + lane;
#pragma unroll 2
            for (int hh = 0; hh < 4; hh++) {
                const float* k = ks + hh * 272;
                const float a0 = __ldcg(k), a1 = __ldcg(k + 16), a2 = __ldcg(k + 128), a3 = __ldcg(k + 144);
                const float b0 = __ldcg(k + 8), b1 = __ldcg(k + 24), b2 = __ldcg(k + 136), b3 = __ldcg(k + 152);
                const float2 z0 = __ldcg((const float2*)(k - g - 30 * t + 256)), z1 = __ldcg((const float2*)(k - g - 30 * t + 264));
                kf[(hh * 3 + 0) * 32] = make_uint2(pack_bf16(a0, a1), pack_bf16(a2, a3));
                kf[(hh * 3 + 1) * 32] = make_uint2(pack_bf16(b0, b1), pack_bf16(b2, b3));
                kf[(hh * 3 + 2) * 32] = make_uint2(pack_bf16(z0.x, z0.y), pack_bf16(z1.x, z1.y));
            }
            __syncwarp();
            if (lane == 0) mbar_arrive(sb + BAR_KVREADY);
            TSW(4, 4);
            if (lane == 0) {
                char* z = (char*)(g_A2 + (size_t)((epoch & 1) ^ 1) * A2_N + (size_t)((m * 2 + (c >> 2)) * 18) * 4 * 256);
                const int cc = c & 3;
#pragma unroll 1
                for (int i = 0; i < 18; i++) {
                    const int blk = (i < 8) ? ((i >> 2) * 4 + cc) * 4 + (i & 3)
                                  : (i < 10) ? (8 + (cc >> 1)) * 4 + 2 * (cc & 1) + (i - 8)
                                  : (i < 14) ? (10 + cc) * 4 + (i - 10) : (14 + cc) * 4 + (i - 14);
                    asm volatile("cp.async.bulk.global.shared::cta.bulk_group [%0], [%1], 4096;"
                                 ::"l"(z + (size_t)blk * 4096), "r"(sb + OFF_ZERO) : "memory");
                }
                asm volatile("cp.async.bulk.commit_group;" ::: "memory");
            }
            if (lane == 0) asm volatile("cp.async.bulk.wait_group 0;" ::: "memory");
        }
    } else {
        asm volatile("setmaxnreg.inc.sync.aligned.u32 232;");
        const int wg = warp >> 2, w = warp & 3;
        const int g = lane >> 2, t = lane & 3;
        float acc[64];
        uint32_t xa[128];
        float rho0, rho1;
        RowScale r0, r1;
        unsigned par;

        TS(wg, 1);
        {
            const int row = wg * 64 + w * 16 + (lane & 7) + ((lane >> 3) & 1) * 8;
            const uint32_t rbase = sb + XST0 * STAGE_BYTES + row * 128;
            const int hi = lane >> 4, r7 = lane & 7;
            float sm[2][4], c0[2][4], c1[2][4];
#pragma unroll
            for (int i = 0; i < 8; i++) { sm[i >> 2][i & 3] = 0.f; c0[i >> 2][i & 3] = 0.f; c1[i >> 2][i & 3] = 0.f; }
            if (wg == 1) bar_arrive(7, 256);
#pragma unroll
            for (int kb = 0; kb < 8; kb++) {
                mbar_wait(sb + BAR_XFULL + 8 * kb, 0);
#pragma unroll
                for (int ks = 0; ks < 4; ks++) {
                    uint32_t* a = &xa[(kb * 4 + ks) * 4];
                    const uint32_t addr = rbase + kb * STAGE_BYTES + (((2 * ks + hi) ^ r7) << 4);
                    asm volatile("ldmatrix.sync.aligned.m8n8.x4.shared.b16 {%0,%1,%2,%3}, [%4];"
                                 : "=r"(a[0]), "=r"(a[1]), "=r"(a[2]), "=r"(a[3]) : "r"(addr) : "memory");
                    mma16816(sm[ks & 1], a, 0x3F803F80u, 0x3F803F80u);
                    mma16816(c0[ks & 1], a, a[0], a[2]);
                    mma16816(c1[ks & 1], a, a[1], a[3]);
                }
            }
            TS(wg, 2);
            const float mean0 = (sm[0][0] + sm[1][0]) * (1.f / 512.f);
            const float mean1 = (sm[0][2] + sm[1][2]) * (1.f / 512.f);
            __syncwarp();
            if (lane < 8) mbar_arrive(sb + BAR_EMPTY + 8 * (XST0 + lane));
            const __nv_bfloat162 mb0 = __float2bfloat162_rn(mean0), mb1 = __float2bfloat162_rn(mean1);
#pragma unroll
            for (int i = 0; i < 128; i++) {
                __nv_bfloat162 v = *reinterpret_cast<__nv_bfloat162*>(&xa[i]);
                v = __hsub2(v, (i & 1) ? mb1 : mb0);
                xa[i] = *reinterpret_cast<uint32_t*>(&v);
            }
            const float d0 = (g & 1) ? c0[0][1] + c0[1][1] : c0[0][0] + c0[1][0];
            const float d1 = (g & 1) ? c1[0][3] + c1[1][3] : c1[0][2] + c1[1][2];
            const int src = (lane & ~3) | (g >> 1);
            const float var0 = fmaxf(__shfl_sync(0xffffffffu, d0, src) * (1.f / 512.f) - mean0 * mean0, 0.f);
            const float var1 = fmaxf(__shfl_sync(0xffffffffu, d1, src) * (1.f / 512.f) - mean1 * mean1, 0.f);
            const float sd0 = bf16_round(sqrt_fast(bf16_round(bf16_round(var0) + 1e-5f)));
            const float sd1 = bf16_round(sqrt_fast(bf16_round(bf16_round(var1) + 1e-5f)));
            rho0 = rcp_fast(sd0);
            rho1 = rcp_fast(sd1);
            r0.rho = rho0; r0.rl = rho0 * 1.4426950408889634f; r0.var = sd0 * sd0;
            r1.rho = rho1; r1.rl = rho1 * 1.4426950408889634f; r1.var = sd1 * sd1;
        }

        TS(wg, 3);
        const uint32_t desc128 = ((sb & 0x3FFFF) >> 4) | ((8192u >> 4) << 16);
        const int cc = c & 3;

        {
            mainloop128(acc, xa, 0, sb, desc128, lane, wg);
            TS(wg, 4);
            {
                TS(wg, 24);
                const uint32_t pkb = sb + (SCR0 + wg) * STAGE_BYTES;
                mbar_wait(sb + BAR_FULL + 8 * (SCR0 + wg), 0);
                const uint32_t ra = pkb + (w * 16 + g) * 128 + t * 4;
#pragma unroll
                for (int nb = 0; nb < 8; nb++) {
                    const uint32_t off = (uint32_t)((nb ^ g) << 4);
                    uint32_t p0 = pack_bf16(phi_f(acc[nb * 4], r0), phi_f(acc[nb * 4 + 1], r0));
                    uint32_t p1 = pack_bf16(phi_f(acc[nb * 4 + 2], r1), phi_f(acc[nb * 4 + 3], r1));
                    uint32_t v0 = pack_bf16(acc[32 + nb * 4] * rho0, acc[32 + nb * 4 + 1] * rho0);
                    uint32_t v1 = pack_bf16(acc[32 + nb * 4 + 2] * rho1, acc[32 + nb * 4 + 3] * rho1);
                    asm volatile("st.shared.u32 [%0], %1;" ::"r"(ra + off), "r"(p0) : "memory");
                    asm volatile("st.shared.u32 [%0], %1;" ::"r"(ra + off + 1024), "r"(p1) : "memory");
                    asm volatile("st.shared.u32 [%0], %1;" ::"r"(ra + off + 8192), "r"(v0) : "memory");
                    asm volatile("st.shared.u32 [%0], %1;" ::"r"(ra + off + 8192 + 1024), "r"(v1) : "memory");
                }
                TS(wg, 25);
                asm volatile("fence.proxy.async.shared::cta;" ::: "memory");
                bar_sync(1 + wg, 128);
                TS(wg, 26);
                const uint64_t da = make_desc(pkb, 8192, 1024, 1);
                const uint64_t db = make_desc(pkb + 8192, 8192, 1024, 1);
                const uint64_t d1 = make_desc(sb + OFF_ONES, 128, 128, 0);
                float kva[32], za[4];
                wg_fence();
#pragma unroll
                for (int ks = 0; ks < 4; ks++) {
                    wgmma_n64_ss_tt(kva, da + ks * 128, db + ks * 128, ks != 0);
                    wgmma_n8_ss_tn(za, da + ks * 128, d1, ks != 0);
                }
                wg_commit();
                wg_wait<0>();
                acc_fence(kva);
                acc_fence(za);
                if (lane < 2) mbar_arrive(sb + BAR_EMPTY + 8 * (SCR0 + lane));
                TS(wg, 27);
                float o[8];
#pragma unroll
                for (int i = 0; i < 8; i++)
                    o[i] = (w == 0) ? kva[i] : (w == 1) ? kva[8 + i] : (w == 2) ? kva[16 + i] : kva[24 + i];
                mbar_wait(sb + BAR_EPOCH, 0);
                par = *(volatile unsigned*)(smem + OFF_EPOCH) & 1;
                float* dst = (float*)(g_kvacc + (par * 8 + c) * 272) + w * 272 + g * 16 + 2 * t;
                red_add2(dst, o[0], o[1]);
                red_add2(dst + 128, o[2], o[3]);
                red_add2(dst + 8, o[4], o[5]);
                red_add2(dst + 136, o[6], o[7]);
                if (t == 0) {
                    atomicAdd(dst - g * 15 + 256, za[0]);
                    atomicAdd(dst - g * 15 + 264, za[2]);
                }
            }
            bar_arrive(3 + wg, 160);
            TS(wg, 5);
        }
        uint4* a2w = g_A2 + (size_t)par * A2_N + (size_t)((m * 2 + (c >> 2)) * 18) * 4 * 256 + warp * 32 + lane;
#pragma unroll
        for (int tile = 1; tile < 3; tile++) {
            mainloop128(acc, xa, 2 + 8 * tile, sb, desc128, lane, wg);
            TS(wg, 4 + 2 * tile);
            uint4* dst = a2w + (size_t)((4 * (tile - 1) + cc) * 4) * 256;
#pragma unroll
            for (int ks = 0; ks < 4; ks++) st_frag(dst + ks * 256, swiglu8(&acc[ks * 8], &acc[32 + ks * 8], r0, r1));
            TS(wg, 5 + 2 * tile);
        }
        {
            float qa[32], gu[32];
            mainloop64x2(qa, gu, xa, 26, sb, desc128, lane, wg);
            TS(wg, 10);
            uint4* dst = a2w + (size_t)((8 + (cc >> 1)) * 4 + 2 * (cc & 1)) * 256;
#pragma unroll
            for (int ks = 0; ks < 2; ks++) st_frag(dst + ks * 256, swiglu8(&gu[ks * 8], &gu[16 + ks * 8], r0, r1));
            TS(wg, 13);
            mbar_wait(sb + BAR_KVREADY, 0);
            TS(wg, 14);
            const uint2* kf = (const uint2*)(smem + OFF_KVFRAG);
            dst = a2w + (size_t)((10 + cc) * 4) * 256;
#pragma unroll
            for (int hh = 0; hh < 4; hh++) {
                const float* q = &qa[hh * 8];
                uint32_t a[4];
                a[0] = pack_bf16(phi_f(q[0], r0), phi_f(q[1], r0));
                a[1] = pack_bf16(phi_f(q[2], r1), phi_f(q[3], r1));
                a[2] = pack_bf16(phi_f(q[4], r0), phi_f(q[5], r0));
                a[3] = pack_bf16(phi_f(q[6], r1), phi_f(q[7], r1));
                float n0[4] = {0.f, 0.f, 0.f, 0.f}, n1[4] = {0.f, 0.f, 0.f, 0.f}, dn[4] = {0.f, 0.f, 0.f, 0.f};
                const uint2 b0 = kf[(hh * 3 + 0) * 32 + lane], b1 = kf[(hh * 3 + 1) * 32 + lane],
                            bz = kf[(hh * 3 + 2) * 32 + lane];
                mma16816(n0, a, b0.x, b0.y);
                mma16816(n1, a, b1.x, b1.y);
                mma16816(dn, a, bz.x, bz.y);
                const float i0 = rcp_fast(dn[0] + 1e-6f), i1 = rcp_fast(dn[2] + 1e-6f);
                uint4 v;
                v.x = pack_bf16(n0[0] * i0, n0[1] * i0);
                v.y = pack_bf16(n0[2] * i1, n0[3] * i1);
                v.z = pack_bf16(n1[0] * i0, n1[1] * i0);
                v.w = pack_bf16(n1[2] * i1, n1[3] * i1);
                v.y = v.y ? v.y : 0x8000u;
                v.w = v.w ? v.w : 0x8000u;
                st_frag(dst + hh * 256, v);
            }
            TS(wg, 11);
        }
        const uint4* a2r = g_A2 + (size_t)par * A2_N + (size_t)((m2 * 2 + rank) * 18) * 4 * 256 + warp * 32 + lane;
        uint4 af[2][12];
        {
            mainloop128(acc, xa, 34, sb, desc128, lane, wg);
            TS(wg, 12);
            uint4* dst = a2w + (size_t)((14 + cc) * 4) * 256;
#pragma unroll
            for (int ks = 0; ks < 4; ks++) st_frag(dst + ks * 256, swiglu8(&acc[ks * 8], &acc[32 + ks * 8], r0, r1));
            TS(wg, 15);
        }

        {
            float ao[32], ap[32];
            const uint32_t dso = desc128 + rank * 512, dsp = desc128 + (rank ^ 1) * 512;
            TS(wg, 16);
#pragma unroll
            for (int gi = 0; gi < 6; gi++) {
                if (gi == 5) TS(wg, 17);
                uint4(&f)[12] = af[gi & 1];
#pragma unroll
                for (int bb = 0; bb < 3; bb++) {
                    const int ub = p2_useB(gi * 3 + bb);
                    if (p2_id(gi * 3 + bb) < 8) {
                        mbar_wait(sb + BAR_FULL + 8 * ring_slot(ub - 1), ring_lap(ub - 1) & 1);
                        const uint4* src = (const uint4*)(smem + ring_slot(ub - 1) * STAGE_BYTES) + tid;
#pragma unroll
                        for (int ks = 0; ks < 4; ks++) f[bb * 4 + ks] = src[ks * 256];
                    }
                    mbar_wait(sb + BAR_FULL + 8 * ring_slot(ub), ring_lap(ub) & 1);
                }
                {
                    unsigned n = 0;
                    while (frag_stale(f)) {
#pragma unroll
                        for (int i = 0; i < 12; i++) f[i] = ld_frag(a2r + (p2_id(gi * 3 + (i >> 2)) * 4 + (i & 3)) * 256);
                        if (++n > SPIN_LIMIT) asm volatile("trap;");
                    }
                }
                bar_sync(7 + wg, 256);
                wg_fence();
#pragma unroll
                for (int i = 0; i < 12; i++) {
                    const uint32_t so = ring_slot(p2_useB(gi * 3 + (i >> 2))) * (STAGE_BYTES >> 4) + (i & 3) * 128;
                    const uint32_t* a = reinterpret_cast<const uint32_t*>(&f[i]);
                    wgmma_n64_rs<DHI128>(ap, a, dsp + so, (gi | i) != 0);
                    if (gi < 5) wgmma_n64_rs<DHI128>(ao, a, dso + so, (gi | i) != 0);
                }
                wg_commit();
                bar_arrive(8 - wg, 256);
                if (gi < 5) {
#pragma unroll
                    for (int i = 0; i < 12; i++)
                        if (p2_id(gi * 3 + 3 + (i >> 2)) >= 8)
                            af[(gi + 1) & 1][i] = ld_frag(a2r + (p2_id(gi * 3 + 3 + (i >> 2)) * 4 + (i & 3)) * 256);
                    wg_wait<0>();
                    if (gi < 3 && lane < 6 - gi)
                        mbar_arrive(sb + BAR_EMPTY + 8 * ring_slot((gi == 0 ? 42 : gi == 1 ? 48 : 53) + lane));
                }
            }
            const int row0 = m2 * 128 + wg * 64 + w * 16 + g;
            const int col0 = j2 * 128 + rank * 64 + 2 * t;
            uint32_t xr[16];
#pragma unroll
            for (int nb = 0; nb < 8; nb++) {
                xr[2 * nb] = __ldg((const uint32_t*)(xg + (size_t)row0 * 512 + col0 + nb * 8));
                xr[2 * nb + 1] = __ldg((const uint32_t*)(xg + (size_t)(row0 + 8) * 512 + col0 + nb * 8));
            }
            uint32_t rdst, rbar;
            asm volatile("mapa.shared::cluster.u32 %0, %1, %2;"
                         : "=r"(rdst) : "r"(sb + (XCH0 + wg) * STAGE_BYTES + (tid & 127) * 16), "r"(rank ^ 1));
            asm volatile("mapa.shared::cluster.u32 %0, %1, %2;" : "=r"(rbar) : "r"(sb + BAR_XCHG), "r"(rank ^ 1));
            mbar_wait(sb + BAR_XRDY, 0);
            wg_wait<0>();
            acc_fence(ap);
            TS(wg, 18);
#pragma unroll
            for (int i = 0; i < 8; i++)
                asm volatile("st.async.shared::cluster.mbarrier::complete_tx::bytes.v4.f32 [%0], {%1,%2,%3,%4}, [%5];"
                             ::"r"(rdst + i * 2048), "f"(ap[4 * i]), "f"(ap[4 * i + 1]), "f"(ap[4 * i + 2]), "f"(ap[4 * i + 3]),
                             "r"(rbar) : "memory");
            bar_sync(7 + wg, 256);
            wg_fence();
#pragma unroll
            for (int i = 0; i < 12; i++)
                wgmma_n64_rs<DHI128>(ao, reinterpret_cast<const uint32_t*>(&af[1][i]),
                                     dso + ring_slot(65 + (i >> 2)) * (STAGE_BYTES >> 4) + (i & 3) * 128, 1);
            wg_commit();
            if (wg == 0) bar_arrive(8, 256);
            wg_wait<0>();
            acc_fence(ao);
            mbar_wait(sb + BAR_XCHG, 0);
            TS(wg, 19);
            const float4* rx = (const float4*)(smem + (XCH0 + wg) * STAGE_BYTES) + (tid & 127);
#pragma unroll
            for (int nb = 0; nb < 8; nb++) {
                const float4 p = rx[nb * 128];
                const uint32_t o0 = pack_bf16(ao[4 * nb] + p.x + bf_lo(xr[2 * nb]), ao[4 * nb + 1] + p.y + bf_hi(xr[2 * nb]));
                const uint32_t o1 = pack_bf16(ao[4 * nb + 2] + p.z + bf_lo(xr[2 * nb + 1]), ao[4 * nb + 3] + p.w + bf_hi(xr[2 * nb + 1]));
                *(uint32_t*)(outg + (size_t)row0 * 512 + col0 + nb * 8) = o0;
                *(uint32_t*)(outg + (size_t)(row0 + 8) * 512 + col0 + nb * 8) = o1;
            }
        }
        TS(wg, 20);
    }
}

typedef CUresult (*EncodeFn)(CUtensorMap*, CUtensorMapDataType, cuuint32_t, void*, const cuuint64_t*, const cuuint64_t*,
                             const cuuint32_t*, const cuuint32_t*, CUtensorMapInterleave, CUtensorMapSwizzle,
                             CUtensorMapL2promotion, CUtensorMapFloatOOBfill);

void make_map(EncodeFn enc, CUtensorMap* tm, const void* ptr, int rows, int cols, int box_rows, int box_cols,
              CUtensorMapSwizzle swz) {
    cuuint64_t dims[2] = {(cuuint64_t)cols, (cuuint64_t)rows};
    cuuint64_t strides[1] = {(cuuint64_t)cols * 2};
    cuuint32_t box[2] = {(cuuint32_t)box_cols, (cuuint32_t)box_rows};
    cuuint32_t es[2] = {1, 1};
    enc(tm, CU_TENSOR_MAP_DATA_TYPE_BFLOAT16, 2, const_cast<void*>(ptr), dims, strides, box, es,
        CU_TENSOR_MAP_INTERLEAVE_NONE, swz, CU_TENSOR_MAP_L2_PROMOTION_L2_256B, CU_TENSOR_MAP_FLOAT_OOB_FILL_NONE);
}

}

extern "C" void kernel_launch(void* const* d_in, const int* in_sizes, int n_in, void* d_out, int out_size) {
    (void)in_sizes; (void)n_in; (void)out_size;
    static EncodeFn enc = nullptr;
    if (!enc) {
        void* fn = nullptr;
        cudaDriverEntryPointQueryResult qr;
        cudaGetDriverEntryPoint("cuTensorMapEncodeTiled", &fn, cudaEnableDefault, &qr);
        enc = (EncodeFn)fn;
        cudaFuncSetAttribute(fused_kernel, cudaFuncAttributeMaxDynamicSharedMemorySize, SMEM_BYTES);
    }
    const void* x = d_in[0];
    const void* wqkv = d_in[1];
    const void* wo = d_in[2];
    const void* w1 = d_in[4];
    const void* w3 = d_in[5];
    const void* w2 = d_in[6];
    CUtensorMap tx, tqkv, t1, t3, t1h, t3h, t2, t2h, two;
    make_map(enc, &tx, x, 2048, 512, 128, 64, CU_TENSOR_MAP_SWIZZLE_128B);
    make_map(enc, &tqkv, wqkv, 512, 1536, 64, 64, CU_TENSOR_MAP_SWIZZLE_128B);
    make_map(enc, &t1, w1, 512, 1792, 64, 64, CU_TENSOR_MAP_SWIZZLE_128B);
    make_map(enc, &t3, w3, 512, 1792, 64, 64, CU_TENSOR_MAP_SWIZZLE_128B);
    make_map(enc, &t1h, w1, 512, 1792, 64, 32, CU_TENSOR_MAP_SWIZZLE_64B);
    make_map(enc, &t3h, w3, 512, 1792, 64, 32, CU_TENSOR_MAP_SWIZZLE_64B);
    make_map(enc, &t2, w2, 1792, 512, 64, 64, CU_TENSOR_MAP_SWIZZLE_128B);
    make_map(enc, &t2h, w2, 1792, 512, 32, 64, CU_TENSOR_MAP_SWIZZLE_128B);
    make_map(enc, &two, wo, 512, 512, 64, 64, CU_TENSOR_MAP_SWIZZLE_128B);
    fused_kernel<<<128, 384, SMEM_BYTES>>>(tx, tqkv, t1, t3, t1h, t3h, t2, t2h, two, (const __nv_bfloat16*)x,
                                           (__nv_bfloat16*)d_out, (const char*)wqkv, (const char*)w1, (const char*)w3,
                                           (const char*)w2, (const char*)wo);
}
```

```cpp
#include <cuda_runtime.h>
#include <cuda_bf16.h>
#include <cuda.h>
#include <stdint.h>

namespace {

constexpr int NST = 13;
constexpr int STAGE_BYTES = 16384;
constexpr int XST0 = 5;
constexpr int SCR0 = 8;
constexpr int XCH0 = 3;
__host__ __device__ constexpr int p2_id(int i) {
    constexpr int t[18] = {0, 1, 2, 3, 8, 4, 5, 9, 10, 6, 11, 12, 7, 13, 14, 15, 16, 17};
    return t[i];
}
__host__ __device__ constexpr int p2_useB(int i) {
    constexpr int t[18] = {43, 45, 47, 49, 50, 52, 54, 55, 56, 58, 59, 60, 62, 63, 64, 65, 66, 67};
    return t[i];
}
constexpr int OFF_MISC = NST * STAGE_BYTES;
constexpr int OFF_KVFRAG = OFF_MISC;
constexpr int OFF_ONES = OFF_MISC + 3072;
constexpr int OFF_BARS = OFF_MISC + 3328;
constexpr int BAR_FULL = OFF_BARS;
constexpr int BAR_EMPTY = BAR_FULL + 8 * NST;
constexpr int BAR_XFULL = BAR_EMPTY + 8 * NST;
constexpr int BAR_KVREADY = BAR_XFULL + 64;
constexpr int BAR_XCHG = BAR_KVREADY + 8;
constexpr int BAR_EPOCH = BAR_XCHG + 8;
constexpr int BAR_XRDY = BAR_EPOCH + 8;
constexpr int OFF_EPOCH = BAR_XRDY + 8;
constexpr int OFF_ZERO = OFF_MISC + 4096;
constexpr int SMEM_BYTES = OFF_MISC + 8192;

constexpr unsigned SPIN_LIMIT = 1u << 24;

constexpr int A2_N = 16 * 2 * 18 * 4 * 256;
__device__ uint4 g_A2[2 * A2_N];
__device__ float4 g_kvacc[2 * 8 * 272];
__device__ unsigned g_kvcnt[8];
__constant__ unsigned char P2_ID[18] = {0, 1, 2, 3, 8, 4, 5, 9, 10, 6, 11, 12, 7, 13, 14, 15, 16, 17};
__device__ unsigned g_epoch;
__device__ unsigned g_ticket;

#define TS(role, i)
#define TSW(role, i)

__device__ __forceinline__ uint32_t smem_u32(const void* p) { return (uint32_t)__cvta_generic_to_shared(p); }
__device__ __forceinline__ void mbar_init(uint32_t bar, uint32_t cnt) {
    asm volatile("mbarrier.init.shared::cta.b64 [%0], %1;" ::"r"(bar), "r"(cnt) : "memory");
}
__device__ __forceinline__ void mbar_expect_tx(uint32_t bar, uint32_t bytes) {
    asm volatile("mbarrier.arrive.expect_tx.shared::cta.b64 _, [%0], %1;" ::"r"(bar), "r"(bytes) : "memory");
}
__device__ __forceinline__ void mbar_arrive(uint32_t bar) {
    asm volatile("mbarrier.arrive.shared::cta.b64 _, [%0];" ::"r"(bar) : "memory");
}
__device__ __forceinline__ void mbar_arrive_cta(uint32_t bar, uint32_t cta) {
    asm volatile(
        "{\n.reg .b32 ra;\nmapa.shared::cluster.u32 ra, %0, %1;\n"
        "mbarrier.arrive.shared::cluster.b64 _, [ra];\n}" ::"r"(bar), "r"(cta) : "memory");
}
__device__ __forceinline__ void mbar_wait(uint32_t bar, uint32_t parity) {
    asm volatile(
        "{\n.reg .pred p, q;\n.reg .u32 n;\nmov.u32 n, 0;\n"
        "WAIT_%=:\n"
        "mbarrier.try_wait.parity.shared::cta.b64 p, [%0], %1;\n"
        "@p bra.uni DONE_%=;\n"
        "add.u32 n, n, 1;\n"
        "setp.gt.u32 q, n, %2;\n"
        "@q trap;\n"
        "bra.uni WAIT_%=;\n"
        "DONE_%=:\n}"
        ::"r"(bar), "r"(parity), "n"(SPIN_LIMIT) : "memory");
}
__device__ __forceinline__ unsigned ld_acquire(const unsigned* p) {
    unsigned v;
    asm volatile("ld.acquire.gpu.global.u32 %0, [%1];" : "=r"(v) : "l"(p) : "memory");
    return v;
}
__device__ __forceinline__ void st_release(unsigned* p, unsigned v) {
    asm volatile("st.release.gpu.global.u32 [%0], %1;" ::"l"(p), "r"(v) : "memory");
}
__device__ __forceinline__ unsigned read_epoch() {
    return __shfl_sync(0xffffffffu, *(volatile unsigned*)&g_epoch, 0) + 1;
}
__device__ __forceinline__ void tma_load(uint32_t dst, const CUtensorMap* tm, uint32_t bar, int x, int y) {
    asm volatile(
        "cp.async.bulk.tensor.2d.shared::cluster.global.mbarrier::complete_tx::bytes [%0], [%1, {%3, %4}], [%2];"
        ::"r"(dst), "l"(tm), "r"(bar), "r"(x), "r"(y) : "memory");
}
__device__ __forceinline__ void tma_load_mc(uint32_t dst, const CUtensorMap* tm, uint32_t bar, int x, int y) {
    asm volatile(
        "cp.async.bulk.tensor.2d.shared::cluster.global.mbarrier::complete_tx::bytes.multicast::cluster "
        "[%0], [%1, {%3, %4}], [%2], %5;"
        ::"r"(dst), "l"(tm), "r"(bar), "r"(x), "r"(y), "h"((uint16_t)3) : "memory");
}
__device__ __forceinline__ void prefetch_tm(const CUtensorMap* tm) {
    asm volatile("prefetch.tensormap [%0];" ::"l"(tm) : "memory");
}
__device__ __forceinline__ void l2_prefetch(const void* p, uint32_t bytes) {
    asm volatile("cp.async.bulk.prefetch.L2.global [%0], %1;" ::"l"(p), "r"(bytes) : "memory");
}
__device__ __forceinline__ void bar_sync(int id, int n) { asm volatile("bar.sync %0, %1;" ::"r"(id), "r"(n) : "memory"); }
__device__ __forceinline__ void bar_arrive(int id, int n) { asm volatile("bar.arrive %0, %1;" ::"r"(id), "r"(n) : "memory"); }
__device__ __forceinline__ void wg_fence() { asm volatile("wgmma.fence.sync.aligned;" ::: "memory"); }
__device__ __forceinline__ void wg_commit() { asm volatile("wgmma.commit_group.sync.aligned;" ::: "memory"); }
template <int N>
__device__ __forceinline__ void wg_wait() { asm volatile("wgmma.wait_group.sync.aligned %0;" ::"n"(N) : "memory"); }

__device__ __forceinline__ uint64_t make_desc(uint32_t addr, uint32_t lbo, uint32_t sbo, uint64_t swz) {
    return (uint64_t)((addr & 0x3FFFF) >> 4) | ((uint64_t)(lbo >> 4) << 16) | ((uint64_t)(sbo >> 4) << 32) | (swz << 62);
}

#define ACC8(a, o) "+f"(a[o]), "+f"(a[o + 1]), "+f"(a[o + 2]), "+f"(a[o + 3]), "+f"(a[o + 4]), "+f"(a[o + 5]), "+f"(a[o + 6]), "+f"(a[o + 7])
constexpr uint32_t DHI128 = (1024u >> 4) | (1u << 30);
constexpr uint32_t DHI64 = (512u >> 4) | (2u << 30);
__device__ __forceinline__ void wgmma_n128_rs(float (&d)[64], const uint32_t* a, uint32_t db, int scale_d) {
    asm volatile(
        "{\n.reg .pred p;\n.reg .b64 dd;\nsetp.ne.b32 p, %69, 0;\nmov.b64 dd, {%68, %70};\n"
        "wgmma.mma_async.sync.aligned.m64n128k16.f32.bf16.bf16 "
        "{%0,%1,%2,%3,%4,%5,%6,%7,%8,%9,%10,%11,%12,%13,%14,%15,%16,%17,%18,%19,%20,%21,%22,%23,%24,%25,%26,%27,%28,%29,%30,%31,"
        "%32,%33,%34,%35,%36,%37,%38,%39,%40,%41,%42,%43,%44,%45,%46,%47,%48,%49,%50,%51,%52,%53,%54,%55,%56,%57,%58,%59,%60,%61,%62,%63},"
        "{%64,%65,%66,%67}, dd, p, 1, 1, 1;\n}"
        : ACC8(d, 0), ACC8(d, 8), ACC8(d, 16), ACC8(d, 24), ACC8(d, 32), ACC8(d, 40), ACC8(d, 48), ACC8(d, 56)
        : "r"(a[0]), "r"(a[1]), "r"(a[2]), "r"(a[3]), "r"(db), "r"(scale_d), "n"(DHI128));
}
template <uint32_t HI>
__device__ __forceinline__ void wgmma_n64_rs(float (&d)[32], const uint32_t* a, uint32_t db, int scale_d) {
    asm volatile(
        "{\n.reg .pred p;\n.reg .b64 dd;\nsetp.ne.b32 p, %37, 0;\nmov.b64 dd, {%36, %38};\n"
        "wgmma.mma_async.sync.aligned.m64n64k16.f32.bf16.bf16 "
        "{%0,%1,%2,%3,%4,%5,%6,%7,%8,%9,%10,%11,%12,%13,%14,%15,%16,%17,%18,%19,%20,%21,%22,%23,%24,%25,%26,%27,%28,%29,%30,%31},"
        "{%32,%33,%34,%35}, dd, p, 1, 1, 1;\n}"
        : ACC8(d, 0), ACC8(d, 8), ACC8(d, 16), ACC8(d, 24)
        : "r"(a[0]), "r"(a[1]), "r"(a[2]), "r"(a[3]), "r"(db), "r"(scale_d), "n"(HI));
}
__device__ __forceinline__ void wgmma_n64_ss_tt(float (&d)[32], uint64_t da, uint64_t db, int scale_d) {
    asm volatile(
        "{\n.reg .pred p;\nsetp.ne.b32 p, %34, 0;\n"
        "wgmma.mma_async.sync.aligned.m64n64k16.f32.bf16.bf16 "
        "{%0,%1,%2,%3,%4,%5,%6,%7,%8,%9,%10,%11,%12,%13,%14,%15,%16,%17,%18,%19,%20,%21,%22,%23,%24,%25,%26,%27,%28,%29,%30,%31},"
        "%32, %33, p, 1, 1, 1, 1;\n}"
        : ACC8(d, 0), ACC8(d, 8), ACC8(d, 16), ACC8(d, 24)
        : "l"(da), "l"(db), "r"(scale_d));
}
__device__ __forceinline__ void wgmma_n8_ss_tn(float (&d)[4], uint64_t da, uint64_t db, int scale_d) {
    asm volatile(
        "{\n.reg .pred p;\nsetp.ne.b32 p, %6, 0;\n"
        "wgmma.mma_async.sync.aligned.m64n8k16.f32.bf16.bf16 {%0,%1,%2,%3}, %4, %5, p, 1, 1, 1, 0;\n}"
        : "+f"(d[0]), "+f"(d[1]), "+f"(d[2]), "+f"(d[3])
        : "l"(da), "l"(db), "r"(scale_d));
}
template <int N>
__device__ __forceinline__ void acc_fence(float (&d)[N]) {
#pragma unroll
    for (int i = 0; i < N; i++) asm volatile("" : "+f"(d[i])::"memory");
}
__device__ __forceinline__ void mma16816(float (&c)[4], const uint32_t* a, uint32_t b0, uint32_t b1) {
    asm volatile(
        "mma.sync.aligned.m16n8k16.row.col.f32.bf16.bf16.f32 {%0,%1,%2,%3}, {%4,%5,%6,%7}, {%8,%9}, {%0,%1,%2,%3};"
        : "+f"(c[0]), "+f"(c[1]), "+f"(c[2]), "+f"(c[3])
        : "r"(a[0]), "r"(a[1]), "r"(a[2]), "r"(a[3]), "r"(b0), "r"(b1));
}
__device__ __forceinline__ uint32_t pack_bf16(float lo, float hi) {
    uint32_t r;
    asm("cvt.rn.bf16x2.f32 %0, %1, %2;" : "=r"(r) : "f"(hi), "f"(lo));
    return r;
}
__device__ __forceinline__ float bf_lo(uint32_t v) { return __uint_as_float(v << 16); }
__device__ __forceinline__ float bf_hi(uint32_t v) { return __uint_as_float(v & 0xffff0000u); }
__device__ __forceinline__ float bf16_round(float v) { return __bfloat162float(__float2bfloat16_rn(v)); }
__device__ __forceinline__ float sqrt_fast(float v) {
    float r;
    asm("sqrt.approx.ftz.f32 %0, %1;" : "=f"(r) : "f"(v));
    return r;
}
__device__ __forceinline__ float rcp_fast(float v) {
    float r;
    asm("rcp.approx.ftz.f32 %0, %1;" : "=f"(r) : "f"(v));
    return r;
}
__device__ __forceinline__ float ex2_fast(float v) {
    float r;
    asm("ex2.approx.ftz.f32 %0, %1;" : "=f"(r) : "f"(v));
    return r;
}
__device__ __forceinline__ int fresh_tid() {
    int v;
    asm volatile("mov.u32 %0, %%tid.x;" : "=r"(v));
    return v;
}
__device__ __forceinline__ int fresh_bid() {
    int v;
    asm volatile("mov.u32 %0, %%ctaid.x;" : "=r"(v));
    return v;
}
struct RowScale { float rho, rl, var; };
__device__ __forceinline__ RowScale row_scale(float sd) {
    asm volatile("" : "+f"(sd));
    RowScale r;
    r.rho = rcp_fast(sd);
    r.rl = r.rho * 1.4426950408889634f;
    r.var = sd * sd;
    return r;
}
__device__ __forceinline__ uint4* a2_write_ptr(const uint8_t* smem) {
    const int bid = fresh_bid();
    const unsigned par = *(volatile const unsigned*)(smem + OFF_EPOCH) & 1;
    return g_A2 + (size_t)par * A2_N + (size_t)(((bid >> 3) * 2 + ((bid >> 2) & 1)) * 18) * 4 * 256 + fresh_tid();
}
__device__ __forceinline__ float phi_f(float a, const RowScale& r) {
    return fmaf(fmaxf(a, 0.f), r.rho, ex2_fast(fminf(a, 0.f) * r.rl) + 1e-6f);
}
__device__ __forceinline__ float swiglu_f(float ga, float ua, const RowScale& r) {
    return (ga * ua) * rcp_fast(fmaf(ex2_fast(-ga * r.rl), r.var, r.var));
}
__device__ __forceinline__ uint4 swiglu8(const float* gp, const float* up, const RowScale& r0, const RowScale& r1) {
    uint4 v;
    v.x = pack_bf16(swiglu_f(gp[0], up[0], r0), swiglu_f(gp[1], up[1], r0));
    v.y = pack_bf16(swiglu_f(gp[2], up[2], r1), swiglu_f(gp[3], up[3], r1));
    v.z = pack_bf16(swiglu_f(gp[4], up[4], r0), swiglu_f(gp[5], up[5], r0));
    v.w = pack_bf16(swiglu_f(gp[6], up[6], r1), swiglu_f(gp[7], up[7], r1));
    v.y = v.y ? v.y : 0x8000u;
    v.w = v.w ? v.w : 0x8000u;
    return v;
}
__device__ __forceinline__ bool frag_stale(const uint4 (&f)[12]) {
    unsigned v = min(f[0].y, f[0].w);
#pragma unroll
    for (int i = 1; i < 12; i++) v = min(v, min(f[i].y, f[i].w));
    return __any_sync(0xffffffffu, v == 0u);
}
__device__ __forceinline__ void st_frag(uint4* p, uint4 v) {
    asm volatile("st.relaxed.gpu.global.v4.u32 [%0], {%1,%2,%3,%4};" ::"l"(p), "r"(v.x), "r"(v.y), "r"(v.z), "r"(v.w) : "memory");
}
__device__ __forceinline__ uint4 ld_frag(const uint4* p) {
    uint4 v;
    asm volatile("ld.relaxed.gpu.global.v4.u32 {%0,%1,%2,%3}, [%4];" : "=r"(v.x), "=r"(v.y), "=r"(v.z), "=r"(v.w) : "l"(p) : "memory");
    return v;
}
__device__ __forceinline__ void red_add2(float* p, float a, float b) {
    asm volatile("red.global.add.v2.f32 [%0], {%1, %2};" ::"l"(p), "f"(a), "f"(b) : "memory");
}
__device__ __forceinline__ void cp_async16(uint32_t dst, const void* src) {
    asm volatile("cp.async.cg.shared.global [%0], [%1], 16;" ::"r"(dst), "l"(src) : "memory");
}

__host__ __device__ constexpr int ring_lap(int u) { return (u * 79) >> 10; }
__host__ __device__ constexpr int ring_slot(int u) { return u - NST * ring_lap(u); }

__device__ __forceinline__ void mainloop128(float (&acc)[64], const uint32_t (&xa)[128], int u0, uint32_t sb,
                                            uint32_t desc128, int lane, int wg, bool last = false) {
    bar_sync(7 + wg, 256);
#pragma unroll
    for (int kb = 0; kb < 8; kb++) {
        const int st = ring_slot(u0 + kb);
        mbar_wait(sb + BAR_FULL + 8 * st, ring_lap(u0 + kb) & 1);
        wg_fence();
        const uint32_t d = desc128 + st * (STAGE_BYTES >> 4);
#pragma unroll
        for (int ks = 0; ks < 4; ks++) wgmma_n128_rs(acc, &xa[(kb * 4 + ks) * 4], d + ks * 128, (kb | ks) != 0);
        wg_commit();
        if (kb == 7 && !(last && wg == 1)) bar_arrive(8 - wg, 256);
        if (kb > 0) {
            wg_wait<1>();
            if (lane == 0) mbar_arrive(sb + BAR_EMPTY + 8 * ring_slot(u0 + kb - 1));
        }
    }
    wg_wait<0>();
    acc_fence(acc);
    if (lane == 0) mbar_arrive(sb + BAR_EMPTY + 8 * ring_slot(u0 + 7));
}
__device__ __forceinline__ void mainloop64x2(float (&a0)[32], float (&a1)[32], const uint32_t (&xa)[128], int u0,
                                             uint32_t sb, uint32_t desc128, int lane, int wg) {
    bar_sync(7 + wg, 256);
#pragma unroll
    for (int kb = 0; kb < 8; kb++) {
        const int st = ring_slot(u0 + kb);
        mbar_wait(sb + BAR_FULL + 8 * st, ring_lap(u0 + kb) & 1);
        wg_fence();
        const uint32_t d = desc128 + st * (STAGE_BYTES >> 4);
        const uint32_t d2 = d + (8192 >> 4) - ((4096u >> 4) << 16);
#pragma unroll
        for (int ks = 0; ks < 4; ks++) {
            wgmma_n64_rs<DHI128>(a0, &xa[(kb * 4 + ks) * 4], d + ks * 128, (kb | ks) != 0);
            wgmma_n64_rs<DHI64>(a1, &xa[(kb * 4 + ks) * 4], d2 + ks * 64, (kb | ks) != 0);
        }
        wg_commit();
        if (kb == 7) bar_arrive(8 - wg, 256);
        if (kb > 0) {
            wg_wait<1>();
            if (lane == 0) mbar_arrive(sb + BAR_EMPTY + 8 * ring_slot(u0 + kb - 1));
        }
    }
    wg_wait<0>();
    acc_fence(a0);
    acc_fence(a1);
    if (lane == 0) mbar_arrive(sb + BAR_EMPTY + 8 * ring_slot(u0 + 7));
}

__global__ void __cluster_dims__(2, 1, 1) __launch_bounds__(384, 1)
fused_kernel(const __grid_constant__ CUtensorMap tm_x, const __grid_constant__ CUtensorMap tm_qkv,
             const __grid_constant__ CUtensorMap tm_w1, const __grid_constant__ CUtensorMap tm_w3,
             const __grid_constant__ CUtensorMap tm_w1h, const __grid_constant__ CUtensorMap tm_w3h,
             const __grid_constant__ CUtensorMap tm_w2, const __grid_constant__ CUtensorMap tm_w2h,
             const __grid_constant__ CUtensorMap tm_wo, const __nv_bfloat16* __restrict__ xg,
             __nv_bfloat16* __restrict__ outg, const char* __restrict__ p_qkv, const char* __restrict__ p_w1,
             const char* __restrict__ p_w3, const char* __restrict__ p_w2, const char* __restrict__ p_wo) {
    extern __shared__ __align__(1024) uint8_t smem[];
    const uint32_t sb = smem_u32(smem);
    const int tid = threadIdx.x;
    const int warp = tid >> 5, lane = tid & 31;
    const int rank = blockIdx.x & 1;
    const int pair = blockIdx.x >> 1;
    const int m = pair >> 2;
    const int j2 = pair & 3;
    const int c = 2 * j2 + rank;
    const int m2 = m;

    TS(tid >> 7, 0);
    if (tid == 256) {
        prefetch_tm(&tm_x);
#pragma unroll
        for (int i = 0; i < 8; i++) mbar_init(sb + BAR_XFULL + 8 * i, 1);
#pragma unroll
        for (int kb = 0; kb < 8; kb++) mbar_expect_tx(sb + BAR_XFULL + 8 * kb, 16384);
        asm volatile("fence.mbarrier_init.release.cluster;" ::: "memory");
        TS(2, 21);
    } else if (tid == 0) {
#pragma unroll
        for (int i = 0; i < NST; i++) mbar_init(sb + BAR_FULL + 8 * i, 1);
        asm volatile("fence.mbarrier_init.release.cluster;" ::: "memory");
    } else if (tid == 32) {
#pragma unroll
        for (int i = 0; i < NST; i++) mbar_init(sb + BAR_EMPTY + 8 * i, 8);
        asm volatile("fence.mbarrier_init.release.cluster;" ::: "memory");
    } else if (tid == 64) {
#pragma unroll
        for (int i = 0; i < 4; i++) mbar_init(sb + BAR_KVREADY + 8 * i, 1);
        mbar_expect_tx(sb + BAR_XCHG, 32768);
        asm volatile("fence.mbarrier_init.release.cluster;" ::: "memory");
    } else if (tid >= 128 && tid < 256) {
        ((uint4*)(smem + OFF_ZERO))[tid - 128] = make_uint4(0, 0, 0, 0);
        ((uint4*)(smem + OFF_ZERO))[tid] = make_uint4(0, 0, 0, 0);
        asm volatile("fence.proxy.async.shared::cta;" ::: "memory");
    } else if (tid == 288) {
        prefetch_tm(&tm_qkv);
        prefetch_tm(&tm_w1);
        prefetch_tm(&tm_w3);
        prefetch_tm(&tm_w1h);
        prefetch_tm(&tm_w3h);
        prefetch_tm(&tm_w2);
        prefetch_tm(&tm_w2h);
        prefetch_tm(&tm_wo);
    } else if (tid >= 320) {
        ((uint32_t*)(smem + OFF_ONES))[tid - 320] = 0x3F803F80u;
        asm volatile("fence.proxy.async.shared::cta;" ::: "memory");
    }
    __syncthreads();
    TS(tid >> 7, 22);
    asm volatile("barrier.cluster.arrive.relaxed.aligned;\nbarrier.cluster.wait.acquire.aligned;" ::: "memory");

    if (warp >= 8) {
        asm volatile("setmaxnreg.dec.sync.aligned.u32 40;");
        if (warp == 8) {
            if (lane == 0) {
                int st = 0;
                uint32_t lap = 0;
                unsigned par = 0;
                char* zdst = nullptr;
#pragma unroll
                for (int i = 0; i < 4; i++) {
                    const int kb = 2 * i + rank;
                    tma_load_mc(sb + (XST0 + kb) * STAGE_BYTES, &tm_x, sb + BAR_XFULL + 8 * kb, kb * 64, m * 128);
                }
                for (int it = 0; it < 40; it++) {
                    const int tile = it >> 3, kb = it & 7;
                    const uint32_t full = sb + BAR_FULL + 8 * st;
                    mbar_wait(sb + BAR_EMPTY + 8 * st, (st >= XST0) ? (lap & 1) : ((lap & 1) ^ 1));
                    mbar_expect_tx(full, STAGE_BYTES);
                    const uint32_t dst = sb + st * STAGE_BYTES;
                    if (tile == 0) {
                        tma_load(dst, &tm_qkv, full, 512 + 64 * c, kb * 64);
                        tma_load(dst + 8192, &tm_qkv, full, 1024 + 64 * c, kb * 64);
                    } else if (tile != 3) {
                        const int col = 224 * c + 64 * (tile == 4 ? 2 : tile - 1);
                        tma_load(dst, &tm_w1, full, col, kb * 64);
                        tma_load(dst + 8192, &tm_w3, full, col, kb * 64);
                    } else {
                        tma_load(dst, &tm_qkv, full, 64 * c, kb * 64);
                        tma_load(dst + 8192, &tm_w1h, full, 224 * c + 192, kb * 64);
                        tma_load(dst + 12288, &tm_w3h, full, 224 * c + 192, kb * 64);
                    }
                    if (++st == NST) { st = 0; lap++; }
                    if (it == 7) {
                        mbar_wait(sb + BAR_EPOCH, 0);
                        par = *(volatile unsigned*)(smem + OFF_EPOCH) & 1;
                        zdst = (char*)(g_A2 + (size_t)(par ^ 1) * A2_N + (size_t)((m * 2 + (c >> 2)) * 18) * 4 * 256);
                        mbar_wait(sb + BAR_EMPTY + 8 * SCR0, 0);
                        mbar_arrive(sb + BAR_FULL + 8 * SCR0);
                        mbar_wait(sb + BAR_EMPTY + 8 * (SCR0 + 1), 0);
                        mbar_arrive(sb + BAR_FULL + 8 * (SCR0 + 1));
                        st += 2;
                    }
                }
                TS(2, 1);
                const char* a2b = (const char*)(g_A2 + (size_t)par * A2_N + (size_t)((m2 * 2 + rank) * 18) * 4 * 256);
#pragma unroll 1
                for (int i = 0; i < 18; i++) {
                    const int b = P2_ID[i];
                    if (b < 8) {
                        mbar_wait(sb + BAR_EMPTY + 8 * st, (st >= XST0) ? (lap & 1) : ((lap & 1) ^ 1));
                        mbar_expect_tx(sb + BAR_FULL + 8 * st, STAGE_BYTES);
                        asm volatile("cp.async.bulk.shared::cluster.global.mbarrier::complete_tx::bytes [%0], [%1], 16384, [%2];"
                                     ::"r"(sb + st * STAGE_BYTES), "l"(a2b + b * 16384), "r"(sb + BAR_FULL + 8 * st) : "memory");
                        if (++st == NST) { st = 0; lap++; }
                    }
                    const uint32_t full = sb + BAR_FULL + 8 * st;
                    const uint32_t dst = sb + st * STAGE_BYTES;
                    mbar_wait(sb + BAR_EMPTY + 8 * st, (st >= XST0) ? (lap & 1) : ((lap & 1) ^ 1));
                    mbar_expect_tx(full, STAGE_BYTES);
                    if (b < 8 || b >= 14) {
                        const int row = (b < 8) ? 224 * (4 * rank + (b & 3)) + 64 * (b >> 2) : 224 * (4 * rank + b - 14) + 128;
                        tma_load(dst, &tm_w2, full, 128 * j2, row);
                        tma_load(dst + 8192, &tm_w2, full, 128 * j2 + 64, row);
                    } else if (b < 10) {
                        const int row = 224 * (4 * rank + 2 * (b - 8)) + 192;
                        tma_load(dst, &tm_w2h, full, 128 * j2, row);
                        tma_load(dst + 4096, &tm_w2h, full, 128 * j2, row + 224);
                        tma_load(dst + 8192, &tm_w2h, full, 128 * j2 + 64, row);
                        tma_load(dst + 12288, &tm_w2h, full, 128 * j2 + 64, row + 224);
                    } else {
                        const int row = 64 * (4 * rank + (b - 10));
                        tma_load(dst, &tm_wo, full, 128 * j2, row);
                        tma_load(dst + 8192, &tm_wo, full, 128 * j2 + 64, row);
                    }
                    TS(2, 2 + i);
                    if (++st == NST) { st = 0; lap++; }
                }
                mbar_wait(sb + BAR_EMPTY + 8 * XCH0, (lap & 1) ^ 1);
                mbar_wait(sb + BAR_EMPTY + 8 * (XCH0 + 1), (lap & 1) ^ 1);
                mbar_arrive_cta(sb + BAR_XRDY, rank ^ 1);
#pragma unroll 1
                for (int i = 0; i < 18; i++) {
                    const int cc = c & 3;
                    const int blk = (i < 8) ? ((i >> 2) * 4 + cc) * 4 + (i & 3)
                                  : (i < 10) ? (8 + (cc >> 1)) * 4 + 2 * (cc & 1) + (i - 8)
                                  : (i < 14) ? (10 + cc) * 4 + (i - 10) : (14 + cc) * 4 + (i - 14);
                    asm volatile("cp.async.bulk.global.shared::cta.bulk_group [%0], [%1], 4096;"
                                 ::"l"(zdst + (size_t)blk * 4096), "r"(sb + OFF_ZERO) : "memory");
                }
                asm volatile("cp.async.bulk.commit_group;" ::: "memory");
                asm volatile("cp.async.bulk.wait_group 0;" ::: "memory");
                TS(2, 20);
            }
        } else if (warp < 11) {
            const int wg = warp - 9;
            bar_sync(3 + wg, 160);
            if (lane == 0) asm volatile("red.release.gpu.global.add.u32 [%0], 1;" ::"l"(&g_kvcnt[c]) : "memory");
            TSW(3, wg);
        } else {
            const unsigned epoch = read_epoch();
            if (lane == 0) {
                const unsigned tk = atomicInc(&g_ticket, 127u);
                if (tk == 127u) *(volatile unsigned*)&g_epoch = epoch;
            }
            if (lane == 0) *(volatile unsigned*)(smem + OFF_EPOCH) = epoch;
            __syncwarp();
            if (lane == 0) mbar_arrive(sb + BAR_EPOCH);
            if (lane < 17) g_kvacc[(((epoch & 1) ^ 1) * 8 + c) * 272 + 17 * m + lane] = make_float4(0.f, 0.f, 0.f, 0.f);
            {
                unsigned n = 0;
                while ((int)(ld_acquire(&g_kvcnt[c]) - 32u * epoch) < 0) {
                    __nanosleep(200);
                    if (++n > SPIN_LIMIT) asm volatile("trap;");
                }
            }
            TSW(4, 0);
            const int g = lane >> 2, t = lane & 3;
            const float* ks = (const float*)(g_kvacc + ((epoch & 1) * 8 + c) * 272) + 32 * t + g;
            uint2* kf = (uint2*)(smem + OFF_KVFRAG) + lane;
#pragma unroll 2
            for (int hh = 0; hh < 4; hh++) {
                const float* k = ks + hh * 272;
                const float a0 = __ldcg(k), a1 = __ldcg(k + 16), a2 = __ldcg(k + 128), a3 = __ldcg(k + 144);
                const float b0 = __ldcg(k + 8), b1 = __ldcg(k + 24), b2 = __ldcg(k + 136), b3 = __ldcg(k + 152);
                const float2 z0 = __ldcg((const float2*)(k - g - 30 * t + 256)), z1 = __ldcg((const float2*)(k - g - 30 * t + 264));
                kf[(hh * 3 + 0) * 32] = make_uint2(pack_bf16(a0, a1), pack_bf16(a2, a3));
                kf[(hh * 3 + 1) * 32] = make_uint2(pack_bf16(b0, b1), pack_bf16(b2, b3));
                kf[(hh * 3 + 2) * 32] = make_uint2(pack_bf16(z0.x, z0.y), pack_bf16(z1.x, z1.y));
            }
            __syncwarp();
            if (lane == 0) mbar_arrive(sb + BAR_KVREADY);
            TSW(4, 4);
        }
    } else {
        asm volatile("setmaxnreg.inc.sync.aligned.u32 232;");
        const int wg = warp >> 2, w = warp & 3;
        const int g = lane >> 2, t = lane & 3;
        float acc[64];
        uint32_t xa[128];
        float sd0, sd1;

        TS(wg, 1);
        {
            const int row = wg * 64 + w * 16 + (lane & 7) + ((lane >> 3) & 1) * 8;
            const uint32_t rbase = sb + XST0 * STAGE_BYTES + row * 128;
            const int hi = lane >> 4, r7 = lane & 7;
            float sm[2][4], c0[2][4], c1[2][4];
#pragma unroll
            for (int i = 0; i < 8; i++) { sm[i >> 2][i & 3] = 0.f; c0[i >> 2][i & 3] = 0.f; c1[i >> 2][i & 3] = 0.f; }
            if (wg == 1) bar_arrive(7, 256);
#pragma unroll
            for (int kb = 0; kb < 8; kb++) {
                mbar_wait(sb + BAR_XFULL + 8 * kb, 0);
#pragma unroll
                for (int ks = 0; ks < 4; ks++) {
                    uint32_t* a = &xa[(kb * 4 + ks) * 4];
                    const uint32_t addr = rbase + kb * STAGE_BYTES + (((2 * ks + hi) ^ r7) << 4);
                    asm volatile("ldmatrix.sync.aligned.m8n8.x4.shared.b16 {%0,%1,%2,%3}, [%4];"
                                 : "=r"(a[0]), "=r"(a[1]), "=r"(a[2]), "=r"(a[3]) : "r"(addr) : "memory");
                    mma16816(sm[ks & 1], a, 0x3F803F80u, 0x3F803F80u);
                    mma16816(c0[ks & 1], a, a[0], a[2]);
                    mma16816(c1[ks & 1], a, a[1], a[3]);
                }
            }
            TS(wg, 2);
            const float mean0 = (sm[0][0] + sm[1][0]) * (1.f / 512.f);
            const float mean1 = (sm[0][2] + sm[1][2]) * (1.f / 512.f);
            __syncwarp();
            if (lane < 8) mbar_arrive(sb + BAR_EMPTY + 8 * (XST0 + lane));
            const __nv_bfloat162 mb0 = __float2bfloat162_rn(mean0), mb1 = __float2bfloat162_rn(mean1);
#pragma unroll
            for (int i = 0; i < 128; i++) {
                __nv_bfloat162 v = *reinterpret_cast<__nv_bfloat162*>(&xa[i]);
                v = __hsub2(v, (i & 1) ? mb1 : mb0);
                xa[i] = *reinterpret_cast<uint32_t*>(&v);
            }
            const float d0 = (g & 1) ? c0[0][1] + c0[1][1] : c0[0][0] + c0[1][0];
            const float d1 = (g & 1) ? c1[0][3] + c1[1][3] : c1[0][2] + c1[1][2];
            const int src = (lane & ~3) | (g >> 1);
            const float var0 = fmaxf(__shfl_sync(0xffffffffu, d0, src) * (1.f / 512.f) - mean0 * mean0, 0.f);
            const float var1 = fmaxf(__shfl_sync(0xffffffffu, d1, src) * (1.f / 512.f) - mean1 * mean1, 0.f);
            sd0 = bf16_round(sqrt_fast(bf16_round(bf16_round(var0) + 1e-5f)));
            sd1 = bf16_round(sqrt_fast(bf16_round(bf16_round(var1) + 1e-5f)));
        }

        TS(wg, 3);
        const uint32_t desc128 = ((sb & 0x3FFFF) >> 4) | ((8192u >> 4) << 16);

        {
            mainloop128(acc, xa, 0, sb, desc128, lane, wg);
            TS(wg, 4);
            {
                TS(wg, 24);
                const RowScale r0 = row_scale(sd0), r1 = row_scale(sd1);
                const float rho0 = r0.rho, rho1 = r1.rho;
                const uint32_t pkb = sb + (SCR0 + wg) * STAGE_BYTES;
                mbar_wait(sb + BAR_FULL + 8 * (SCR0 + wg), 0);
                const uint32_t ra = pkb + (w * 16 + g) * 128 + t * 4;
#pragma unroll
                for (int nb = 0; nb < 8; nb++) {
                    const uint32_t off = (uint32_t)((nb ^ g) << 4);
                    uint32_t p0 = pack_bf16(phi_f(acc[nb * 4], r0), phi_f(acc[nb * 4 + 1], r0));
                    uint32_t p1 = pack_bf16(phi_f(acc[nb * 4 + 2], r1), phi_f(acc[nb * 4 + 3], r1));
                    uint32_t v0 = pack_bf16(acc[32 + nb * 4] * rho0, acc[32 + nb * 4 + 1] * rho0);
                    uint32_t v1 = pack_bf16(acc[32 + nb * 4 + 2] * rho1, acc[32 + nb * 4 + 3] * rho1);
                    asm volatile("st.shared.u32 [%0], %1;" ::"r"(ra + off), "r"(p0) : "memory");
                    asm volatile("st.shared.u32 [%0], %1;" ::"r"(ra + off + 1024), "r"(p1) : "memory");
                    asm volatile("st.shared.u32 [%0], %1;" ::"r"(ra + off + 8192), "r"(v0) : "memory");
                    asm volatile("st.shared.u32 [%0], %1;" ::"r"(ra + off + 8192 + 1024), "r"(v1) : "memory");
                }
                TS(wg, 25);
                asm volatile("fence.proxy.async.shared::cta;" ::: "memory");
                bar_sync(1 + wg, 128);
                TS(wg, 26);
                const uint64_t da = make_desc(pkb, 8192, 1024, 1);
                const uint64_t db = make_desc(pkb + 8192, 8192, 1024, 1);
                const uint64_t d1 = make_desc(sb + OFF_ONES, 128, 128, 0);
                float kva[32], za[4];
                wg_fence();
#pragma unroll
                for (int ks = 0; ks < 4; ks++) {
                    wgmma_n64_ss_tt(kva, da + ks * 128, db + ks * 128, ks != 0);
                    wgmma_n8_ss_tn(za, da + ks * 128, d1, ks != 0);
                }
                wg_commit();
                wg_wait<0>();
                acc_fence(kva);
                acc_fence(za);
                if (lane < 2) mbar_arrive(sb + BAR_EMPTY + 8 * (SCR0 + lane));
                TS(wg, 27);
                float o[8];
#pragma unroll
                for (int i = 0; i < 8; i++)
                    o[i] = (w == 0) ? kva[i] : (w == 1) ? kva[8 + i] : (w == 2) ? kva[16 + i] : kva[24 + i];
                mbar_wait(sb + BAR_EPOCH, 0);
                const unsigned par = *(volatile unsigned*)(smem + OFF_EPOCH) & 1;
                float* dst = (float*)(g_kvacc + (par * 8 + c) * 272) + w * 272 + g * 16 + 2 * t;
                red_add2(dst, o[0], o[1]);
                red_add2(dst + 128, o[2], o[3]);
                red_add2(dst + 8, o[4], o[5]);
                red_add2(dst + 136, o[6], o[7]);
                if (t == 0) {
                    atomicAdd(dst - g * 15 + 256, za[0]);
                    atomicAdd(dst - g * 15 + 264, za[2]);
                }
            }
            bar_arrive(3 + wg, 160);
            TS(wg, 5);
        }
#pragma unroll
        for (int tile = 1; tile < 3; tile++) {
            mainloop128(acc, xa, 2 + 8 * tile, sb, desc128, lane, wg);
            TS(wg, 4 + 2 * tile);
            const RowScale r0 = row_scale(sd0), r1 = row_scale(sd1);
            uint4* dst = a2_write_ptr(smem) + (size_t)((4 * (tile - 1) + (fresh_bid() & 3)) * 4) * 256;
#pragma unroll
            for (int ks = 0; ks < 4; ks++) st_frag(dst + ks * 256, swiglu8(&acc[ks * 8], &acc[32 + ks * 8], r0, r1));
            TS(wg, 5 + 2 * tile);
        }
        {
            float qa[32], gu[32];
            mainloop64x2(qa, gu, xa, 26, sb, desc128, lane, wg);
            TS(wg, 10);
            const RowScale r0 = row_scale(sd0), r1 = row_scale(sd1);
            uint4* const a2w = a2_write_ptr(smem);
            const int cc = fresh_bid() & 3;
            uint4* dst = a2w + (size_t)((8 + (cc >> 1)) * 4 + 2 * (cc & 1)) * 256;
#pragma unroll
            for (int ks = 0; ks < 2; ks++) st_frag(dst + ks * 256, swiglu8(&gu[ks * 8], &gu[16 + ks * 8], r0, r1));
            TS(wg, 13);
            mbar_wait(sb + BAR_KVREADY, 0);
            TS(wg, 14);
            const uint2* kf = (const uint2*)(smem + OFF_KVFRAG);
            dst = a2w + (size_t)((10 + cc) * 4) * 256;
#pragma unroll
            for (int hh = 0; hh < 4; hh++) {
                const float* q = &qa[hh * 8];
                uint32_t a[4];
                a[0] = pack_bf16(phi_f(q[0], r0), phi_f(q[1], r0));
                a[1] = pack_bf16(phi_f(q[2], r1), phi_f(q[3], r1));
                a[2] = pack_bf16(phi_f(q[4], r0), phi_f(q[5], r0));
                a[3] = pack_bf16(phi_f(q[6], r1), phi_f(q[7], r1));
                float n0[4] = {0.f, 0.f, 0.f, 0.f}, n1[4] = {0.f, 0.f, 0.f, 0.f}, dn[4] = {0.f, 0.f, 0.f, 0.f};
                const uint2 b0 = kf[(hh * 3 + 0) * 32 + lane], b1 = kf[(hh * 3 + 1) * 32 + lane],
                            bz = kf[(hh * 3 + 2) * 32 + lane];
                mma16816(n0, a, b0.x, b0.y);
                mma16816(n1, a, b1.x, b1.y);
                mma16816(dn, a, bz.x, bz.y);
                const float i0 = rcp_fast(dn[0] + 1e-6f), i1 = rcp_fast(dn[2] + 1e-6f);
                uint4 v;
                v.x = pack_bf16(n0[0] * i0, n0[1] * i0);
                v.y = pack_bf16(n0[2] * i1, n0[3] * i1);
                v.z = pack_bf16(n1[0] * i0, n1[1] * i0);
                v.w = pack_bf16(n1[2] * i1, n1[3] * i1);
                v.y = v.y ? v.y : 0x8000u;
                v.w = v.w ? v.w : 0x8000u;
                st_frag(dst + hh * 256, v);
            }
            TS(wg, 11);
        }
        uint4 af[2][12];
        {
            mainloop128(acc, xa, 34, sb, desc128, lane, wg);
            TS(wg, 12);
            const RowScale r0 = row_scale(sd0), r1 = row_scale(sd1);
            uint4* dst = a2_write_ptr(smem) + (size_t)((14 + (fresh_bid() & 3)) * 4) * 256;
#pragma unroll
            for (int ks = 0; ks < 4; ks++) st_frag(dst + ks * 256, swiglu8(&acc[ks * 8], &acc[32 + ks * 8], r0, r1));
            TS(wg, 15);
        }

        {
            const int tid = fresh_tid(), bid = fresh_bid();
            const int lane = tid & 31, w = (tid >> 5) & 3, g = lane >> 2, t = lane & 3;
            const int rank = bid & 1, m2 = bid >> 3, j2 = (bid >> 1) & 3;
            const uint4* a2r = g_A2 + (size_t)(*(volatile unsigned*)(smem + OFF_EPOCH) & 1) * A2_N +
                               (size_t)((m2 * 2 + rank) * 18) * 4 * 256 + tid;
            float ao[32], ap[32];
            const uint32_t dso = desc128 + rank * 512, dsp = desc128 + (rank ^ 1) * 512;
            TS(wg, 16);
#pragma unroll
            for (int gi = 0; gi < 6; gi++) {
                if (gi == 5) TS(wg, 17);
                uint4(&f)[12] = af[gi & 1];
#pragma unroll
                for (int bb = 0; bb < 3; bb++) {
                    const int ub = p2_useB(gi * 3 + bb);
                    if (p2_id(gi * 3 + bb) < 8) {
                        mbar_wait(sb + BAR_FULL + 8 * ring_slot(ub - 1), ring_lap(ub - 1) & 1);
                        const uint4* src = (const uint4*)(smem + ring_slot(ub - 1) * STAGE_BYTES) + tid;
#pragma unroll
                        for (int ks = 0; ks < 4; ks++) f[bb * 4 + ks] = src[ks * 256];
                    }
                    mbar_wait(sb + BAR_FULL + 8 * ring_slot(ub), ring_lap(ub) & 1);
                }
                {
                    unsigned n = 0;
                    while (frag_stale(f)) {
#pragma unroll
                        for (int i = 0; i < 12; i++) f[i] = ld_frag(a2r + (p2_id(gi * 3 + (i >> 2)) * 4 + (i & 3)) * 256);
                        if (++n > SPIN_LIMIT) asm volatile("trap;");
                    }
                }
                if (gi == 0 && lane < 3) mbar_arrive(sb + BAR_EMPTY + 8 * ring_slot(42 + 2 * lane));
                if (gi == 1 && lane < 2) mbar_arrive(sb + BAR_EMPTY + 8 * ring_slot(48 + 3 * lane));
                if (gi == 2 && lane == 0) mbar_arrive(sb + BAR_EMPTY + 8 * ring_slot(53));
                bar_sync(7 + wg, 256);
                wg_fence();
#pragma unroll
                for (int i = 0; i < 12; i++) {
                    const uint32_t so = ring_slot(p2_useB(gi * 3 + (i >> 2))) * (STAGE_BYTES >> 4) + (i & 3) * 128;
                    const uint32_t* a = reinterpret_cast<const uint32_t*>(&f[i]);
                    wgmma_n64_rs<DHI128>(ap, a, dsp + so, (gi | i) != 0);
                    if (gi < 5) wgmma_n64_rs<DHI128>(ao, a, dso + so, (gi | i) != 0);
                }
                wg_commit();
                bar_arrive(8 - wg, 256);
                if (gi < 5) {
#pragma unroll
                    for (int i = 0; i < 12; i++)
                        if (p2_id(gi * 3 + 3 + (i >> 2)) >= 8)
                            af[(gi + 1) & 1][i] = ld_frag(a2r + (p2_id(gi * 3 + 3 + (i >> 2)) * 4 + (i & 3)) * 256);
                    wg_wait<0>();
                    if (gi < 3 && lane < 3)
                        mbar_arrive(sb + BAR_EMPTY + 8 * ring_slot(lane == 0 ? p2_useB(gi * 3) : lane == 1 ? p2_useB(gi * 3 + 1) : p2_useB(gi * 3 + 2)));
                }
            }
            const int row0 = m2 * 128 + wg * 64 + w * 16 + g;
            const int col0 = j2 * 128 + rank * 64 + 2 * t;
            uint32_t xr[16];
#pragma unroll
            for (int nb = 0; nb < 8; nb++) {
                xr[2 * nb] = __ldg((const uint32_t*)(xg + (size_t)row0 * 512 + col0 + nb * 8));
                xr[2 * nb + 1] = __ldg((const uint32_t*)(xg + (size_t)(row0 + 8) * 512 + col0 + nb * 8));
            }
            uint32_t rdst, rbar;
            asm volatile("mapa.shared::cluster.u32 %0, %1, %2;"
                         : "=r"(rdst) : "r"(sb + (XCH0 + wg) * STAGE_BYTES + (tid & 127) * 16), "r"(rank ^ 1));
            asm volatile("mapa.shared::cluster.u32 %0, %1, %2;" : "=r"(rbar) : "r"(sb + BAR_XCHG), "r"(rank ^ 1));
            mbar_wait(sb + BAR_XRDY, 0);
            wg_wait<0>();
            acc_fence(ap);
            TS(wg, 18);
#pragma unroll
            for (int i = 0; i < 8; i++)
                asm volatile("st.async.shared::cluster.mbarrier::complete_tx::bytes.v4.f32 [%0], {%1,%2,%3,%4}, [%5];"
                             ::"r"(rdst + i * 2048), "f"(ap[4 * i]), "f"(ap[4 * i + 1]), "f"(ap[4 * i + 2]), "f"(ap[4 * i + 3]),
                             "r"(rbar) : "memory");
            bar_sync(7 + wg, 256);
            wg_fence();
#pragma unroll
            for (int i = 0; i < 12; i++)
                wgmma_n64_rs<DHI128>(ao, reinterpret_cast<const uint32_t*>(&af[1][i]),
                                     dso + ring_slot(65 + (i >> 2)) * (STAGE_BYTES >> 4) + (i & 3) * 128, 1);
            wg_commit();
            if (wg == 0) bar_arrive(8, 256);
            wg_wait<0>();
            acc_fence(ao);
            mbar_wait(sb + BAR_XCHG, 0);
            TS(wg, 19);
            const float4* rx = (const float4*)(smem + (XCH0 + wg) * STAGE_BYTES) + (tid & 127);
#pragma unroll
            for (int nb = 0; nb < 8; nb++) {
                const float4 p = rx[nb * 128];
                const uint32_t o0 = pack_bf16(ao[4 * nb] + p.x + bf_lo(xr[2 * nb]), ao[4 * nb + 1] + p.y + bf_hi(xr[2 * nb]));
                const uint32_t o1 = pack_bf16(ao[4 * nb + 2] + p.z + bf_lo(xr[2 * nb + 1]), ao[4 * nb + 3] + p.w + bf_hi(xr[2 * nb + 1]));
                *(uint32_t*)(outg + (size_t)row0 * 512 + col0 + nb * 8) = o0;
                *(uint32_t*)(outg + (size_t)(row0 + 8) * 512 + col0 + nb * 8) = o1;
            }
        }
        TS(wg, 20);
    }
}

typedef CUresult (*EncodeFn)(CUtensorMap*, CUtensorMapDataType, cuuint32_t, void*, const cuuint64_t*, const cuuint64_t*,
                             const cuuint32_t*, const cuuint32_t*, CUtensorMapInterleave, CUtensorMapSwizzle,
                             CUtensorMapL2promotion, CUtensorMapFloatOOBfill);

void make_map(EncodeFn enc, CUtensorMap* tm, const void* ptr, int rows, int cols, int box_rows, int box_cols,
              CUtensorMapSwizzle swz) {
    cuuint64_t dims[2] = {(cuuint64_t)cols, (cuuint64_t)rows};
    cuuint64_t strides[1] = {(cuuint64_t)cols * 2};
    cuuint32_t box[2] = {(cuuint32_t)box_cols, (cuuint32_t)box_rows};
    cuuint32_t es[2] = {1, 1};
    enc(tm, CU_TENSOR_MAP_DATA_TYPE_BFLOAT16, 2, const_cast<void*>(ptr), dims, strides, box, es,
        CU_TENSOR_MAP_INTERLEAVE_NONE, swz, CU_TENSOR_MAP_L2_PROMOTION_L2_256B, CU_TENSOR_MAP_FLOAT_OOB_FILL_NONE);
}

}

extern "C" void kernel_launch(void* const* d_in, const int* in_sizes, int n_in, void* d_out, int out_size) {
    (void)in_sizes; (void)n_in; (void)out_size;
    static EncodeFn enc = nullptr;
    if (!enc) {
        void* fn = nullptr;
        cudaDriverEntryPointQueryResult qr;
        cudaGetDriverEntryPoint("cuTensorMapEncodeTiled", &fn, cudaEnableDefault, &qr);
        enc = (EncodeFn)fn;
        cudaFuncSetAttribute(fused_kernel, cudaFuncAttributeMaxDynamicSharedMemorySize, SMEM_BYTES);
    }
    const void* x = d_in[0];
    const void* wqkv = d_in[1];
    const void* wo = d_in[2];
    const void* w1 = d_in[4];
    const void* w3 = d_in[5];
    const void* w2 = d_in[6];
    CUtensorMap tx, tqkv, t1, t3, t1h, t3h, t2, t2h, two;
    make_map(enc, &tx, x, 2048, 512, 128, 64, CU_TENSOR_MAP_SWIZZLE_128B);
    make_map(enc, &tqkv, wqkv, 512, 1536, 64, 64, CU_TENSOR_MAP_SWIZZLE_128B);
    make_map(enc, &t1, w1, 512, 1792, 64, 64, CU_TENSOR_MAP_SWIZZLE_128B);
    make_map(enc, &t3, w3, 512, 1792, 64, 64, CU_TENSOR_MAP_SWIZZLE_128B);
    make_map(enc, &t1h, w1, 512, 1792, 64, 32, CU_TENSOR_MAP_SWIZZLE_64B);
    make_map(enc, &t3h, w3, 512, 1792, 64, 32, CU_TENSOR_MAP_SWIZZLE_64B);
    make_map(enc, &t2, w2, 1792, 512, 64, 64, CU_TENSOR_MAP_SWIZZLE_128B);
    make_map(enc, &t2h, w2, 1792, 512, 32, 64, CU_TENSOR_MAP_SWIZZLE_128B);
    make_map(enc, &two, wo, 512, 512, 64, 64, CU_TENSOR_MAP_SWIZZLE_128B);
    fused_kernel<<<128, 384, SMEM_BYTES>>>(tx, tqkv, t1, t3, t1h, t3h, t2, t2h, two, (const __nv_bfloat16*)x,
                                           (__nv_bfloat16*)d_out, (const char*)wqkv, (const char*)w1, (const char*)w3,
                                           (const char*)w2, (const char*)wo);
}
```

```cpp
#include <cuda_runtime.h>
#include <cuda_bf16.h>
#include <cuda.h>
#include <stdint.h>

namespace {

constexpr int NST = 13;
constexpr int STAGE_BYTES = 16384;
constexpr int XST0 = 5;
constexpr int SCR0 = 8;
#define P2_ORDER {0, 1, 2, 3, 4, 8, 5, 6, 9, 7, 10, 12, 11, 13, 14, 15, 16, 17}
#define P2_SMASK 0x16DFu
__host__ __device__ constexpr int p2_id(int i) {
    constexpr int t[18] = P2_ORDER;
    return t[i];
}
__host__ __device__ constexpr bool p2_s(int i) { return (P2_SMASK >> i) & 1; }
__host__ __device__ constexpr int popc18(unsigned v) {
    v = v - ((v >> 1) & 0x55555555u);
    v = (v & 0x33333333u) + ((v >> 2) & 0x33333333u);
    return (int)((((v + (v >> 4)) & 0x0F0F0F0Fu) * 0x01010101u) >> 24);
}
__host__ __device__ constexpr int p2_useB(int i) { return 42 + i + popc18(P2_SMASK & ((2u << i) - 1)); }
constexpr int XCH_USE = p2_useB(17) + 1;
__host__ __device__ constexpr bool p2_recycled(int u) { return u + NST <= XCH_USE + 1; }
constexpr int OFF_MISC = NST * STAGE_BYTES;
constexpr int OFF_KVB = OFF_MISC;
constexpr int OFF_ONES = OFF_MISC + 3072;
constexpr int OFF_BARS = OFF_MISC + 3328;
constexpr int BAR_FULL = OFF_BARS;
constexpr int BAR_EMPTY = BAR_FULL + 8 * NST;
constexpr int BAR_XFULL = BAR_EMPTY + 8 * NST;
constexpr int BAR_KVREADY = BAR_XFULL + 64;
constexpr int BAR_XCHG = BAR_KVREADY + 8;
constexpr int BAR_EPOCH = BAR_XCHG + 8;
constexpr int BAR_XRDY = BAR_EPOCH + 8;
constexpr int OFF_EPOCH = BAR_XRDY + 8;
constexpr int OFF_ZERO = OFF_MISC + 4096;
constexpr int SMEM_BYTES = OFF_MISC + 8192;

constexpr unsigned SPIN_LIMIT = 1u << 24;

constexpr int A2_N = 16 * 2 * 18 * 4 * 256;
__device__ uint4 g_A2[2 * A2_N];
__device__ float4 g_kvacc[2 * 8 * 272];
__device__ unsigned g_kvcnt[8];
__constant__ unsigned char P2_ID[18] = P2_ORDER;
__device__ unsigned g_epoch;
__device__ unsigned g_ticket;

#define TS(role, i)
#define TSW(role, i)

__device__ __forceinline__ uint32_t smem_u32(const void* p) { return (uint32_t)__cvta_generic_to_shared(p); }
__device__ __forceinline__ void mbar_init(uint32_t bar, uint32_t cnt) {
    asm volatile("mbarrier.init.shared::cta.b64 [%0], %1;" ::"r"(bar), "r"(cnt) : "memory");
}
__device__ __forceinline__ void mbar_expect_tx(uint32_t bar, uint32_t bytes) {
    asm volatile("mbarrier.arrive.expect_tx.shared::cta.b64 _, [%0], %1;" ::"r"(bar), "r"(bytes) : "memory");
}
__device__ __forceinline__ void mbar_arrive(uint32_t bar) {
    asm volatile("mbarrier.arrive.shared::cta.b64 _, [%0];" ::"r"(bar) : "memory");
}
__device__ __forceinline__ void mbar_arrive_cta(uint32_t bar, uint32_t cta) {
    asm volatile(
        "{\n.reg .b32 ra;\nmapa.shared::cluster.u32 ra, %0, %1;\n"
        "mbarrier.arrive.shared::cluster.b64 _, [ra];\n}" ::"r"(bar), "r"(cta) : "memory");
}
__device__ __forceinline__ void mbar_wait(uint32_t bar, uint32_t parity) {
    asm volatile(
        "{\n.reg .pred p, q;\n.reg .u32 n;\nmov.u32 n, 0;\n"
        "WAIT_%=:\n"
        "mbarrier.try_wait.parity.shared::cta.b64 p, [%0], %1;\n"
        "@p bra.uni DONE_%=;\n"
        "add.u32 n, n, 1;\n"
        "setp.gt.u32 q, n, %2;\n"
        "@q trap;\n"
        "bra.uni WAIT_%=;\n"
        "DONE_%=:\n}"
        ::"r"(bar), "r"(parity), "n"(SPIN_LIMIT) : "memory");
}
__device__ __forceinline__ unsigned ld_acquire(const unsigned* p) {
    unsigned v;
    asm volatile("ld.acquire.gpu.global.u32 %0, [%1];" : "=r"(v) : "l"(p) : "memory");
    return v;
}
__device__ __forceinline__ void st_release(unsigned* p, unsigned v) {
    asm volatile("st.release.gpu.global.u32 [%0], %1;" ::"l"(p), "r"(v) : "memory");
}
__device__ __forceinline__ unsigned read_epoch() {
    return __shfl_sync(0xffffffffu, *(volatile unsigned*)&g_epoch, 0) + 1;
}
__device__ __forceinline__ void tma_load(uint32_t dst, const CUtensorMap* tm, uint32_t bar, int x, int y) {
    asm volatile(
        "cp.async.bulk.tensor.2d.shared::cluster.global.mbarrier::complete_tx::bytes [%0], [%1, {%3, %4}], [%2];"
        ::"r"(dst), "l"(tm), "r"(bar), "r"(x), "r"(y) : "memory");
}
__device__ __forceinline__ void tma_load_mc(uint32_t dst, const CUtensorMap* tm, uint32_t bar, int x, int y) {
    asm volatile(
        "cp.async.bulk.tensor.2d.shared::cluster.global.mbarrier::complete_tx::bytes.multicast::cluster "
        "[%0], [%1, {%3, %4}], [%2], %5;"
        ::"r"(dst), "l"(tm), "r"(bar), "r"(x), "r"(y), "h"((uint16_t)3) : "memory");
}
__device__ __forceinline__ void prefetch_tm(const CUtensorMap* tm) {
    asm volatile("prefetch.tensormap [%0];" ::"l"(tm) : "memory");
}
__device__ __forceinline__ void l2_prefetch(const void* p, uint32_t bytes) {
    asm volatile("cp.async.bulk.prefetch.L2.global [%0], %1;" ::"l"(p), "r"(bytes) : "memory");
}
__device__ __forceinline__ void bar_sync(int id, int n) { asm volatile("bar.sync %0, %1;" ::"r"(id), "r"(n) : "memory"); }
__device__ __forceinline__ void bar_arrive(int id, int n) { asm volatile("bar.arrive %0, %1;" ::"r"(id), "r"(n) : "memory"); }
__device__ __forceinline__ void wg_fence() { asm volatile("wgmma.fence.sync.aligned;" ::: "memory"); }
__device__ __forceinline__ void wg_commit() { asm volatile("wgmma.commit_group.sync.aligned;" ::: "memory"); }
template <int N>
__device__ __forceinline__ void wg_wait() { asm volatile("wgmma.wait_group.sync.aligned %0;" ::"n"(N) : "memory"); }

__device__ __forceinline__ uint64_t make_desc(uint32_t addr, uint32_t lbo, uint32_t sbo, uint64_t swz) {
    return (uint64_t)((addr & 0x3FFFF) >> 4) | ((uint64_t)(lbo >> 4) << 16) | ((uint64_t)(sbo >> 4) << 32) | (swz << 62);
}

#define ACC8(a, o) "+f"(a[o]), "+f"(a[o + 1]), "+f"(a[o + 2]), "+f"(a[o + 3]), "+f"(a[o + 4]), "+f"(a[o + 5]), "+f"(a[o + 6]), "+f"(a[o + 7])
constexpr uint32_t DHI128 = (1024u >> 4) | (1u << 30);
constexpr uint32_t DHI64 = (512u >> 4) | (2u << 30);
__device__ __forceinline__ void wgmma_n128_rs(float (&d)[64], const uint32_t* a, uint32_t db, int scale_d) {
    asm volatile(
        "{\n.reg .pred p;\n.reg .b64 dd;\nsetp.ne.b32 p, %69, 0;\nmov.b64 dd, {%68, %70};\n"
        "wgmma.mma_async.sync.aligned.m64n128k16.f32.bf16.bf16 "
        "{%0,%1,%2,%3,%4,%5,%6,%7,%8,%9,%10,%11,%12,%13,%14,%15,%16,%17,%18,%19,%20,%21,%22,%23,%24,%25,%26,%27,%28,%29,%30,%31,"
        "%32,%33,%34,%35,%36,%37,%38,%39,%40,%41,%42,%43,%44,%45,%46,%47,%48,%49,%50,%51,%52,%53,%54,%55,%56,%57,%58,%59,%60,%61,%62,%63},"
        "{%64,%65,%66,%67}, dd, p, 1, 1, 1;\n}"
        : ACC8(d, 0), ACC8(d, 8), ACC8(d, 16), ACC8(d, 24), ACC8(d, 32), ACC8(d, 40), ACC8(d, 48), ACC8(d, 56)
        : "r"(a[0]), "r"(a[1]), "r"(a[2]), "r"(a[3]), "r"(db), "r"(scale_d), "n"(DHI128));
}
template <uint32_t HI>
__device__ __forceinline__ void wgmma_n64_rs(float (&d)[32], const uint32_t* a, uint32_t db, int scale_d) {
    asm volatile(
        "{\n.reg .pred p;\n.reg .b64 dd;\nsetp.ne.b32 p, %37, 0;\nmov.b64 dd, {%36, %38};\n"
        "wgmma.mma_async.sync.aligned.m64n64k16.f32.bf16.bf16 "
        "{%0,%1,%2,%3,%4,%5,%6,%7,%8,%9,%10,%11,%12,%13,%14,%15,%16,%17,%18,%19,%20,%21,%22,%23,%24,%25,%26,%27,%28,%29,%30,%31},"
        "{%32,%33,%34,%35}, dd, p, 1, 1, 1;\n}"
        : ACC8(d, 0), ACC8(d, 8), ACC8(d, 16), ACC8(d, 24)
        : "r"(a[0]), "r"(a[1]), "r"(a[2]), "r"(a[3]), "r"(db), "r"(scale_d), "n"(HI));
}
__device__ __forceinline__ void wgmma_n64_ss_tt(float (&d)[32], uint64_t da, uint64_t db, int scale_d) {
    asm volatile(
        "{\n.reg .pred p;\nsetp.ne.b32 p, %34, 0;\n"
        "wgmma.mma_async.sync.aligned.m64n64k16.f32.bf16.bf16 "
        "{%0,%1,%2,%3,%4,%5,%6,%7,%8,%9,%10,%11,%12,%13,%14,%15,%16,%17,%18,%19,%20,%21,%22,%23,%24,%25,%26,%27,%28,%29,%30,%31},"
        "%32, %33, p, 1, 1, 1, 1;\n}"
        : ACC8(d, 0), ACC8(d, 8), ACC8(d, 16), ACC8(d, 24)
        : "l"(da), "l"(db), "r"(scale_d));
}
__device__ __forceinline__ void wgmma_n8_ss_tn(float (&d)[4], uint64_t da, uint64_t db, int scale_d) {
    asm volatile(
        "{\n.reg .pred p;\nsetp.ne.b32 p, %6, 0;\n"
        "wgmma.mma_async.sync.aligned.m64n8k16.f32.bf16.bf16 {%0,%1,%2,%3}, %4, %5, p, 1, 1, 1, 0;\n}"
        : "+f"(d[0]), "+f"(d[1]), "+f"(d[2]), "+f"(d[3])
        : "l"(da), "l"(db), "r"(scale_d));
}
__device__ __forceinline__ void wgmma_n24_rs(float (&d)[12], const uint32_t* a, uint64_t db) {
    asm volatile(
        "wgmma.mma_async.sync.aligned.m64n24k16.f32.bf16.bf16 {%0,%1,%2,%3,%4,%5,%6,%7,%8,%9,%10,%11}, "
        "{%12,%13,%14,%15}, %16, 0, 1, 1, 0;"
        : ACC8(d, 0), "+f"(d[8]), "+f"(d[9]), "+f"(d[10]), "+f"(d[11])
        : "r"(a[0]), "r"(a[1]), "r"(a[2]), "r"(a[3]), "l"(db));
}
template <int N>
__device__ __forceinline__ void acc_fence(float (&d)[N]) {
#pragma unroll
    for (int i = 0; i < N; i++) asm volatile("" : "+f"(d[i])::"memory");
}
__device__ __forceinline__ void mma16816(float (&c)[4], const uint32_t* a, uint32_t b0, uint32_t b1) {
    asm volatile(
        "mma.sync.aligned.m16n8k16.row.col.f32.bf16.bf16.f32 {%0,%1,%2,%3}, {%4,%5,%6,%7}, {%8,%9}, {%0,%1,%2,%3};"
        : "+f"(c[0]), "+f"(c[1]), "+f"(c[2]), "+f"(c[3])
        : "r"(a[0]), "r"(a[1]), "r"(a[2]), "r"(a[3]), "r"(b0), "r"(b1));
}
__device__ __forceinline__ uint32_t pack_bf16(float lo, float hi) {
    uint32_t r;
    asm("cvt.rn.bf16x2.f32 %0, %1, %2;" : "=r"(r) : "f"(hi), "f"(lo));
    return r;
}
__device__ __forceinline__ float bf_lo(uint32_t v) { return __uint_as_float(v << 16); }
__device__ __forceinline__ float bf_hi(uint32_t v) { return __uint_as_float(v & 0xffff0000u); }
__device__ __forceinline__ float bf16_round(float v) { return __bfloat162float(__float2bfloat16_rn(v)); }
__device__ __forceinline__ float sqrt_fast(float v) {
    float r;
    asm("sqrt.approx.ftz.f32 %0, %1;" : "=f"(r) : "f"(v));
    return r;
}
__device__ __forceinline__ float rcp_fast(float v) {
    float r;
    asm("rcp.approx.ftz.f32 %0, %1;" : "=f"(r) : "f"(v));
    return r;
}
__device__ __forceinline__ float ex2_fast(float v) {
    float r;
    asm("ex2.approx.ftz.f32 %0, %1;" : "=f"(r) : "f"(v));
    return r;
}
__device__ __forceinline__ int fresh_tid() {
    int v;
    asm volatile("mov.u32 %0, %%tid.x;" : "=r"(v));
    return v;
}
__device__ __forceinline__ int fresh_bid() {
    int v;
    asm volatile("mov.u32 %0, %%ctaid.x;" : "=r"(v));
    return v;
}
struct RowScale { float rho, rl, var; };
__device__ __forceinline__ RowScale row_scale(float sd) {
    asm volatile("" : "+f"(sd));
    RowScale r;
    r.rho = rcp_fast(sd);
    r.rl = r.rho * 1.4426950408889634f;
    r.var = sd * sd;
    return r;
}
__device__ __forceinline__ uint4* a2_write_ptr(const uint8_t* smem) {
    const int bid = fresh_bid();
    const unsigned par = *(volatile const unsigned*)(smem + OFF_EPOCH) & 1;
    return g_A2 + (size_t)par * A2_N + (size_t)(((bid >> 3) * 2 + ((bid >> 2) & 1)) * 18) * 4 * 256 + fresh_tid();
}
__device__ __forceinline__ float phi_f(float a, const RowScale& r) {
    return fmaf(fmaxf(a, 0.f), r.rho, ex2_fast(fminf(a, 0.f) * r.rl) + 1e-6f);
}
__device__ __forceinline__ float swiglu_f(float ga, float ua, const RowScale& r) {
    return (ga * ua) * rcp_fast(fmaf(ex2_fast(-ga * r.rl), r.var, r.var));
}
__device__ __forceinline__ uint4 swiglu8(const float* gp, const float* up, const RowScale& r0, const RowScale& r1) {
    uint4 v;
    v.x = pack_bf16(swiglu_f(gp[0], up[0], r0), swiglu_f(gp[1], up[1], r0));
    v.y = pack_bf16(swiglu_f(gp[2], up[2], r1), swiglu_f(gp[3], up[3], r1));
    v.z = pack_bf16(swiglu_f(gp[4], up[4], r0), swiglu_f(gp[5], up[5], r0));
    v.w = pack_bf16(swiglu_f(gp[6], up[6], r1), swiglu_f(gp[7], up[7], r1));
    v.y = v.y ? v.y : 0x8000u;
    v.w = v.w ? v.w : 0x8000u;
    return v;
}
__device__ __forceinline__ bool frag_stale(const uint4 (&f)[12]) {
    unsigned v = min(f[0].y, f[0].w);
#pragma unroll
    for (int i = 1; i < 12; i++) v = min(v, min(f[i].y, f[i].w));
    return __any_sync(0xffffffffu, v == 0u);
}
__device__ __forceinline__ void st_frag(uint4* p, uint4 v) {
    asm volatile("st.relaxed.gpu.global.v4.u32 [%0], {%1,%2,%3,%4};" ::"l"(p), "r"(v.x), "r"(v.y), "r"(v.z), "r"(v.w) : "memory");
}
__device__ __forceinline__ uint4 ld_frag(const uint4* p) {
    uint4 v;
    asm volatile("ld.relaxed.gpu.global.v4.u32 {%0,%1,%2,%3}, [%4];" : "=r"(v.x), "=r"(v.y), "=r"(v.z), "=r"(v.w) : "l"(p) : "memory");
    return v;
}
__device__ __forceinline__ void red_add2(float* p, float a, float b) {
    asm volatile("red.global.add.v2.f32 [%0], {%1, %2};" ::"l"(p), "f"(a), "f"(b) : "memory");
}
__device__ __forceinline__ void cp_async16(uint32_t dst, const void* src) {
    asm volatile("cp.async.cg.shared.global [%0], [%1], 16;" ::"r"(dst), "l"(src) : "memory");
}

__host__ __device__ constexpr int ring_lap(int u) { return (u * 79) >> 10; }
__host__ __device__ constexpr int ring_slot(int u) { return u - NST * ring_lap(u); }

__device__ __forceinline__ void mainloop128(float (&acc)[64], const uint32_t (&xa)[128], int u0, uint32_t sb,
                                            uint32_t desc128, int lane, int wg, bool last = false) {
    bar_sync(7 + wg, 256);
#pragma unroll
    for (int kb = 0; kb < 8; kb++) {
        const int st = ring_slot(u0 + kb);
        mbar_wait(sb + BAR_FULL + 8 * st, ring_lap(u0 + kb) & 1);
        wg_fence();
        const uint32_t d = desc128 + st * (STAGE_BYTES >> 4);
#pragma unroll
        for (int ks = 0; ks < 4; ks++) wgmma_n128_rs(acc, &xa[(kb * 4 + ks) * 4], d + ks * 128, (kb | ks) != 0);
        wg_commit();
        if (kb == 7 && !(last && wg == 1)) bar_arrive(8 - wg, 256);
        if (kb > 0) {
            wg_wait<1>();
            if (lane == 0) mbar_arrive(sb + BAR_EMPTY + 8 * ring_slot(u0 + kb - 1));
        }
    }
    wg_wait<0>();
    acc_fence(acc);
    if (lane == 0) mbar_arrive(sb + BAR_EMPTY + 8 * ring_slot(u0 + 7));
}
__device__ __forceinline__ void mainloop64x2(float (&a0)[32], float (&a1)[32], const uint32_t (&xa)[128], int u0,
                                             uint32_t sb, uint32_t desc128, int lane, int wg) {
    bar_sync(7 + wg, 256);
#pragma unroll
    for (int kb = 0; kb < 8; kb++) {
        const int st = ring_slot(u0 + kb);
        mbar_wait(sb + BAR_FULL + 8 * st, ring_lap(u0 + kb) & 1);
        wg_fence();
        const uint32_t d = desc128 + st * (STAGE_BYTES >> 4);
        const uint32_t d2 = d + (8192 >> 4) - ((4096u >> 4) << 16);
#pragma unroll
        for (int ks = 0; ks < 4; ks++) {
            wgmma_n64_rs<DHI128>(a0, &xa[(kb * 4 + ks) * 4], d + ks * 128, (kb | ks) != 0);
            wgmma_n64_rs<DHI64>(a1, &xa[(kb * 4 + ks) * 4], d2 + ks * 64, (kb | ks) != 0);
        }
        wg_commit();
        if (kb == 7) bar_arrive(8 - wg, 256);
        if (kb > 0) {
            wg_wait<1>();
            if (lane == 0) mbar_arrive(sb + BAR_EMPTY + 8 * ring_slot(u0 + kb - 1));
        }
    }
    wg_wait<0>();
    acc_fence(a0);
    acc_fence(a1);
    if (lane == 0) mbar_arrive(sb + BAR_EMPTY + 8 * ring_slot(u0 + 7));
}

__global__ void __cluster_dims__(2, 1, 1) __launch_bounds__(384, 1)
fused_kernel(const __grid_constant__ CUtensorMap tm_x, const __grid_constant__ CUtensorMap tm_qkv,
             const __grid_constant__ CUtensorMap tm_w1, const __grid_constant__ CUtensorMap tm_w3,
             const __grid_constant__ CUtensorMap tm_w1h, const __grid_constant__ CUtensorMap tm_w3h,
             const __grid_constant__ CUtensorMap tm_w2, const __grid_constant__ CUtensorMap tm_w2h,
             const __grid_constant__ CUtensorMap tm_wo, const __nv_bfloat16* __restrict__ xg,
             __nv_bfloat16* __restrict__ outg, const char* __restrict__ p_qkv, const char* __restrict__ p_w1,
             const char* __restrict__ p_w3, const char* __restrict__ p_w2, const char* __restrict__ p_wo) {
    extern __shared__ __align__(1024) uint8_t smem[];
    const uint32_t sb = smem_u32(smem);
    const int tid = threadIdx.x;
    const int warp = tid >> 5, lane = tid & 31;
    const int rank = blockIdx.x & 1;
    const int pair = blockIdx.x >> 1;
    const int m = pair >> 2;
    const int j2 = pair & 3;
    const int c = 2 * j2 + rank;
    const int m2 = m;

    TS(tid >> 7, 0);
    if (tid == 256) {
        prefetch_tm(&tm_x);
#pragma unroll
        for (int i = 0; i < 8; i++) mbar_init(sb + BAR_XFULL + 8 * i, 1);
#pragma unroll
        for (int kb = 0; kb < 8; kb++) mbar_expect_tx(sb + BAR_XFULL + 8 * kb, 16384);
        asm volatile("fence.mbarrier_init.release.cluster;" ::: "memory");
        TS(2, 21);
    } else if (tid == 0) {
#pragma unroll
        for (int i = 0; i < NST; i++) mbar_init(sb + BAR_FULL + 8 * i, 1);
        asm volatile("fence.mbarrier_init.release.cluster;" ::: "memory");
    } else if (tid == 32) {
#pragma unroll
        for (int i = 0; i < NST; i++) mbar_init(sb + BAR_EMPTY + 8 * i, 8);
        asm volatile("fence.mbarrier_init.release.cluster;" ::: "memory");
    } else if (tid == 64) {
#pragma unroll
        for (int i = 0; i < 4; i++) mbar_init(sb + BAR_KVREADY + 8 * i, 1);
        mbar_expect_tx(sb + BAR_XCHG, 32768);
        asm volatile("fence.mbarrier_init.release.cluster;" ::: "memory");
    } else if (tid >= 128 && tid < 256) {
        ((uint4*)(smem + OFF_ZERO))[tid - 128] = make_uint4(0, 0, 0, 0);
        ((uint4*)(smem + OFF_ZERO))[tid] = make_uint4(0, 0, 0, 0);
        asm volatile("fence.proxy.async.shared::cta;" ::: "memory");
    } else if (tid == 288) {
        prefetch_tm(&tm_qkv);
        prefetch_tm(&tm_w1);
        prefetch_tm(&tm_w3);
        prefetch_tm(&tm_w1h);
        prefetch_tm(&tm_w3h);
        prefetch_tm(&tm_w2);
        prefetch_tm(&tm_w2h);
        prefetch_tm(&tm_wo);
    } else if (tid >= 320) {
        ((uint32_t*)(smem + OFF_ONES))[tid - 320] = 0x3F803F80u;
        asm volatile("fence.proxy.async.shared::cta;" ::: "memory");
    }
    __syncthreads();
    TS(tid >> 7, 22);
    asm volatile("barrier.cluster.arrive.relaxed.aligned;\nbarrier.cluster.wait.acquire.aligned;" ::: "memory");

    if (warp >= 8) {
        asm volatile("setmaxnreg.dec.sync.aligned.u32 40;");
        if (warp == 8) {
            if (lane == 0) {
                int st = 0;
                uint32_t lap = 0;
                unsigned par = 0;
                char* zdst = nullptr;
#pragma unroll
                for (int i = 0; i < 4; i++) {
                    const int kb = 2 * i + rank;
                    tma_load_mc(sb + (XST0 + kb) * STAGE_BYTES, &tm_x, sb + BAR_XFULL + 8 * kb, kb * 64, m * 128);
                }
                for (int it = 0; it < 40; it++) {
                    const int tile = it >> 3, kb = it & 7;
                    const uint32_t full = sb + BAR_FULL + 8 * st;
                    mbar_wait(sb + BAR_EMPTY + 8 * st, (st >= XST0) ? (lap & 1) : ((lap & 1) ^ 1));
                    mbar_expect_tx(full, STAGE_BYTES);
                    const uint32_t dst = sb + st * STAGE_BYTES;
                    if (tile == 0) {
                        tma_load(dst, &tm_qkv, full, 512 + 64 * c, kb * 64);
                        tma_load(dst + 8192, &tm_qkv, full, 1024 + 64 * c, kb * 64);
                    } else if (tile != 3) {
                        const int col = 224 * c + 64 * (tile == 4 ? 2 : tile - 1);
                        tma_load(dst, &tm_w1, full, col, kb * 64);
                        tma_load(dst + 8192, &tm_w3, full, col, kb * 64);
                    } else {
                        tma_load(dst, &tm_qkv, full, 64 * c, kb * 64);
                        tma_load(dst + 8192, &tm_w1h, full, 224 * c + 192, kb * 64);
                        tma_load(dst + 12288, &tm_w3h, full, 224 * c + 192, kb * 64);
                    }
                    if (++st == NST) { st = 0; lap++; }
                    if (it == 7) {
                        mbar_wait(sb + BAR_EPOCH, 0);
                        par = *(volatile unsigned*)(smem + OFF_EPOCH) & 1;
                        zdst = (char*)(g_A2 + (size_t)(par ^ 1) * A2_N + (size_t)((m * 2 + (c >> 2)) * 18) * 4 * 256);
                        mbar_wait(sb + BAR_EMPTY + 8 * SCR0, 0);
                        mbar_arrive(sb + BAR_FULL + 8 * SCR0);
                        mbar_wait(sb + BAR_EMPTY + 8 * (SCR0 + 1), 0);
                        mbar_arrive(sb + BAR_FULL + 8 * (SCR0 + 1));
                        st += 2;
                    }
                }
                TS(2, 1);
                const char* a2b = (const char*)(g_A2 + (size_t)par * A2_N + (size_t)((m2 * 2 + rank) * 18) * 4 * 256);
#pragma unroll 1
                for (int i = 0; i < 18; i++) {
                    const int b = P2_ID[i];
                    if ((P2_SMASK >> i) & 1) {
                        mbar_wait(sb + BAR_EMPTY + 8 * st, (st >= XST0) ? (lap & 1) : ((lap & 1) ^ 1));
                        mbar_expect_tx(sb + BAR_FULL + 8 * st, STAGE_BYTES);
                        asm volatile("cp.async.bulk.shared::cluster.global.mbarrier::complete_tx::bytes [%0], [%1], 16384, [%2];"
                                     ::"r"(sb + st * STAGE_BYTES), "l"(a2b + b * 16384), "r"(sb + BAR_FULL + 8 * st) : "memory");
                        if (++st == NST) { st = 0; lap++; }
                    }
                    const uint32_t full = sb + BAR_FULL + 8 * st;
                    const uint32_t dst = sb + st * STAGE_BYTES;
                    mbar_wait(sb + BAR_EMPTY + 8 * st, (st >= XST0) ? (lap & 1) : ((lap & 1) ^ 1));
                    mbar_expect_tx(full, STAGE_BYTES);
                    const int cp = 128 * j2 + 64 * (rank ^ 1), co = 128 * j2 + 64 * rank;
                    if (b < 8 || b >= 14) {
                        const int row = (b < 8) ? 224 * (4 * rank + (b & 3)) + 64 * (b >> 2) : 224 * (4 * rank + b - 14) + 128;
                        tma_load(dst, &tm_w2, full, cp, row);
                        tma_load(dst + 8192, &tm_w2, full, co, row);
                    } else if (b < 10) {
                        const int row = 224 * (4 * rank + 2 * (b - 8)) + 192;
                        tma_load(dst, &tm_w2h, full, cp, row);
                        tma_load(dst + 4096, &tm_w2h, full, cp, row + 224);
                        tma_load(dst + 8192, &tm_w2h, full, co, row);
                        tma_load(dst + 12288, &tm_w2h, full, co, row + 224);
                    } else {
                        const int row = 64 * (4 * rank + (b - 10));
                        tma_load(dst, &tm_wo, full, cp, row);
                        tma_load(dst + 8192, &tm_wo, full, co, row);
                    }
                    TS(2, 2 + i);
                    if (++st == NST) { st = 0; lap++; }
                }
#pragma unroll
                for (int k = 0; k < 2; k++)
                    mbar_wait(sb + BAR_EMPTY + 8 * ring_slot(XCH_USE + k),
                              (ring_lap(XCH_USE + k) & 1) ^ (ring_slot(XCH_USE + k) >= XST0 ? 0 : 1));
                mbar_arrive_cta(sb + BAR_XRDY, rank ^ 1);
#pragma unroll 1
                for (int i = 0; i < 18; i++) {
                    const int cc = c & 3;
                    const int blk = (i < 8) ? ((i >> 2) * 4 + cc) * 4 + (i & 3)
                                  : (i < 10) ? (8 + (cc >> 1)) * 4 + 2 * (cc & 1) + (i - 8)
                                  : (i < 14) ? (10 + cc) * 4 + (i - 10) : (14 + cc) * 4 + (i - 14);
                    asm volatile("cp.async.bulk.global.shared::cta.bulk_group [%0], [%1], 4096;"
                                 ::"l"(zdst + (size_t)blk * 4096), "r"(sb + OFF_ZERO) : "memory");
                }
                asm volatile("cp.async.bulk.commit_group;" ::: "memory");
                asm volatile("cp.async.bulk.wait_group 0;" ::: "memory");
                TS(2, 20);
            }
        } else if (warp < 11) {
            const int wg = warp - 9;
            bar_sync(3 + wg, 160);
            if (lane == 0) asm volatile("red.release.gpu.global.add.u32 [%0], 1;" ::"l"(&g_kvcnt[c]) : "memory");
            TSW(3, wg);
        } else {
            const unsigned epoch = read_epoch();
            if (lane == 0) {
                const unsigned tk = atomicInc(&g_ticket, 127u);
                if (tk == 127u) *(volatile unsigned*)&g_epoch = epoch;
            }
            if (lane == 0) *(volatile unsigned*)(smem + OFF_EPOCH) = epoch;
            __syncwarp();
            if (lane == 0) mbar_arrive(sb + BAR_EPOCH);
            if (lane < 17) g_kvacc[(((epoch & 1) ^ 1) * 8 + c) * 272 + 17 * m + lane] = make_float4(0.f, 0.f, 0.f, 0.f);
            {
                unsigned n = 0;
                while ((int)(ld_acquire(&g_kvcnt[c]) - 32u * epoch) < 0) {
                    __nanosleep(200);
                    if (++n > SPIN_LIMIT) asm volatile("trap;");
                }
            }
            TSW(4, 0);
            const int g = lane >> 2, t = lane & 3;
            const float* ks = (const float*)(g_kvacc + ((epoch & 1) * 8 + c) * 272) + 32 * t + g;
            uint32_t* kb = (uint32_t*)(smem + OFF_KVB) + g * 4 + t;
#pragma unroll 2
            for (int hh = 0; hh < 4; hh++) {
                const float* k = ks + hh * 272;
                const float a0 = __ldcg(k), a1 = __ldcg(k + 16), a2 = __ldcg(k + 128), a3 = __ldcg(k + 144);
                const float b0 = __ldcg(k + 8), b1 = __ldcg(k + 24), b2 = __ldcg(k + 136), b3 = __ldcg(k + 152);
                const float2 z0 = __ldcg((const float2*)(k - g - 30 * t + 256)), z1 = __ldcg((const float2*)(k - g - 30 * t + 264));
                uint32_t* o = kb + hh * 192;
                o[0] = pack_bf16(a0, a1);
                o[32] = pack_bf16(a2, a3);
                o[64] = pack_bf16(b0, b1);
                o[96] = pack_bf16(b2, b3);
                o[128] = pack_bf16(z0.x, z0.y);
                o[160] = pack_bf16(z1.x, z1.y);
            }
            asm volatile("fence.proxy.async.shared::cta;" ::: "memory");
            __syncwarp();
            if (lane == 0) mbar_arrive(sb + BAR_KVREADY);
            TSW(4, 4);
        }
    } else {
        asm volatile("setmaxnreg.inc.sync.aligned.u32 232;");
        const int wg = warp >> 2, w = warp & 3;
        const int g = lane >> 2, t = lane & 3;
        float acc[64];
        uint32_t xa[128];
        float sd0, sd1;

        TS(wg, 1);
        {
            const int row = wg * 64 + w * 16 + (lane & 7) + ((lane >> 3) & 1) * 8;
            const uint32_t rbase = sb + XST0 * STAGE_BYTES + row * 128;
            const int hi = lane >> 4, r7 = lane & 7;
            float sm[2][4], c0[2][4], c1[2][4];
#pragma unroll
            for (int i = 0; i < 8; i++) { sm[i >> 2][i & 3] = 0.f; c0[i >> 2][i & 3] = 0.f; c1[i >> 2][i & 3] = 0.f; }
            if (wg == 1) bar_arrive(7, 256);
#pragma unroll
            for (int kb = 0; kb < 8; kb++) {
                mbar_wait(sb + BAR_XFULL + 8 * kb, 0);
#pragma unroll
                for (int ks = 0; ks < 4; ks++) {
                    uint32_t* a = &xa[(kb * 4 + ks) * 4];
                    const uint32_t addr = rbase + kb * STAGE_BYTES + (((2 * ks + hi) ^ r7) << 4);
                    asm volatile("ldmatrix.sync.aligned.m8n8.x4.shared.b16 {%0,%1,%2,%3}, [%4];"
                                 : "=r"(a[0]), "=r"(a[1]), "=r"(a[2]), "=r"(a[3]) : "r"(addr) : "memory");
                    mma16816(sm[ks & 1], a, 0x3F803F80u, 0x3F803F80u);
                    mma16816(c0[ks & 1], a, a[0], a[2]);
                    mma16816(c1[ks & 1], a, a[1], a[3]);
                }
            }
            TS(wg, 2);
            const float mean0 = (sm[0][0] + sm[1][0]) * (1.f / 512.f);
            const float mean1 = (sm[0][2] + sm[1][2]) * (1.f / 512.f);
            __syncwarp();
            if (lane < 8) mbar_arrive(sb + BAR_EMPTY + 8 * (XST0 + lane));
            const __nv_bfloat162 mb0 = __float2bfloat162_rn(mean0), mb1 = __float2bfloat162_rn(mean1);
#pragma unroll
            for (int i = 0; i < 128; i++) {
                __nv_bfloat162 v = *reinterpret_cast<__nv_bfloat162*>(&xa[i]);
                v = __hsub2(v, (i & 1) ? mb1 : mb0);
                xa[i] = *reinterpret_cast<uint32_t*>(&v);
            }
            const float d0 = (g & 1) ? c0[0][1] + c0[1][1] : c0[0][0] + c0[1][0];
            const float d1 = (g & 1) ? c1[0][3] + c1[1][3] : c1[0][2] + c1[1][2];
            const int src = (lane & ~3) | (g >> 1);
            const float var0 = fmaxf(__shfl_sync(0xffffffffu, d0, src) * (1.f / 512.f) - mean0 * mean0, 0.f);
            const float var1 = fmaxf(__shfl_sync(0xffffffffu, d1, src) * (1.f / 512.f) - mean1 * mean1, 0.f);
            sd0 = bf16_round(sqrt_fast(bf16_round(bf16_round(var0) + 1e-5f)));
            sd1 = bf16_round(sqrt_fast(bf16_round(bf16_round(var1) + 1e-5f)));
        }

        TS(wg, 3);
        const uint32_t desc128 = ((sb & 0x3FFFF) >> 4) | ((8192u >> 4) << 16);

        {
            mainloop128(acc, xa, 0, sb, desc128, lane, wg);
            TS(wg, 4);
            {
                TS(wg, 24);
                const RowScale r0 = row_scale(sd0), r1 = row_scale(sd1);
                const float rho0 = r0.rho, rho1 = r1.rho;
                const uint32_t pkb = sb + (SCR0 + wg) * STAGE_BYTES;
                mbar_wait(sb + BAR_FULL + 8 * (SCR0 + wg), 0);
                const uint32_t ra = pkb + (w * 16 + g) * 128 + t * 4;
#pragma unroll
                for (int nb = 0; nb < 8; nb++) {
                    const uint32_t off = (uint32_t)((nb ^ g) << 4);
                    uint32_t p0 = pack_bf16(phi_f(acc[nb * 4], r0), phi_f(acc[nb * 4 + 1], r0));
                    uint32_t p1 = pack_bf16(phi_f(acc[nb * 4 + 2], r1), phi_f(acc[nb * 4 + 3], r1));
                    uint32_t v0 = pack_bf16(acc[32 + nb * 4] * rho0, acc[32 + nb * 4 + 1] * rho0);
                    uint32_t v1 = pack_bf16(acc[32 + nb * 4 + 2] * rho1, acc[32 + nb * 4 + 3] * rho1);
                    asm volatile("st.shared.u32 [%0], %1;" ::"r"(ra + off), "r"(p0) : "memory");
                    asm volatile("st.shared.u32 [%0], %1;" ::"r"(ra + off + 1024), "r"(p1) : "memory");
                    asm volatile("st.shared.u32 [%0], %1;" ::"r"(ra + off + 8192), "r"(v0) : "memory");
                    asm volatile("st.shared.u32 [%0], %1;" ::"r"(ra + off + 8192 + 1024), "r"(v1) : "memory");
                }
                TS(wg, 25);
                asm volatile("fence.proxy.async.shared::cta;" ::: "memory");
                bar_sync(1 + wg, 128);
                TS(wg, 26);
                const uint64_t da = make_desc(pkb, 8192, 1024, 1);
                const uint64_t db = make_desc(pkb + 8192, 8192, 1024, 1);
                const uint64_t d1 = make_desc(sb + OFF_ONES, 128, 128, 0);
                float kva[32], za[4];
                wg_fence();
#pragma unroll
                for (int ks = 0; ks < 4; ks++) {
                    wgmma_n64_ss_tt(kva, da + ks * 128, db + ks * 128, ks != 0);
                    wgmma_n8_ss_tn(za, da + ks * 128, d1, ks != 0);
                }
                wg_commit();
                wg_wait<0>();
                acc_fence(kva);
                acc_fence(za);
                if (lane < 2) mbar_arrive(sb + BAR_EMPTY + 8 * (SCR0 + lane));
                TS(wg, 27);
                float o[8];
#pragma unroll
                for (int i = 0; i < 8; i++)
                    o[i] = (w == 0) ? kva[i] : (w == 1) ? kva[8 + i] : (w == 2) ? kva[16 + i] : kva[24 + i];
                mbar_wait(sb + BAR_EPOCH, 0);
                const unsigned par = *(volatile unsigned*)(smem + OFF_EPOCH) & 1;
                float* dst = (float*)(g_kvacc + (par * 8 + c) * 272) + w * 272 + g * 16 + 2 * t;
                red_add2(dst, o[0], o[1]);
                red_add2(dst + 128, o[2], o[3]);
                red_add2(dst + 8, o[4], o[5]);
                red_add2(dst + 136, o[6], o[7]);
                if (t == 0) {
                    atomicAdd(dst - g * 15 + 256, za[0]);
                    atomicAdd(dst - g * 15 + 264, za[2]);
                }
            }
            bar_arrive(3 + wg, 160);
            TS(wg, 5);
        }
#pragma unroll
        for (int tile = 1; tile < 3; tile++) {
            mainloop128(acc, xa, 2 + 8 * tile, sb, desc128, lane, wg);
            TS(wg, 4 + 2 * tile);
            const RowScale r0 = row_scale(sd0), r1 = row_scale(sd1);
            uint4* dst = a2_write_ptr(smem) + (size_t)((4 * (tile - 1) + (fresh_bid() & 3)) * 4) * 256;
#pragma unroll
            for (int ks = 0; ks < 4; ks++) st_frag(dst + ks * 256, swiglu8(&acc[ks * 8], &acc[32 + ks * 8], r0, r1));
            TS(wg, 5 + 2 * tile);
        }
        {
            float qa[32], gu[32];
            mainloop64x2(qa, gu, xa, 26, sb, desc128, lane, wg);
            TS(wg, 10);
            const RowScale r0 = row_scale(sd0), r1 = row_scale(sd1);
            uint4* const a2w = a2_write_ptr(smem);
            const int cc = fresh_bid() & 3;
            uint4* dst = a2w + (size_t)((8 + (cc >> 1)) * 4 + 2 * (cc & 1)) * 256;
#pragma unroll
            for (int ks = 0; ks < 2; ks++) st_frag(dst + ks * 256, swiglu8(&gu[ks * 8], &gu[16 + ks * 8], r0, r1));
            uint32_t pq[16];
#pragma unroll
            for (int i = 0; i < 16; i++) {
                const RowScale& r = (i & 1) ? r1 : r0;
                pq[i] = pack_bf16(phi_f(qa[2 * i], r), phi_f(qa[2 * i + 1], r));
            }
            TS(wg, 13);
            mbar_wait(sb + BAR_KVREADY, 0);
            TS(wg, 14);
            float nd[4][12];
            const uint64_t dk = make_desc(sb + OFF_KVB, 128, 256, 0);
            wg_fence();
#pragma unroll
            for (int hh = 0; hh < 4; hh++) wgmma_n24_rs(nd[hh], &pq[4 * hh], dk + hh * (768 >> 4));
            wg_commit();
            wg_wait<0>();
            dst = a2w + (size_t)((10 + cc) * 4) * 256;
#pragma unroll
            for (int hh = 0; hh < 4; hh++) {
                acc_fence(nd[hh]);
                const float* n = nd[hh];
                const float i0 = rcp_fast(n[8] + 1e-6f), i1 = rcp_fast(n[10] + 1e-6f);
                uint4 v;
                v.x = pack_bf16(n[0] * i0, n[1] * i0);
                v.y = pack_bf16(n[2] * i1, n[3] * i1);
                v.z = pack_bf16(n[4] * i0, n[5] * i0);
                v.w = pack_bf16(n[6] * i1, n[7] * i1);
                v.y = v.y ? v.y : 0x8000u;
                v.w = v.w ? v.w : 0x8000u;
                st_frag(dst + hh * 256, v);
            }
            TS(wg, 11);
        }
        uint4 af[2][12];
        {
            mainloop128(acc, xa, 34, sb, desc128, lane, wg);
            TS(wg, 12);
            if (!p2_s(0) || !p2_s(1) || !p2_s(2)) {
                const int bid = fresh_bid();
                const uint4* a2r = g_A2 + (size_t)(*(volatile unsigned*)(smem + OFF_EPOCH) & 1) * A2_N +
                                   (size_t)(((bid >> 3) * 2 + (bid & 1)) * 18) * 4 * 256 + fresh_tid();
#pragma unroll
                for (int i = 0; i < 12; i++)
                    if (!p2_s(i >> 2)) af[0][i] = ld_frag(a2r + (p2_id(i >> 2) * 4 + (i & 3)) * 256);
            }
            const RowScale r0 = row_scale(sd0), r1 = row_scale(sd1);
            uint4* dst = a2_write_ptr(smem) + (size_t)((14 + (fresh_bid() & 3)) * 4) * 256;
#pragma unroll
            for (int ks = 0; ks < 4; ks++) st_frag(dst + ks * 256, swiglu8(&acc[ks * 8], &acc[32 + ks * 8], r0, r1));
            TS(wg, 15);
        }

        {
            const int tid = fresh_tid(), bid = fresh_bid();
            const int lane = tid & 31, w = (tid >> 5) & 3, g = lane >> 2, t = lane & 3;
            const int rank = bid & 1, m2 = bid >> 3, j2 = (bid >> 1) & 3;
            const uint4* a2r = g_A2 + (size_t)(*(volatile unsigned*)(smem + OFF_EPOCH) & 1) * A2_N +
                               (size_t)((m2 * 2 + rank) * 18) * 4 * 256 + tid;
            float ao[32], ap[32];
            const uint32_t dso = desc128 + 512, dsp = desc128;
            TS(wg, 16);
#pragma unroll
            for (int gi = 0; gi < 6; gi++) {
                if (gi == 5) TS(wg, 17);
                uint4(&f)[12] = af[gi & 1];
#pragma unroll
                for (int bb = 0; bb < 3; bb++) {
                    const int ub = p2_useB(gi * 3 + bb);
                    if (p2_s(gi * 3 + bb)) {
                        mbar_wait(sb + BAR_FULL + 8 * ring_slot(ub - 1), ring_lap(ub - 1) & 1);
                        const uint4* src = (const uint4*)(smem + ring_slot(ub - 1) * STAGE_BYTES) + tid;
#pragma unroll
                        for (int ks = 0; ks < 4; ks++) f[bb * 4 + ks] = src[ks * 256];
                    }
                    mbar_wait(sb + BAR_FULL + 8 * ring_slot(ub), ring_lap(ub) & 1);
                }
                {
                    unsigned n = 0;
                    while (frag_stale(f)) {
#pragma unroll
                        for (int i = 0; i < 12; i++) f[i] = ld_frag(a2r + (p2_id(gi * 3 + (i >> 2)) * 4 + (i & 3)) * 256);
                        if (++n > SPIN_LIMIT) asm volatile("trap;");
                    }
                }
#pragma unroll
                for (int bb = 0; bb < 3; bb++)
                    if (p2_s(gi * 3 + bb) && p2_recycled(p2_useB(gi * 3 + bb) - 1) && lane == bb)
                        mbar_arrive(sb + BAR_EMPTY + 8 * ring_slot(p2_useB(gi * 3 + bb) - 1));
                bar_sync(7 + wg, 256);
                wg_fence();
#pragma unroll
                for (int i = 0; i < 12; i++) {
                    const uint32_t so = ring_slot(p2_useB(gi * 3 + (i >> 2))) * (STAGE_BYTES >> 4) + (i & 3) * 128;
                    const uint32_t* a = reinterpret_cast<const uint32_t*>(&f[i]);
                    wgmma_n64_rs<DHI128>(ap, a, dsp + so, (gi | i) != 0);
                    if (gi < 5) wgmma_n64_rs<DHI128>(ao, a, dso + so, (gi | i) != 0);
                }
                wg_commit();
                bar_arrive(8 - wg, 256);
                if (gi < 5) {
#pragma unroll
                    for (int i = 0; i < 12; i++)
                        if (!p2_s(gi * 3 + 3 + (i >> 2)))
                            af[(gi + 1) & 1][i] = ld_frag(a2r + (p2_id(gi * 3 + 3 + (i >> 2)) * 4 + (i & 3)) * 256);
                    wg_wait<0>();
#pragma unroll
                    for (int bb = 0; bb < 3; bb++)
                        if (p2_recycled(p2_useB(gi * 3 + bb)) && lane == bb)
                            mbar_arrive(sb + BAR_EMPTY + 8 * ring_slot(p2_useB(gi * 3 + bb)));
                }
            }
            const int row0 = m2 * 128 + wg * 64 + w * 16 + g;
            const int col0 = j2 * 128 + rank * 64 + 2 * t;
            uint32_t xr[16];
#pragma unroll
            for (int nb = 0; nb < 8; nb++) {
                xr[2 * nb] = __ldg((const uint32_t*)(xg + (size_t)row0 * 512 + col0 + nb * 8));
                xr[2 * nb + 1] = __ldg((const uint32_t*)(xg + (size_t)(row0 + 8) * 512 + col0 + nb * 8));
            }
            const int xslot = wg ? ring_slot(XCH_USE + 1) : ring_slot(XCH_USE);
            uint32_t rdst, rbar;
            asm volatile("mapa.shared::cluster.u32 %0, %1, %2;"
                         : "=r"(rdst) : "r"(sb + xslot * STAGE_BYTES + (tid & 127) * 16), "r"(rank ^ 1));
            asm volatile("mapa.shared::cluster.u32 %0, %1, %2;" : "=r"(rbar) : "r"(sb + BAR_XCHG), "r"(rank ^ 1));
            mbar_wait(sb + BAR_XRDY, 0);
            wg_wait<0>();
            acc_fence(ap);
            TS(wg, 18);
#pragma unroll
            for (int i = 0; i < 8; i++)
                asm volatile("st.async.shared::cluster.mbarrier::complete_tx::bytes.v4.f32 [%0], {%1,%2,%3,%4}, [%5];"
                             ::"r"(rdst + i * 2048), "f"(ap[4 * i]), "f"(ap[4 * i + 1]), "f"(ap[4 * i + 2]), "f"(ap[4 * i + 3]),
                             "r"(rbar) : "memory");
            bar_sync(7 + wg, 256);
            wg_fence();
#pragma unroll
            for (int i = 0; i < 12; i++)
                wgmma_n64_rs<DHI128>(ao, reinterpret_cast<const uint32_t*>(&af[1][i]),
                                     dso + ring_slot(p2_useB(15 + (i >> 2))) * (STAGE_BYTES >> 4) + (i & 3) * 128, 1);
            wg_commit();
            if (wg == 0) bar_arrive(8, 256);
            wg_wait<0>();
            acc_fence(ao);
            mbar_wait(sb + BAR_XCHG, 0);
            TS(wg, 19);
            const float4* rx = (const float4*)(smem + xslot * STAGE_BYTES) + (tid & 127);
#pragma unroll
            for (int nb = 0; nb < 8; nb++) {
                const float4 p = rx[nb * 128];
                const uint32_t o0 = pack_bf16(ao[4 * nb] + p.x + bf_lo(xr[2 * nb]), ao[4 * nb + 1] + p.y + bf_hi(xr[2 * nb]));
                const uint32_t o1 = pack_bf16(ao[4 * nb + 2] + p.z + bf_lo(xr[2 * nb + 1]), ao[4 * nb + 3] + p.w + bf_hi(xr[2 * nb + 1]));
                *(uint32_t*)(outg + (size_t)row0 * 512 + col0 + nb * 8) = o0;
                *(uint32_t*)(outg + (size_t)(row0 + 8) * 512 + col0 + nb * 8) = o1;
            }
        }
        TS(wg, 20);
    }
}

typedef CUresult (*EncodeFn)(CUtensorMap*, CUtensorMapDataType, cuuint32_t, void*, const cuuint64_t*, const cuuint64_t*,
                             const cuuint32_t*, const cuuint32_t*, CUtensorMapInterleave, CUtensorMapSwizzle,
                             CUtensorMapL2promotion, CUtensorMapFloatOOBfill);

void make_map(EncodeFn enc, CUtensorMap* tm, const void* ptr, int rows, int cols, int box_rows, int box_cols,
              CUtensorMapSwizzle swz) {
    cuuint64_t dims[2] = {(cuuint64_t)cols, (cuuint64_t)rows};
    cuuint64_t strides[1] = {(cuuint64_t)cols * 2};
    cuuint32_t box[2] = {(cuuint32_t)box_cols, (cuuint32_t)box_rows};
    cuuint32_t es[2] = {1, 1};
    enc(tm, CU_TENSOR_MAP_DATA_TYPE_BFLOAT16, 2, const_cast<void*>(ptr), dims, strides, box, es,
        CU_TENSOR_MAP_INTERLEAVE_NONE, swz, CU_TENSOR_MAP_L2_PROMOTION_L2_256B, CU_TENSOR_MAP_FLOAT_OOB_FILL_NONE);
}

}

extern "C" void kernel_launch(void* const* d_in, const int* in_sizes, int n_in, void* d_out, int out_size) {
    (void)in_sizes; (void)n_in; (void)out_size;
    static EncodeFn enc = nullptr;
    if (!enc) {
        void* fn = nullptr;
        cudaDriverEntryPointQueryResult qr;
        cudaGetDriverEntryPoint("cuTensorMapEncodeTiled", &fn, cudaEnableDefault, &qr);
        enc = (EncodeFn)fn;
        cudaFuncSetAttribute(fused_kernel, cudaFuncAttributeMaxDynamicSharedMemorySize, SMEM_BYTES);
    }
    const void* x = d_in[0];
    const void* wqkv = d_in[1];
    const void* wo = d_in[2];
    const void* w1 = d_in[4];
    const void* w3 = d_in[5];
    const void* w2 = d_in[6];
    CUtensorMap tx, tqkv, t1, t3, t1h, t3h, t2, t2h, two;
    make_map(enc, &tx, x, 2048, 512, 128, 64, CU_TENSOR_MAP_SWIZZLE_128B);
    make_map(enc, &tqkv, wqkv, 512, 1536, 64, 64, CU_TENSOR_MAP_SWIZZLE_128B);
    make_map(enc, &t1, w1, 512, 1792, 64, 64, CU_TENSOR_MAP_SWIZZLE_128B);
    make_map(enc, &t3, w3, 512, 1792, 64, 64, CU_TENSOR_MAP_SWIZZLE_128B);
    make_map(enc, &t1h, w1, 512, 1792, 64, 32, CU_TENSOR_MAP_SWIZZLE_64B);
    make_map(enc, &t3h, w3, 512, 1792, 64, 32, CU_TENSOR_MAP_SWIZZLE_64B);
    make_map(enc, &t2, w2, 1792, 512, 64, 64, CU_TENSOR_MAP_SWIZZLE_128B);
    make_map(enc, &t2h, w2, 1792, 512, 32, 64, CU_TENSOR_MAP_SWIZZLE_128B);
    make_map(enc, &two, wo, 512, 512, 64, 64, CU_TENSOR_MAP_SWIZZLE_128B);
    fused_kernel<<<128, 384, SMEM_BYTES>>>(tx, tqkv, t1, t3, t1h, t3h, t2, t2h, two, (const __nv_bfloat16*)x,
                                           (__nv_bfloat16*)d_out, (const char*)wqkv, (const char*)w1, (const char*)w3,
                                           (const char*)w2, (const char*)wo);
}
```

```cpp
#include <cuda_runtime.h>
#include <cuda_bf16.h>
#include <cuda.h>
#include <stdint.h>

namespace {

constexpr int NST = 13;
constexpr int STAGE_BYTES = 16384;
constexpr int XST0 = 5;
constexpr int SCR0 = 8;
#define P2_ORDER {0, 1, 2, 3, 4, 8, 5, 6, 9, 7, 10, 12, 11, 13, 14, 15, 16, 17}
#define P2_SMASK 0x16DFu
__host__ __device__ constexpr int p2_id(int i) {
    constexpr int t[18] = P2_ORDER;
    return t[i];
}
__host__ __device__ constexpr bool p2_s(int i) { return (P2_SMASK >> i) & 1; }
__host__ __device__ constexpr int popc18(unsigned v) {
    v = v - ((v >> 1) & 0x55555555u);
    v = (v & 0x33333333u) + ((v >> 2) & 0x33333333u);
    return (int)((((v + (v >> 4)) & 0x0F0F0F0Fu) * 0x01010101u) >> 24);
}
__host__ __device__ constexpr int p2_useB(int i) { return 42 + i + popc18(P2_SMASK & ((2u << i) - 1)); }
constexpr int XCH_USE = p2_useB(17) + 1;
__host__ __device__ constexpr bool p2_recycled(int u) { return u + NST <= XCH_USE + 1; }
constexpr int OFF_MISC = NST * STAGE_BYTES;
constexpr int OFF_KVB = OFF_MISC;
constexpr int OFF_ONES = OFF_MISC + 3072;
constexpr int OFF_BARS = OFF_MISC + 3328;
constexpr int BAR_FULL = OFF_BARS;
constexpr int BAR_EMPTY = BAR_FULL + 8 * NST;
constexpr int BAR_XFULL = BAR_EMPTY + 8 * NST;
constexpr int BAR_KVREADY = BAR_XFULL + 64;
constexpr int BAR_XCHG = BAR_KVREADY + 8;
constexpr int BAR_EPOCH = BAR_XCHG + 8;
constexpr int BAR_XRDY = BAR_EPOCH + 8;
constexpr int OFF_EPOCH = BAR_XRDY + 8;
constexpr int SMEM_BYTES = OFF_MISC + 4096;

constexpr unsigned SPIN_LIMIT = 1u << 24;

constexpr int A2_N = 16 * 2 * 18 * 4 * 256;
__device__ uint4 g_A2[2 * A2_N];
__device__ float4 g_kvacc[2 * 8 * 272];
__device__ unsigned g_kvcnt[8];
__constant__ unsigned char P2_ID[18] = P2_ORDER;
__device__ unsigned g_epoch;
__device__ unsigned g_ticket;

#define TS(role, i)
#define TSW(role, i)

__device__ __forceinline__ uint32_t smem_u32(const void* p) { return (uint32_t)__cvta_generic_to_shared(p); }
__device__ __forceinline__ void mbar_init(uint32_t bar, uint32_t cnt) {
    asm volatile("mbarrier.init.shared::cta.b64 [%0], %1;" ::"r"(bar), "r"(cnt) : "memory");
}
__device__ __forceinline__ void mbar_expect_tx(uint32_t bar, uint32_t bytes) {
    asm volatile("mbarrier.arrive.expect_tx.shared::cta.b64 _, [%0], %1;" ::"r"(bar), "r"(bytes) : "memory");
}
__device__ __forceinline__ void mbar_arrive(uint32_t bar) {
    asm volatile("mbarrier.arrive.shared::cta.b64 _, [%0];" ::"r"(bar) : "memory");
}
__device__ __forceinline__ void mbar_arrive_cta(uint32_t bar, uint32_t cta) {
    asm volatile(
        "{\n.reg .b32 ra;\nmapa.shared::cluster.u32 ra, %0, %1;\n"
        "mbarrier.arrive.shared::cluster.b64 _, [ra];\n}" ::"r"(bar), "r"(cta) : "memory");
}
__device__ __forceinline__ void mbar_wait(uint32_t bar, uint32_t parity) {
    asm volatile(
        "{\n.reg .pred p, q;\n.reg .u32 n;\nmov.u32 n, 0;\n"
        "WAIT_%=:\n"
        "mbarrier.try_wait.parity.shared::cta.b64 p, [%0], %1;\n"
        "@p bra.uni DONE_%=;\n"
        "add.u32 n, n, 1;\n"
        "setp.gt.u32 q, n, %2;\n"
        "@q trap;\n"
        "bra.uni WAIT_%=;\n"
        "DONE_%=:\n}"
        ::"r"(bar), "r"(parity), "n"(SPIN_LIMIT) : "memory");
}
__device__ __forceinline__ unsigned ld_acquire(const unsigned* p) {
    unsigned v;
    asm volatile("ld.acquire.gpu.global.u32 %0, [%1];" : "=r"(v) : "l"(p) : "memory");
    return v;
}
__device__ __forceinline__ void st_release(unsigned* p, unsigned v) {
    asm volatile("st.release.gpu.global.u32 [%0], %1;" ::"l"(p), "r"(v) : "memory");
}
__device__ __forceinline__ unsigned read_epoch() {
    return __shfl_sync(0xffffffffu, *(volatile unsigned*)&g_epoch, 0) + 1;
}
__device__ __forceinline__ void tma_load(uint32_t dst, const CUtensorMap* tm, uint32_t bar, int x, int y) {
    asm volatile(
        "cp.async.bulk.tensor.2d.shared::cluster.global.mbarrier::complete_tx::bytes [%0], [%1, {%3, %4}], [%2];"
        ::"r"(dst), "l"(tm), "r"(bar), "r"(x), "r"(y) : "memory");
}
__device__ __forceinline__ void tma_load_mc(uint32_t dst, const CUtensorMap* tm, uint32_t bar, int x, int y) {
    asm volatile(
        "cp.async.bulk.tensor.2d.shared::cluster.global.mbarrier::complete_tx::bytes.multicast::cluster "
        "[%0], [%1, {%3, %4}], [%2], %5;"
        ::"r"(dst), "l"(tm), "r"(bar), "r"(x), "r"(y), "h"((uint16_t)3) : "memory");
}
__device__ __forceinline__ void prefetch_tm(const CUtensorMap* tm) {
    asm volatile("prefetch.tensormap [%0];" ::"l"(tm) : "memory");
}
__device__ __forceinline__ void l2_prefetch(const void* p, uint32_t bytes) {
    asm volatile("cp.async.bulk.prefetch.L2.global [%0], %1;" ::"l"(p), "r"(bytes) : "memory");
}
__device__ __forceinline__ void bar_sync(int id, int n) { asm volatile("bar.sync %0, %1;" ::"r"(id), "r"(n) : "memory"); }
__device__ __forceinline__ void bar_arrive(int id, int n) { asm volatile("bar.arrive %0, %1;" ::"r"(id), "r"(n) : "memory"); }
__device__ __forceinline__ void wg_fence() { asm volatile("wgmma.fence.sync.aligned;" ::: "memory"); }
__device__ __forceinline__ void wg_commit() { asm volatile("wgmma.commit_group.sync.aligned;" ::: "memory"); }
template <int N>
__device__ __forceinline__ void wg_wait() { asm volatile("wgmma.wait_group.sync.aligned %0;" ::"n"(N) : "memory"); }

__device__ __forceinline__ uint64_t make_desc(uint32_t addr, uint32_t lbo, uint32_t sbo, uint64_t swz) {
    return (uint64_t)((addr & 0x3FFFF) >> 4) | ((uint64_t)(lbo >> 4) << 16) | ((uint64_t)(sbo >> 4) << 32) | (swz << 62);
}

#define ACC8(a, o) "+f"(a[o]), "+f"(a[o + 1]), "+f"(a[o + 2]), "+f"(a[o + 3]), "+f"(a[o + 4]), "+f"(a[o + 5]), "+f"(a[o + 6]), "+f"(a[o + 7])
constexpr uint32_t DHI128 = (1024u >> 4) | (1u << 30);
constexpr uint32_t DHI64 = (512u >> 4) | (2u << 30);
__device__ __forceinline__ void wgmma_n128_rs(float (&d)[64], const uint32_t* a, uint32_t db, int scale_d) {
    asm volatile(
        "{\n.reg .pred p;\n.reg .b64 dd;\nsetp.ne.b32 p, %69, 0;\nmov.b64 dd, {%68, %70};\n"
        "wgmma.mma_async.sync.aligned.m64n128k16.f32.bf16.bf16 "
        "{%0,%1,%2,%3,%4,%5,%6,%7,%8,%9,%10,%11,%12,%13,%14,%15,%16,%17,%18,%19,%20,%21,%22,%23,%24,%25,%26,%27,%28,%29,%30,%31,"
        "%32,%33,%34,%35,%36,%37,%38,%39,%40,%41,%42,%43,%44,%45,%46,%47,%48,%49,%50,%51,%52,%53,%54,%55,%56,%57,%58,%59,%60,%61,%62,%63},"
        "{%64,%65,%66,%67}, dd, p, 1, 1, 1;\n}"
        : ACC8(d, 0), ACC8(d, 8), ACC8(d, 16), ACC8(d, 24), ACC8(d, 32), ACC8(d, 40), ACC8(d, 48), ACC8(d, 56)
        : "r"(a[0]), "r"(a[1]), "r"(a[2]), "r"(a[3]), "r"(db), "r"(scale_d), "n"(DHI128));
}
template <uint32_t HI>
__device__ __forceinline__ void wgmma_n64_rs(float (&d)[32], const uint32_t* a, uint32_t db, int scale_d) {
    asm volatile(
        "{\n.reg .pred p;\n.reg .b64 dd;\nsetp.ne.b32 p, %37, 0;\nmov.b64 dd, {%36, %38};\n"
        "wgmma.mma_async.sync.aligned.m64n64k16.f32.bf16.bf16 "
        "{%0,%1,%2,%3,%4,%5,%6,%7,%8,%9,%10,%11,%12,%13,%14,%15,%16,%17,%18,%19,%20,%21,%22,%23,%24,%25,%26,%27,%28,%29,%30,%31},"
        "{%32,%33,%34,%35}, dd, p, 1, 1, 1;\n}"
        : ACC8(d, 0), ACC8(d, 8), ACC8(d, 16), ACC8(d, 24)
        : "r"(a[0]), "r"(a[1]), "r"(a[2]), "r"(a[3]), "r"(db), "r"(scale_d), "n"(HI));
}
__device__ __forceinline__ void wgmma_n64_ss_tt(float (&d)[32], uint64_t da, uint64_t db, int scale_d) {
    asm volatile(
        "{\n.reg .pred p;\nsetp.ne.b32 p, %34, 0;\n"
        "wgmma.mma_async.sync.aligned.m64n64k16.f32.bf16.bf16 "
        "{%0,%1,%2,%3,%4,%5,%6,%7,%8,%9,%10,%11,%12,%13,%14,%15,%16,%17,%18,%19,%20,%21,%22,%23,%24,%25,%26,%27,%28,%29,%30,%31},"
        "%32, %33, p, 1, 1, 1, 1;\n}"
        : ACC8(d, 0), ACC8(d, 8), ACC8(d, 16), ACC8(d, 24)
        : "l"(da), "l"(db), "r"(scale_d));
}
__device__ __forceinline__ void wgmma_n8_ss_tn(float (&d)[4], uint64_t da, uint64_t db, int scale_d) {
    asm volatile(
        "{\n.reg .pred p;\nsetp.ne.b32 p, %6, 0;\n"
        "wgmma.mma_async.sync.aligned.m64n8k16.f32.bf16.bf16 {%0,%1,%2,%3}, %4, %5, p, 1, 1, 1, 0;\n}"
        : "+f"(d[0]), "+f"(d[1]), "+f"(d[2]), "+f"(d[3])
        : "l"(da), "l"(db), "r"(scale_d));
}
__device__ __forceinline__ void wgmma_n24_rs(float (&d)[12], const uint32_t* a, uint64_t db) {
    asm volatile(
        "wgmma.mma_async.sync.aligned.m64n24k16.f32.bf16.bf16 {%0,%1,%2,%3,%4,%5,%6,%7,%8,%9,%10,%11}, "
        "{%12,%13,%14,%15}, %16, 0, 1, 1, 0;"
        : ACC8(d, 0), "+f"(d[8]), "+f"(d[9]), "+f"(d[10]), "+f"(d[11])
        : "r"(a[0]), "r"(a[1]), "r"(a[2]), "r"(a[3]), "l"(db));
}
template <int N>
__device__ __forceinline__ void acc_fence(float (&d)[N]) {
#pragma unroll
    for (int i = 0; i < N; i++) asm volatile("" : "+f"(d[i])::"memory");
}
__device__ __forceinline__ void mma16816(float (&c)[4], const uint32_t* a, uint32_t b0, uint32_t b1) {
    asm volatile(
        "mma.sync.aligned.m16n8k16.row.col.f32.bf16.bf16.f32 {%0,%1,%2,%3}, {%4,%5,%6,%7}, {%8,%9}, {%0,%1,%2,%3};"
        : "+f"(c[0]), "+f"(c[1]), "+f"(c[2]), "+f"(c[3])
        : "r"(a[0]), "r"(a[1]), "r"(a[2]), "r"(a[3]), "r"(b0), "r"(b1));
}
__device__ __forceinline__ uint32_t pack_bf16(float lo, float hi) {
    uint32_t r;
    asm("cvt.rn.bf16x2.f32 %0, %1, %2;" : "=r"(r) : "f"(hi), "f"(lo));
    return r;
}
__device__ __forceinline__ float bf_lo(uint32_t v) { return __uint_as_float(v << 16); }
__device__ __forceinline__ float bf_hi(uint32_t v) { return __uint_as_float(v & 0xffff0000u); }
__device__ __forceinline__ float bf16_round(float v) { return __bfloat162float(__float2bfloat16_rn(v)); }
__device__ __forceinline__ float sqrt_fast(float v) {
    float r;
    asm("sqrt.approx.ftz.f32 %0, %1;" : "=f"(r) : "f"(v));
    return r;
}
__device__ __forceinline__ float rcp_fast(float v) {
    float r;
    asm("rcp.approx.ftz.f32 %0, %1;" : "=f"(r) : "f"(v));
    return r;
}
__device__ __forceinline__ float ex2_fast(float v) {
    float r;
    asm("ex2.approx.ftz.f32 %0, %1;" : "=f"(r) : "f"(v));
    return r;
}
__device__ __forceinline__ int fresh_tid() {
    int v;
    asm volatile("mov.u32 %0, %%tid.x;" : "=r"(v));
    return v;
}
__device__ __forceinline__ int fresh_bid() {
    int v;
    asm volatile("mov.u32 %0, %%ctaid.x;" : "=r"(v));
    return v;
}
struct RowScale { float rho, rl, var; };
__device__ __forceinline__ RowScale row_scale(float sd) {
    asm volatile("" : "+f"(sd));
    RowScale r;
    r.rho = rcp_fast(sd);
    r.rl = r.rho * 1.4426950408889634f;
    r.var = sd * sd;
    return r;
}
__device__ __forceinline__ uint4* a2_write_ptr(const uint8_t* smem) {
    const int bid = fresh_bid();
    const unsigned par = *(volatile const unsigned*)(smem + OFF_EPOCH) & 1;
    return g_A2 + (size_t)par * A2_N + (size_t)(((bid >> 3) * 2 + ((bid >> 2) & 1)) * 18) * 4 * 256 + fresh_tid();
}
__device__ __forceinline__ float phi_f(float a, const RowScale& r) {
    return fmaf(fmaxf(a, 0.f), r.rho, ex2_fast(fminf(a, 0.f) * r.rl) + 1e-6f);
}
__device__ __forceinline__ float swiglu_f(float ga, float ua, const RowScale& r) {
    return (ga * ua) * rcp_fast(fmaf(ex2_fast(-ga * r.rl), r.var, r.var));
}
__device__ __forceinline__ uint4 swiglu8(const float* gp, const float* up, const RowScale& r0, const RowScale& r1) {
    uint4 v;
    v.x = pack_bf16(swiglu_f(gp[0], up[0], r0), swiglu_f(gp[1], up[1], r0));
    v.y = pack_bf16(swiglu_f(gp[2], up[2], r1), swiglu_f(gp[3], up[3], r1));
    v.z = pack_bf16(swiglu_f(gp[4], up[4], r0), swiglu_f(gp[5], up[5], r0));
    v.w = pack_bf16(swiglu_f(gp[6], up[6], r1), swiglu_f(gp[7], up[7], r1));
    v.y = v.y ? v.y : 0x8000u;
    v.w = v.w ? v.w : 0x8000u;
    return v;
}
__device__ __forceinline__ bool frag_stale(const uint4 (&f)[12]) {
    unsigned v = min(f[0].y, f[0].w);
#pragma unroll
    for (int i = 1; i < 12; i++) v = min(v, min(f[i].y, f[i].w));
    return __any_sync(0xffffffffu, v == 0u);
}
__device__ __forceinline__ void st_frag(uint4* p, uint4 v) {
    asm volatile("st.relaxed.gpu.global.v4.u32 [%0], {%1,%2,%3,%4};" ::"l"(p), "r"(v.x), "r"(v.y), "r"(v.z), "r"(v.w) : "memory");
}
__device__ __forceinline__ uint4 ld_frag(const uint4* p) {
    uint4 v;
    asm volatile("ld.relaxed.gpu.global.v4.u32 {%0,%1,%2,%3}, [%4];" : "=r"(v.x), "=r"(v.y), "=r"(v.z), "=r"(v.w) : "l"(p) : "memory");
    return v;
}
__device__ __forceinline__ void red_add2(float* p, float a, float b) {
    asm volatile("red.global.add.v2.f32 [%0], {%1, %2};" ::"l"(p), "f"(a), "f"(b) : "memory");
}
__device__ __forceinline__ void cp_async16(uint32_t dst, const void* src) {
    asm volatile("cp.async.cg.shared.global [%0], [%1], 16;" ::"r"(dst), "l"(src) : "memory");
}

__host__ __device__ constexpr int ring_lap(int u) { return (u * 79) >> 10; }
__host__ __device__ constexpr int ring_slot(int u) { return u - NST * ring_lap(u); }

__device__ __forceinline__ void mainloop128(float (&acc)[64], const uint32_t (&xa)[128], int u0, uint32_t sb,
                                            uint32_t desc128, int lane, int wg, bool last = false) {
    bar_sync(7 + wg, 256);
#pragma unroll
    for (int kb = 0; kb < 8; kb++) {
        const int st = ring_slot(u0 + kb);
        mbar_wait(sb + BAR_FULL + 8 * st, ring_lap(u0 + kb) & 1);
        wg_fence();
        const uint32_t d = desc128 + st * (STAGE_BYTES >> 4);
#pragma unroll
        for (int ks = 0; ks < 4; ks++) wgmma_n128_rs(acc, &xa[(kb * 4 + ks) * 4], d + ks * 128, (kb | ks) != 0);
        wg_commit();
        if (kb == 7 && !(last && wg == 1)) bar_arrive(8 - wg, 256);
        if (kb > 0) {
            wg_wait<1>();
            if (lane == 0) mbar_arrive(sb + BAR_EMPTY + 8 * ring_slot(u0 + kb - 1));
        }
    }
    wg_wait<0>();
    acc_fence(acc);
    if (lane == 0) mbar_arrive(sb + BAR_EMPTY + 8 * ring_slot(u0 + 7));
}
__device__ __forceinline__ void mainloop64x2(float (&a0)[32], float (&a1)[32], const uint32_t (&xa)[128], int u0,
                                             uint32_t sb, uint32_t desc128, int lane, int wg) {
    bar_sync(7 + wg, 256);
#pragma unroll
    for (int kb = 0; kb < 8; kb++) {
        const int st = ring_slot(u0 + kb);
        mbar_wait(sb + BAR_FULL + 8 * st, ring_lap(u0 + kb) & 1);
        wg_fence();
        const uint32_t d = desc128 + st * (STAGE_BYTES >> 4);
        const uint32_t d2 = d + (8192 >> 4) - ((4096u >> 4) << 16);
#pragma unroll
        for (int ks = 0; ks < 4; ks++) {
            wgmma_n64_rs<DHI128>(a0, &xa[(kb * 4 + ks) * 4], d + ks * 128, (kb | ks) != 0);
            wgmma_n64_rs<DHI64>(a1, &xa[(kb * 4 + ks) * 4], d2 + ks * 64, (kb | ks) != 0);
        }
        wg_commit();
        if (kb == 7) bar_arrive(8 - wg, 256);
        if (kb > 0) {
            wg_wait<1>();
            if (lane == 0) mbar_arrive(sb + BAR_EMPTY + 8 * ring_slot(u0 + kb - 1));
        }
    }
    wg_wait<0>();
    acc_fence(a0);
    acc_fence(a1);
    if (lane == 0) mbar_arrive(sb + BAR_EMPTY + 8 * ring_slot(u0 + 7));
}

__global__ void __cluster_dims__(2, 1, 1) __launch_bounds__(384, 1)
fused_kernel(const __grid_constant__ CUtensorMap tm_x, const __grid_constant__ CUtensorMap tm_qkv,
             const __grid_constant__ CUtensorMap tm_w1, const __grid_constant__ CUtensorMap tm_w3,
             const __grid_constant__ CUtensorMap tm_w1h, const __grid_constant__ CUtensorMap tm_w3h,
             const __grid_constant__ CUtensorMap tm_w2, const __grid_constant__ CUtensorMap tm_w2h,
             const __grid_constant__ CUtensorMap tm_wo, const __nv_bfloat16* __restrict__ xg,
             __nv_bfloat16* __restrict__ outg, const char* __restrict__ p_qkv, const char* __restrict__ p_w1,
             const char* __restrict__ p_w3, const char* __restrict__ p_w2, const char* __restrict__ p_wo) {
    extern __shared__ __align__(1024) uint8_t smem[];
    const uint32_t sb = smem_u32(smem);
    const int tid = threadIdx.x;
    const int warp = tid >> 5, lane = tid & 31;
    const int rank = blockIdx.x & 1;
    const int pair = blockIdx.x >> 1;
    const int m = pair >> 2;
    const int j2 = pair & 3;
    const int c = 2 * j2 + rank;
    const int m2 = m;

    TS(tid >> 7, 0);
    if (tid == 256) {
        prefetch_tm(&tm_x);
#pragma unroll
        for (int i = 0; i < 8; i++) mbar_init(sb + BAR_XFULL + 8 * i, 1);
#pragma unroll
        for (int kb = 0; kb < 8; kb++) mbar_expect_tx(sb + BAR_XFULL + 8 * kb, 16384);
        asm volatile("fence.mbarrier_init.release.cluster;" ::: "memory");
        TS(2, 21);
    } else if (tid == 0) {
#pragma unroll
        for (int i = 0; i < NST; i++) mbar_init(sb + BAR_FULL + 8 * i, 1);
        asm volatile("fence.mbarrier_init.release.cluster;" ::: "memory");
    } else if (tid == 32) {
#pragma unroll
        for (int i = 0; i < NST; i++) mbar_init(sb + BAR_EMPTY + 8 * i, 8);
        asm volatile("fence.mbarrier_init.release.cluster;" ::: "memory");
    } else if (tid == 64) {
#pragma unroll
        for (int i = 0; i < 4; i++) mbar_init(sb + BAR_KVREADY + 8 * i, 1);
        mbar_expect_tx(sb + BAR_XCHG, 32768);
        asm volatile("fence.mbarrier_init.release.cluster;" ::: "memory");
    } else if (tid == 288) {
        prefetch_tm(&tm_qkv);
        prefetch_tm(&tm_w1);
        prefetch_tm(&tm_w3);
        prefetch_tm(&tm_w1h);
        prefetch_tm(&tm_w3h);
        prefetch_tm(&tm_w2);
        prefetch_tm(&tm_w2h);
        prefetch_tm(&tm_wo);
    } else if (tid >= 320) {
        ((uint32_t*)(smem + OFF_ONES))[tid - 320] = 0x3F803F80u;
        asm volatile("fence.proxy.async.shared::cta;" ::: "memory");
    }
    __syncthreads();
    TS(tid >> 7, 22);
    asm volatile("barrier.cluster.arrive.relaxed.aligned;\nbarrier.cluster.wait.acquire.aligned;" ::: "memory");

    if (warp >= 8) {
        asm volatile("setmaxnreg.dec.sync.aligned.u32 40;");
        if (warp == 8) {
            if (lane == 0) {
                int st = 0;
                uint32_t lap = 0;
                unsigned par = 0;
#pragma unroll
                for (int i = 0; i < 4; i++) {
                    const int kb = 2 * i + rank;
                    tma_load_mc(sb + (XST0 + kb) * STAGE_BYTES, &tm_x, sb + BAR_XFULL + 8 * kb, kb * 64, m * 128);
                }
                for (int it = 0; it < 40; it++) {
                    const int tile = it >> 3, kb = it & 7;
                    const uint32_t full = sb + BAR_FULL + 8 * st;
                    mbar_wait(sb + BAR_EMPTY + 8 * st, (st >= XST0) ? (lap & 1) : ((lap & 1) ^ 1));
                    mbar_expect_tx(full, STAGE_BYTES);
                    const uint32_t dst = sb + st * STAGE_BYTES;
                    if (tile == 0) {
                        tma_load(dst, &tm_qkv, full, 512 + 64 * c, kb * 64);
                        tma_load(dst + 8192, &tm_qkv, full, 1024 + 64 * c, kb * 64);
                    } else if (tile != 3) {
                        const int col = 224 * c + 64 * (tile == 4 ? 2 : tile - 1);
                        tma_load(dst, &tm_w1, full, col, kb * 64);
                        tma_load(dst + 8192, &tm_w3, full, col, kb * 64);
                    } else {
                        tma_load(dst, &tm_qkv, full, 64 * c, kb * 64);
                        tma_load(dst + 8192, &tm_w1h, full, 224 * c + 192, kb * 64);
                        tma_load(dst + 12288, &tm_w3h, full, 224 * c + 192, kb * 64);
                    }
                    if (++st == NST) { st = 0; lap++; }
                    if (it == 7) {
                        mbar_wait(sb + BAR_EPOCH, 0);
                        par = *(volatile unsigned*)(smem + OFF_EPOCH) & 1;
                        mbar_wait(sb + BAR_EMPTY + 8 * SCR0, 0);
                        mbar_arrive(sb + BAR_FULL + 8 * SCR0);
                        mbar_wait(sb + BAR_EMPTY + 8 * (SCR0 + 1), 0);
                        mbar_arrive(sb + BAR_FULL + 8 * (SCR0 + 1));
                        st += 2;
                    }
                }
                TS(2, 1);
                const char* a2b = (const char*)(g_A2 + (size_t)par * A2_N + (size_t)((m2 * 2 + rank) * 18) * 4 * 256);
#pragma unroll 1
                for (int i = 0; i < 18; i++) {
                    const int b = P2_ID[i];
                    if ((P2_SMASK >> i) & 1) {
                        mbar_wait(sb + BAR_EMPTY + 8 * st, (st >= XST0) ? (lap & 1) : ((lap & 1) ^ 1));
                        mbar_expect_tx(sb + BAR_FULL + 8 * st, STAGE_BYTES);
                        asm volatile("cp.async.bulk.shared::cluster.global.mbarrier::complete_tx::bytes [%0], [%1], 16384, [%2];"
                                     ::"r"(sb + st * STAGE_BYTES), "l"(a2b + b * 16384), "r"(sb + BAR_FULL + 8 * st) : "memory");
                        if (++st == NST) { st = 0; lap++; }
                    }
                    const uint32_t full = sb + BAR_FULL + 8 * st;
                    const uint32_t dst = sb + st * STAGE_BYTES;
                    mbar_wait(sb + BAR_EMPTY + 8 * st, (st >= XST0) ? (lap & 1) : ((lap & 1) ^ 1));
                    mbar_expect_tx(full, STAGE_BYTES);
                    const int cp = 128 * j2 + 64 * (rank ^ 1), co = 128 * j2 + 64 * rank;
                    if (b < 8 || b >= 14) {
                        const int row = (b < 8) ? 224 * (4 * rank + (b & 3)) + 64 * (b >> 2) : 224 * (4 * rank + b - 14) + 128;
                        tma_load(dst, &tm_w2, full, cp, row);
                        tma_load(dst + 8192, &tm_w2, full, co, row);
                    } else if (b < 10) {
                        const int row = 224 * (4 * rank + 2 * (b - 8)) + 192;
                        tma_load(dst, &tm_w2h, full, cp, row);
                        tma_load(dst + 4096, &tm_w2h, full, cp, row + 224);
                        tma_load(dst + 8192, &tm_w2h, full, co, row);
                        tma_load(dst + 12288, &tm_w2h, full, co, row + 224);
                    } else {
                        const int row = 64 * (4 * rank + (b - 10));
                        tma_load(dst, &tm_wo, full, cp, row);
                        tma_load(dst + 8192, &tm_wo, full, co, row);
                    }
                    TS(2, 2 + i);
                    if (++st == NST) { st = 0; lap++; }
                }
#pragma unroll
                for (int k = 0; k < 2; k++)
                    mbar_wait(sb + BAR_EMPTY + 8 * ring_slot(XCH_USE + k),
                              (ring_lap(XCH_USE + k) & 1) ^ (ring_slot(XCH_USE + k) >= XST0 ? 0 : 1));
                mbar_arrive_cta(sb + BAR_XRDY, rank ^ 1);
                TS(2, 20);
            }
        } else if (warp < 11) {
            const int wg = warp - 9;
            bar_sync(3 + wg, 160);
            if (lane == 0) asm volatile("red.release.gpu.global.add.u32 [%0], 1;" ::"l"(&g_kvcnt[c]) : "memory");
            TSW(3, wg);
            mbar_wait(sb + BAR_EPOCH, 0);
            const unsigned par = *(volatile unsigned*)(smem + OFF_EPOCH) & 1;
            uint4* z = g_A2 + (size_t)(par ^ 1) * A2_N + (size_t)((m * 2 + (c >> 2)) * 18) * 4 * 256 + wg * 128 + lane;
            const int cc = c & 3;
#pragma unroll 1
            for (int i = 0; i < 18; i++) {
                const int blk = (i < 8) ? ((i >> 2) * 4 + cc) * 4 + (i & 3)
                              : (i < 10) ? (8 + (cc >> 1)) * 4 + 2 * (cc & 1) + (i - 8)
                              : (i < 14) ? (10 + cc) * 4 + (i - 10) : (14 + cc) * 4 + (i - 14);
#pragma unroll
                for (int k = 0; k < 4; k++) z[blk * 256 + k * 32] = make_uint4(0, 0, 0, 0);
                __nanosleep(300);
            }
        } else {
            const unsigned epoch = read_epoch();
            if (lane == 0) {
                const unsigned tk = atomicInc(&g_ticket, 127u);
                if (tk == 127u) *(volatile unsigned*)&g_epoch = epoch;
            }
            if (lane == 0) *(volatile unsigned*)(smem + OFF_EPOCH) = epoch;
            __syncwarp();
            if (lane == 0) mbar_arrive(sb + BAR_EPOCH);
            if (lane < 17) g_kvacc[(((epoch & 1) ^ 1) * 8 + c) * 272 + 17 * m + lane] = make_float4(0.f, 0.f, 0.f, 0.f);
            {
                unsigned n = 0;
                while ((int)(ld_acquire(&g_kvcnt[c]) - 32u * epoch) < 0) {
                    __nanosleep(200);
                    if (++n > SPIN_LIMIT) asm volatile("trap;");
                }
            }
            TSW(4, 0);
            const int g = lane >> 2, t = lane & 3;
            const float* ks = (const float*)(g_kvacc + ((epoch & 1) * 8 + c) * 272) + 32 * t + g;
            uint32_t* kb = (uint32_t*)(smem + OFF_KVB) + g * 4 + t;
#pragma unroll 2
            for (int hh = 0; hh < 4; hh++) {
                const float* k = ks + hh * 272;
                const float a0 = __ldcg(k), a1 = __ldcg(k + 16), a2 = __ldcg(k + 128), a3 = __ldcg(k + 144);
                const float b0 = __ldcg(k + 8), b1 = __ldcg(k + 24), b2 = __ldcg(k + 136), b3 = __ldcg(k + 152);
                const float2 z0 = __ldcg((const float2*)(k - g - 30 * t + 256)), z1 = __ldcg((const float2*)(k - g - 30 * t + 264));
                uint32_t* o = kb + hh * 192;
                o[0] = pack_bf16(a0, a1);
                o[32] = pack_bf16(a2, a3);
                o[64] = pack_bf16(b0, b1);
                o[96] = pack_bf16(b2, b3);
                o[128] = pack_bf16(z0.x, z0.y);
                o[160] = pack_bf16(z1.x, z1.y);
            }
            asm volatile("fence.proxy.async.shared::cta;" ::: "memory");
            __syncwarp();
            if (lane == 0) mbar_arrive(sb + BAR_KVREADY);
            TSW(4, 4);
        }
    } else {
        asm volatile("setmaxnreg.inc.sync.aligned.u32 232;");
        const int wg = warp >> 2, w = warp & 3;
        const int g = lane >> 2, t = lane & 3;
        float acc[64];
        uint32_t xa[128];
        float sd0, sd1;

        TS(wg, 1);
        {
            const int row = wg * 64 + w * 16 + (lane & 7) + ((lane >> 3) & 1) * 8;
            const uint32_t rbase = sb + XST0 * STAGE_BYTES + row * 128;
            const int hi = lane >> 4, r7 = lane & 7;
            float sm[2][4], c0[2][4], c1[2][4];
#pragma unroll
            for (int i = 0; i < 8; i++) { sm[i >> 2][i & 3] = 0.f; c0[i >> 2][i & 3] = 0.f; c1[i >> 2][i & 3] = 0.f; }
            if (wg == 1) bar_arrive(7, 256);
#pragma unroll
            for (int kb = 0; kb < 8; kb++) {
                mbar_wait(sb + BAR_XFULL + 8 * kb, 0);
#pragma unroll
                for (int ks = 0; ks < 4; ks++) {
                    uint32_t* a = &xa[(kb * 4 + ks) * 4];
                    const uint32_t addr = rbase + kb * STAGE_BYTES + (((2 * ks + hi) ^ r7) << 4);
                    asm volatile("ldmatrix.sync.aligned.m8n8.x4.shared.b16 {%0,%1,%2,%3}, [%4];"
                                 : "=r"(a[0]), "=r"(a[1]), "=r"(a[2]), "=r"(a[3]) : "r"(addr) : "memory");
                    mma16816(sm[ks & 1], a, 0x3F803F80u, 0x3F803F80u);
                    mma16816(c0[ks & 1], a, a[0], a[2]);
                    mma16816(c1[ks & 1], a, a[1], a[3]);
                }
            }
            TS(wg, 2);
            const float mean0 = (sm[0][0] + sm[1][0]) * (1.f / 512.f);
            const float mean1 = (sm[0][2] + sm[1][2]) * (1.f / 512.f);
            __syncwarp();
            if (lane < 8) mbar_arrive(sb + BAR_EMPTY + 8 * (XST0 + lane));
            const __nv_bfloat162 mb0 = __float2bfloat162_rn(mean0), mb1 = __float2bfloat162_rn(mean1);
#pragma unroll
            for (int i = 0; i < 128; i++) {
                __nv_bfloat162 v = *reinterpret_cast<__nv_bfloat162*>(&xa[i]);
                v = __hsub2(v, (i & 1) ? mb1 : mb0);
                xa[i] = *reinterpret_cast<uint32_t*>(&v);
            }
            const float d0 = (g & 1) ? c0[0][1] + c0[1][1] : c0[0][0] + c0[1][0];
            const float d1 = (g & 1) ? c1[0][3] + c1[1][3] : c1[0][2] + c1[1][2];
            const int src = (lane & ~3) | (g >> 1);
            const float var0 = fmaxf(__shfl_sync(0xffffffffu, d0, src) * (1.f / 512.f) - mean0 * mean0, 0.f);
            const float var1 = fmaxf(__shfl_sync(0xffffffffu, d1, src) * (1.f / 512.f) - mean1 * mean1, 0.f);
            sd0 = bf16_round(sqrt_fast(bf16_round(bf16_round(var0) + 1e-5f)));
            sd1 = bf16_round(sqrt_fast(bf16_round(bf16_round(var1) + 1e-5f)));
        }

        TS(wg, 3);
        const uint32_t desc128 = ((sb & 0x3FFFF) >> 4) | ((8192u >> 4) << 16);

        {
            mainloop128(acc, xa, 0, sb, desc128, lane, wg);
            TS(wg, 4);
            {
                TS(wg, 24);
                const RowScale r0 = row_scale(sd0), r1 = row_scale(sd1);
                const float rho0 = r0.rho, rho1 = r1.rho;
                const uint32_t pkb = sb + (SCR0 + wg) * STAGE_BYTES;
                mbar_wait(sb + BAR_FULL + 8 * (SCR0 + wg), 0);
                const uint32_t ra = pkb + (w * 16 + g) * 128 + t * 4;
#pragma unroll
                for (int nb = 0; nb < 8; nb++) {
                    const uint32_t off = (uint32_t)((nb ^ g) << 4);
                    uint32_t p0 = pack_bf16(phi_f(acc[nb * 4], r0), phi_f(acc[nb * 4 + 1], r0));
                    uint32_t p1 = pack_bf16(phi_f(acc[nb * 4 + 2], r1), phi_f(acc[nb * 4 + 3], r1));
                    uint32_t v0 = pack_bf16(acc[32 + nb * 4] * rho0, acc[32 + nb * 4 + 1] * rho0);
                    uint32_t v1 = pack_bf16(acc[32 + nb * 4 + 2] * rho1, acc[32 + nb * 4 + 3] * rho1);
                    asm volatile("st.shared.u32 [%0], %1;" ::"r"(ra + off), "r"(p0) : "memory");
                    asm volatile("st.shared.u32 [%0], %1;" ::"r"(ra + off + 1024), "r"(p1) : "memory");
                    asm volatile("st.shared.u32 [%0], %1;" ::"r"(ra + off + 8192), "r"(v0) : "memory");
                    asm volatile("st.shared.u32 [%0], %1;" ::"r"(ra + off + 8192 + 1024), "r"(v1) : "memory");
                }
                TS(wg, 25);
                asm volatile("fence.proxy.async.shared::cta;" ::: "memory");
                bar_sync(1 + wg, 128);
                TS(wg, 26);
                const uint64_t da = make_desc(pkb, 8192, 1024, 1);
                const uint64_t db = make_desc(pkb + 8192, 8192, 1024, 1);
                const uint64_t d1 = make_desc(sb + OFF_ONES, 128, 128, 0);
                float kva[32], za[4];
                wg_fence();
#pragma unroll
                for (int ks = 0; ks < 4; ks++) {
                    wgmma_n64_ss_tt(kva, da + ks * 128, db + ks * 128, ks != 0);
                    wgmma_n8_ss_tn(za, da + ks * 128, d1, ks != 0);
                }
                wg_commit();
                wg_wait<0>();
                acc_fence(kva);
                acc_fence(za);
                if (lane < 2) mbar_arrive(sb + BAR_EMPTY + 8 * (SCR0 + lane));
                TS(wg, 27);
                float o[8];
#pragma unroll
                for (int i = 0; i < 8; i++)
                    o[i] = (w == 0) ? kva[i] : (w == 1) ? kva[8 + i] : (w == 2) ? kva[16 + i] : kva[24 + i];
                mbar_wait(sb + BAR_EPOCH, 0);
                const unsigned par = *(volatile unsigned*)(smem + OFF_EPOCH) & 1;
                float* dst = (float*)(g_kvacc + (par * 8 + c) * 272) + w * 272 + g * 16 + 2 * t;
                red_add2(dst, o[0], o[1]);
                red_add2(dst + 128, o[2], o[3]);
                red_add2(dst + 8, o[4], o[5]);
                red_add2(dst + 136, o[6], o[7]);
                if (t == 0) {
                    atomicAdd(dst - g * 15 + 256, za[0]);
                    atomicAdd(dst - g * 15 + 264, za[2]);
                }
            }
            bar_arrive(3 + wg, 160);
            TS(wg, 5);
        }
#pragma unroll
        for (int tile = 1; tile < 3; tile++) {
            mainloop128(acc, xa, 2 + 8 * tile, sb, desc128, lane, wg);
            TS(wg, 4 + 2 * tile);
            const RowScale r0 = row_scale(sd0), r1 = row_scale(sd1);
            uint4* dst = a2_write_ptr(smem) + (size_t)((4 * (tile - 1) + (fresh_bid() & 3)) * 4) * 256;
#pragma unroll
            for (int ks = 0; ks < 4; ks++) st_frag(dst + ks * 256, swiglu8(&acc[ks * 8], &acc[32 + ks * 8], r0, r1));
            TS(wg, 5 + 2 * tile);
        }
        {
            float qa[32], gu[32];
            mainloop64x2(qa, gu, xa, 26, sb, desc128, lane, wg);
            TS(wg, 10);
            const RowScale r0 = row_scale(sd0), r1 = row_scale(sd1);
            uint4* const a2w = a2_write_ptr(smem);
            const int cc = fresh_bid() & 3;
            uint4* dst = a2w + (size_t)((8 + (cc >> 1)) * 4 + 2 * (cc & 1)) * 256;
#pragma unroll
            for (int ks = 0; ks < 2; ks++) st_frag(dst + ks * 256, swiglu8(&gu[ks * 8], &gu[16 + ks * 8], r0, r1));
            uint32_t pq[16];
#pragma unroll
            for (int i = 0; i < 16; i++) {
                const RowScale& r = (i & 1) ? r1 : r0;
                pq[i] = pack_bf16(phi_f(qa[2 * i], r), phi_f(qa[2 * i + 1], r));
            }
            TS(wg, 13);
            mbar_wait(sb + BAR_KVREADY, 0);
            TS(wg, 14);
            float nd[4][12];
            const uint64_t dk = make_desc(sb + OFF_KVB, 128, 256, 0);
            wg_fence();
#pragma unroll
            for (int hh = 0; hh < 4; hh++) wgmma_n24_rs(nd[hh], &pq[4 * hh], dk + hh * (768 >> 4));
            wg_commit();
            wg_wait<0>();
            dst = a2w + (size_t)((10 + cc) * 4) * 256;
#pragma unroll
            for (int hh = 0; hh < 4; hh++) {
                acc_fence(nd[hh]);
                const float* n = nd[hh];
                const float i0 = rcp_fast(n[8] + 1e-6f), i1 = rcp_fast(n[10] + 1e-6f);
                uint4 v;
                v.x = pack_bf16(n[0] * i0, n[1] * i0);
                v.y = pack_bf16(n[2] * i1, n[3] * i1);
                v.z = pack_bf16(n[4] * i0, n[5] * i0);
                v.w = pack_bf16(n[6] * i1, n[7] * i1);
                v.y = v.y ? v.y : 0x8000u;
                v.w = v.w ? v.w : 0x8000u;
                st_frag(dst + hh * 256, v);
            }
            TS(wg, 11);
        }
        uint4 af[2][12];
        {
            mainloop128(acc, xa, 34, sb, desc128, lane, wg);
            TS(wg, 12);
            if (!p2_s(0) || !p2_s(1) || !p2_s(2)) {
                const int bid = fresh_bid();
                const uint4* a2r = g_A2 + (size_t)(*(volatile unsigned*)(smem + OFF_EPOCH) & 1) * A2_N +
                                   (size_t)(((bid >> 3) * 2 + (bid & 1)) * 18) * 4 * 256 + fresh_tid();
#pragma unroll
                for (int i = 0; i < 12; i++)
                    if (!p2_s(i >> 2)) af[0][i] = ld_frag(a2r + (p2_id(i >> 2) * 4 + (i & 3)) * 256);
            }
            const RowScale r0 = row_scale(sd0), r1 = row_scale(sd1);
            uint4* dst = a2_write_ptr(smem) + (size_t)((14 + (fresh_bid() & 3)) * 4) * 256;
#pragma unroll
            for (int ks = 0; ks < 4; ks++) st_frag(dst + ks * 256, swiglu8(&acc[ks * 8], &acc[32 + ks * 8], r0, r1));
            TS(wg, 15);
        }

        {
            const int tid = fresh_tid(), bid = fresh_bid();
            const int lane = tid & 31, w = (tid >> 5) & 3, g = lane >> 2, t = lane & 3;
            const int rank = bid & 1, m2 = bid >> 3, j2 = (bid >> 1) & 3;
            const uint4* a2r = g_A2 + (size_t)(*(volatile unsigned*)(smem + OFF_EPOCH) & 1) * A2_N +
                               (size_t)((m2 * 2 + rank) * 18) * 4 * 256 + tid;
            float ao[32], ap[32];
            const uint32_t dso = desc128 + 512, dsp = desc128;
            TS(wg, 16);
#pragma unroll
            for (int gi = 0; gi < 6; gi++) {
                if (gi == 5) TS(wg, 17);
                uint4(&f)[12] = af[gi & 1];
#pragma unroll
                for (int bb = 0; bb < 3; bb++) {
                    const int ub = p2_useB(gi * 3 + bb);
                    if (p2_s(gi * 3 + bb)) {
                        mbar_wait(sb + BAR_FULL + 8 * ring_slot(ub - 1), ring_lap(ub - 1) & 1);
                        const uint4* src = (const uint4*)(smem + ring_slot(ub - 1) * STAGE_BYTES) + tid;
#pragma unroll
                        for (int ks = 0; ks < 4; ks++) f[bb * 4 + ks] = src[ks * 256];
                    }
                    mbar_wait(sb + BAR_FULL + 8 * ring_slot(ub), ring_lap(ub) & 1);
                }
                {
                    unsigned n = 0;
                    while (frag_stale(f)) {
#pragma unroll
                        for (int i = 0; i < 12; i++) f[i] = ld_frag(a2r + (p2_id(gi * 3 + (i >> 2)) * 4 + (i & 3)) * 256);
                        if (++n > SPIN_LIMIT) asm volatile("trap;");
                    }
                }
#pragma unroll
                for (int bb = 0; bb < 3; bb++)
                    if (p2_s(gi * 3 + bb) && p2_recycled(p2_useB(gi * 3 + bb) - 1) && lane == bb)
                        mbar_arrive(sb + BAR_EMPTY + 8 * ring_slot(p2_useB(gi * 3 + bb) - 1));
                bar_sync(7 + wg, 256);
                wg_fence();
#pragma unroll
                for (int i = 0; i < 12; i++) {
                    const uint32_t so = ring_slot(p2_useB(gi * 3 + (i >> 2))) * (STAGE_BYTES >> 4) + (i & 3) * 128;
                    const uint32_t* a = reinterpret_cast<const uint32_t*>(&f[i]);
                    wgmma_n64_rs<DHI128>(ap, a, dsp + so, (gi | i) != 0);
                    if (gi < 5) wgmma_n64_rs<DHI128>(ao, a, dso + so, (gi | i) != 0);
                }
                wg_commit();
                bar_arrive(8 - wg, 256);
                if (gi < 5) {
#pragma unroll
                    for (int i = 0; i < 12; i++)
                        if (!p2_s(gi * 3 + 3 + (i >> 2)))
                            af[(gi + 1) & 1][i] = ld_frag(a2r + (p2_id(gi * 3 + 3 + (i >> 2)) * 4 + (i & 3)) * 256);
                    wg_wait<0>();
#pragma unroll
                    for (int bb = 0; bb < 3; bb++)
                        if (p2_recycled(p2_useB(gi * 3 + bb)) && lane == bb)
                            mbar_arrive(sb + BAR_EMPTY + 8 * ring_slot(p2_useB(gi * 3 + bb)));
                }
            }
            const int row0 = m2 * 128 + wg * 64 + w * 16 + g;
            const int col0 = j2 * 128 + rank * 64 + 2 * t;
            uint32_t xr[16];
#pragma unroll
            for (int nb = 0; nb < 8; nb++) {
                xr[2 * nb] = __ldg((const uint32_t*)(xg + (size_t)row0 * 512 + col0 + nb * 8));
                xr[2 * nb + 1] = __ldg((const uint32_t*)(xg + (size_t)(row0 + 8) * 512 + col0 + nb * 8));
            }
            const int xslot = wg ? ring_slot(XCH_USE + 1) : ring_slot(XCH_USE);
            uint32_t rdst, rbar;
            asm volatile("mapa.shared::cluster.u32 %0, %1, %2;"
                         : "=r"(rdst) : "r"(sb + xslot * STAGE_BYTES + (tid & 127) * 16), "r"(rank ^ 1));
            asm volatile("mapa.shared::cluster.u32 %0, %1, %2;" : "=r"(rbar) : "r"(sb + BAR_XCHG), "r"(rank ^ 1));
            mbar_wait(sb + BAR_XRDY, 0);
            wg_wait<0>();
            acc_fence(ap);
            TS(wg, 18);
#pragma unroll
            for (int i = 0; i < 8; i++)
                asm volatile("st.async.shared::cluster.mbarrier::complete_tx::bytes.v4.f32 [%0], {%1,%2,%3,%4}, [%5];"
                             ::"r"(rdst + i * 2048), "f"(ap[4 * i]), "f"(ap[4 * i + 1]), "f"(ap[4 * i + 2]), "f"(ap[4 * i + 3]),
                             "r"(rbar) : "memory");
            bar_sync(7 + wg, 256);
            wg_fence();
#pragma unroll
            for (int i = 0; i < 12; i++)
                wgmma_n64_rs<DHI128>(ao, reinterpret_cast<const uint32_t*>(&af[1][i]),
                                     dso + ring_slot(p2_useB(15 + (i >> 2))) * (STAGE_BYTES >> 4) + (i & 3) * 128, 1);
            wg_commit();
            if (wg == 0) bar_arrive(8, 256);
            wg_wait<0>();
            acc_fence(ao);
            mbar_wait(sb + BAR_XCHG, 0);
            TS(wg, 19);
            const float4* rx = (const float4*)(smem + xslot * STAGE_BYTES) + (tid & 127);
#pragma unroll
            for (int nb = 0; nb < 8; nb++) {
                const float4 p = rx[nb * 128];
                const uint32_t o0 = pack_bf16(ao[4 * nb] + p.x + bf_lo(xr[2 * nb]), ao[4 * nb + 1] + p.y + bf_hi(xr[2 * nb]));
                const uint32_t o1 = pack_bf16(ao[4 * nb + 2] + p.z + bf_lo(xr[2 * nb + 1]), ao[4 * nb + 3] + p.w + bf_hi(xr[2 * nb + 1]));
                *(uint32_t*)(outg + (size_t)row0 * 512 + col0 + nb * 8) = o0;
                *(uint32_t*)(outg + (size_t)(row0 + 8) * 512 + col0 + nb * 8) = o1;
            }
        }
        TS(wg, 20);
    }
}

typedef CUresult (*EncodeFn)(CUtensorMap*, CUtensorMapDataType, cuuint32_t, void*, const cuuint64_t*, const cuuint64_t*,
                             const cuuint32_t*, const cuuint32_t*, CUtensorMapInterleave, CUtensorMapSwizzle,
                             CUtensorMapL2promotion, CUtensorMapFloatOOBfill);

void make_map(EncodeFn enc, CUtensorMap* tm, const void* ptr, int rows, int cols, int box_rows, int box_cols,
              CUtensorMapSwizzle swz) {
    cuuint64_t dims[2] = {(cuuint64_t)cols, (cuuint64_t)rows};
    cuuint64_t strides[1] = {(cuuint64_t)cols * 2};
    cuuint32_t box[2] = {(cuuint32_t)box_cols, (cuuint32_t)box_rows};
    cuuint32_t es[2] = {1, 1};
    enc(tm, CU_TENSOR_MAP_DATA_TYPE_BFLOAT16, 2, const_cast<void*>(ptr), dims, strides, box, es,
        CU_TENSOR_MAP_INTERLEAVE_NONE, swz, CU_TENSOR_MAP_L2_PROMOTION_L2_256B, CU_TENSOR_MAP_FLOAT_OOB_FILL_NONE);
}

}

extern "C" void kernel_launch(void* const* d_in, const int* in_sizes, int n_in, void* d_out, int out_size) {
    (void)in_sizes; (void)n_in; (void)out_size;
    static EncodeFn enc = nullptr;
    if (!enc) {
        void* fn = nullptr;
        cudaDriverEntryPointQueryResult qr;
        cudaGetDriverEntryPoint("cuTensorMapEncodeTiled", &fn, cudaEnableDefault, &qr);
        enc = (EncodeFn)fn;
        cudaFuncSetAttribute(fused_kernel, cudaFuncAttributeMaxDynamicSharedMemorySize, SMEM_BYTES);
    }
    const void* x = d_in[0];
    const void* wqkv = d_in[1];
    const void* wo = d_in[2];
    const void* w1 = d_in[4];
    const void* w3 = d_in[5];
    const void* w2 = d_in[6];
    CUtensorMap tx, tqkv, t1, t3, t1h, t3h, t2, t2h, two;
    make_map(enc, &tx, x, 2048, 512, 128, 64, CU_TENSOR_MAP_SWIZZLE_128B);
    make_map(enc, &tqkv, wqkv, 512, 1536, 64, 64, CU_TENSOR_MAP_SWIZZLE_128B);
    make_map(enc, &t1, w1, 512, 1792, 64, 64, CU_TENSOR_MAP_SWIZZLE_128B);
    make_map(enc, &t3, w3, 512, 1792, 64, 64, CU_TENSOR_MAP_SWIZZLE_128B);
    make_map(enc, &t1h, w1, 512, 1792, 64, 32, CU_TENSOR_MAP_SWIZZLE_64B);
    make_map(enc, &t3h, w3, 512, 1792, 64, 32, CU_TENSOR_MAP_SWIZZLE_64B);
    make_map(enc, &t2, w2, 1792, 512, 64, 64, CU_TENSOR_MAP_SWIZZLE_128B);
    make_map(enc, &t2h, w2, 1792, 512, 32, 64, CU_TENSOR_MAP_SWIZZLE_128B);
    make_map(enc, &two, wo, 512, 512, 64, 64, CU_TENSOR_MAP_SWIZZLE_128B);
    fused_kernel<<<128, 384, SMEM_BYTES>>>(tx, tqkv, t1, t3, t1h, t3h, t2, t2h, two, (const __nv_bfloat16*)x,
                                           (__nv_bfloat16*)d_out, (const char*)wqkv, (const char*)w1, (const char*)w3,
                                           (const char*)w2, (const char*)wo);
}
```

```cpp
#include <cuda_runtime.h>
#include <cuda_bf16.h>
#include <cuda.h>
#include <stdint.h>

namespace {

constexpr int NST = 13;
constexpr int STAGE_BYTES = 16384;
constexpr int XST0 = 5;
constexpr int SCR0 = 8;
#define P2_ORDER {0, 1, 2, 3, 4, 8, 5, 6, 9, 7, 10, 12, 11, 13, 14, 15, 16, 17}
#define P2_SMASK 0x16DFu
__host__ __device__ constexpr int p2_id(int i) {
    constexpr int t[18] = P2_ORDER;
    return t[i];
}
__host__ __device__ constexpr bool p2_s(int i) { return (P2_SMASK >> i) & 1; }
__host__ __device__ constexpr int popc18(unsigned v) {
    v = v - ((v >> 1) & 0x55555555u);
    v = (v & 0x33333333u) + ((v >> 2) & 0x33333333u);
    return (int)((((v + (v >> 4)) & 0x0F0F0F0Fu) * 0x01010101u) >> 24);
}
__host__ __device__ constexpr int p2_useB(int i) { return 42 + i + popc18(P2_SMASK & ((2u << i) - 1)); }
constexpr int XCH_USE = p2_useB(17) + 1;
__host__ __device__ constexpr bool p2_recycled(int u) { return u + NST <= XCH_USE + 1; }
constexpr int OFF_MISC = NST * STAGE_BYTES;
constexpr int OFF_KVB = OFF_MISC;
constexpr int OFF_ONES = OFF_MISC + 3072;
constexpr int OFF_BARS = OFF_MISC + 3328;
constexpr int BAR_FULL = OFF_BARS;
constexpr int BAR_EMPTY = BAR_FULL + 8 * NST;
constexpr int BAR_XFULL = BAR_EMPTY + 8 * NST;
constexpr int BAR_KVREADY = BAR_XFULL + 64;
constexpr int BAR_XCHG = BAR_KVREADY + 8;
constexpr int BAR_EPOCH = BAR_XCHG + 8;
constexpr int BAR_XRDY = BAR_EPOCH + 8;
constexpr int OFF_EPOCH = BAR_XRDY + 8;
constexpr int SMEM_BYTES = OFF_MISC + 4096;

constexpr unsigned SPIN_LIMIT = 1u << 24;

constexpr int A2_N = 16 * 2 * 18 * 4 * 256;
__device__ uint4 g_A2[2 * A2_N];
__device__ float4 g_kvacc[2 * 8 * 272];
__device__ unsigned g_kvcnt[8];
__constant__ unsigned char P2_ID[18] = P2_ORDER;
__device__ unsigned g_epoch;
__device__ unsigned g_ticket;

#define TS(role, i)
#define TSW(role, i)

__device__ __forceinline__ uint32_t smem_u32(const void* p) { return (uint32_t)__cvta_generic_to_shared(p); }
__device__ __forceinline__ void mbar_init(uint32_t bar, uint32_t cnt) {
    asm volatile("mbarrier.init.shared::cta.b64 [%0], %1;" ::"r"(bar), "r"(cnt) : "memory");
}
__device__ __forceinline__ void mbar_expect_tx(uint32_t bar, uint32_t bytes) {
    asm volatile("mbarrier.arrive.expect_tx.shared::cta.b64 _, [%0], %1;" ::"r"(bar), "r"(bytes) : "memory");
}
__device__ __forceinline__ void mbar_arrive(uint32_t bar) {
    asm volatile("mbarrier.arrive.shared::cta.b64 _, [%0];" ::"r"(bar) : "memory");
}
__device__ __forceinline__ void mbar_arrive_cta(uint32_t bar, uint32_t cta) {
    asm volatile(
        "{\n.reg .b32 ra;\nmapa.shared::cluster.u32 ra, %0, %1;\n"
        "mbarrier.arrive.shared::cluster.b64 _, [ra];\n}" ::"r"(bar), "r"(cta) : "memory");
}
__device__ __forceinline__ void mbar_wait(uint32_t bar, uint32_t parity) {
    asm volatile(
        "{\n.reg .pred p, q;\n.reg .u32 n;\nmov.u32 n, 0;\n"
        "WAIT_%=:\n"
        "mbarrier.try_wait.parity.shared::cta.b64 p, [%0], %1;\n"
        "@p bra.uni DONE_%=;\n"
        "add.u32 n, n, 1;\n"
        "setp.gt.u32 q, n, %2;\n"
        "@q trap;\n"
        "bra.uni WAIT_%=;\n"
        "DONE_%=:\n}"
        ::"r"(bar), "r"(parity), "n"(SPIN_LIMIT) : "memory");
}
__device__ __forceinline__ unsigned ld_acquire(const unsigned* p) {
    unsigned v;
    asm volatile("ld.acquire.gpu.global.u32 %0, [%1];" : "=r"(v) : "l"(p) : "memory");
    return v;
}
__device__ __forceinline__ unsigned read_epoch() {
    return __shfl_sync(0xffffffffu, *(volatile unsigned*)&g_epoch, 0) + 1;
}
__device__ __forceinline__ void tma_load(uint32_t dst, const CUtensorMap* tm, uint32_t bar, int x, int y) {
    asm volatile(
        "cp.async.bulk.tensor.2d.shared::cluster.global.mbarrier::complete_tx::bytes [%0], [%1, {%3, %4}], [%2];"
        ::"r"(dst), "l"(tm), "r"(bar), "r"(x), "r"(y) : "memory");
}
__device__ __forceinline__ void tma_load_mc(uint32_t dst, const CUtensorMap* tm, uint32_t bar, int x, int y) {
    asm volatile(
        "cp.async.bulk.tensor.2d.shared::cluster.global.mbarrier::complete_tx::bytes.multicast::cluster "
        "[%0], [%1, {%3, %4}], [%2], %5;"
        ::"r"(dst), "l"(tm), "r"(bar), "r"(x), "r"(y), "h"((uint16_t)3) : "memory");
}
__device__ __forceinline__ void prefetch_tm(const CUtensorMap* tm) {
    asm volatile("prefetch.tensormap [%0];" ::"l"(tm) : "memory");
}
__device__ __forceinline__ void bar_sync(int id, int n) { asm volatile("bar.sync %0, %1;" ::"r"(id), "r"(n) : "memory"); }
__device__ __forceinline__ void bar_arrive(int id, int n) { asm volatile("bar.arrive %0, %1;" ::"r"(id), "r"(n) : "memory"); }
__device__ __forceinline__ void wg_fence() { asm volatile("wgmma.fence.sync.aligned;" ::: "memory"); }
__device__ __forceinline__ void wg_commit() { asm volatile("wgmma.commit_group.sync.aligned;" ::: "memory"); }
template <int N>
__device__ __forceinline__ void wg_wait() { asm volatile("wgmma.wait_group.sync.aligned %0;" ::"n"(N) : "memory"); }

__device__ __forceinline__ uint64_t make_desc(uint32_t addr, uint32_t lbo, uint32_t sbo, uint64_t swz) {
    return (uint64_t)((addr & 0x3FFFF) >> 4) | ((uint64_t)(lbo >> 4) << 16) | ((uint64_t)(sbo >> 4) << 32) | (swz << 62);
}

#define ACC8(a, o) "+f"(a[o]), "+f"(a[o + 1]), "+f"(a[o + 2]), "+f"(a[o + 3]), "+f"(a[o + 4]), "+f"(a[o + 5]), "+f"(a[o + 6]), "+f"(a[o + 7])
constexpr uint32_t DHI128 = (1024u >> 4) | (1u << 30);
constexpr uint32_t DHI64 = (512u >> 4) | (2u << 30);
__device__ __forceinline__ void wgmma_n128_rs(float (&d)[64], const uint32_t* a, uint32_t db, int scale_d) {
    asm volatile(
        "{\n.reg .pred p;\n.reg .b64 dd;\nsetp.ne.b32 p, %69, 0;\nmov.b64 dd, {%68, %70};\n"
        "wgmma.mma_async.sync.aligned.m64n128k16.f32.bf16.bf16 "
        "{%0,%1,%2,%3,%4,%5,%6,%7,%8,%9,%10,%11,%12,%13,%14,%15,%16,%17,%18,%19,%20,%21,%22,%23,%24,%25,%26,%27,%28,%29,%30,%31,"
        "%32,%33,%34,%35,%36,%37,%38,%39,%40,%41,%42,%43,%44,%45,%46,%47,%48,%49,%50,%51,%52,%53,%54,%55,%56,%57,%58,%59,%60,%61,%62,%63},"
        "{%64,%65,%66,%67}, dd, p, 1, 1, 1;\n}"
        : ACC8(d, 0), ACC8(d, 8), ACC8(d, 16), ACC8(d, 24), ACC8(d, 32), ACC8(d, 40), ACC8(d, 48), ACC8(d, 56)
        : "r"(a[0]), "r"(a[1]), "r"(a[2]), "r"(a[3]), "r"(db), "r"(scale_d), "n"(DHI128));
}
template <uint32_t HI>
__device__ __forceinline__ void wgmma_n64_rs(float (&d)[32], const uint32_t* a, uint32_t db, int scale_d) {
    asm volatile(
        "{\n.reg .pred p;\n.reg .b64 dd;\nsetp.ne.b32 p, %37, 0;\nmov.b64 dd, {%36, %38};\n"
        "wgmma.mma_async.sync.aligned.m64n64k16.f32.bf16.bf16 "
        "{%0,%1,%2,%3,%4,%5,%6,%7,%8,%9,%10,%11,%12,%13,%14,%15,%16,%17,%18,%19,%20,%21,%22,%23,%24,%25,%26,%27,%28,%29,%30,%31},"
        "{%32,%33,%34,%35}, dd, p, 1, 1, 1;\n}"
        : ACC8(d, 0), ACC8(d, 8), ACC8(d, 16), ACC8(d, 24)
        : "r"(a[0]), "r"(a[1]), "r"(a[2]), "r"(a[3]), "r"(db), "r"(scale_d), "n"(HI));
}
__device__ __forceinline__ void wgmma_n64_ss_tt(float (&d)[32], uint64_t da, uint64_t db, int scale_d) {
    asm volatile(
        "{\n.reg .pred p;\nsetp.ne.b32 p, %34, 0;\n"
        "wgmma.mma_async.sync.aligned.m64n64k16.f32.bf16.bf16 "
        "{%0,%1,%2,%3,%4,%5,%6,%7,%8,%9,%10,%11,%12,%13,%14,%15,%16,%17,%18,%19,%20,%21,%22,%23,%24,%25,%26,%27,%28,%29,%30,%31},"
        "%32, %33, p, 1, 1, 1, 1;\n}"
        : ACC8(d, 0), ACC8(d, 8), ACC8(d, 16), ACC8(d, 24)
        : "l"(da), "l"(db), "r"(scale_d));
}
__device__ __forceinline__ void wgmma_n8_ss_tn(float (&d)[4], uint64_t da, uint64_t db, int scale_d) {
    asm volatile(
        "{\n.reg .pred p;\nsetp.ne.b32 p, %6, 0;\n"
        "wgmma.mma_async.sync.aligned.m64n8k16.f32.bf16.bf16 {%0,%1,%2,%3}, %4, %5, p, 1, 1, 1, 0;\n}"
        : "+f"(d[0]), "+f"(d[1]), "+f"(d[2]), "+f"(d[3])
        : "l"(da), "l"(db), "r"(scale_d));
}
__device__ __forceinline__ void wgmma_n24_rs(float (&d)[12], const uint32_t* a, uint64_t db) {
    asm volatile(
        "wgmma.mma_async.sync.aligned.m64n24k16.f32.bf16.bf16 {%0,%1,%2,%3,%4,%5,%6,%7,%8,%9,%10,%11}, "
        "{%12,%13,%14,%15}, %16, 0, 1, 1, 0;"
        : ACC8(d, 0), "+f"(d[8]), "+f"(d[9]), "+f"(d[10]), "+f"(d[11])
        : "r"(a[0]), "r"(a[1]), "r"(a[2]), "r"(a[3]), "l"(db));
}
template <int N>
__device__ __forceinline__ void acc_fence(float (&d)[N]) {
#pragma unroll
    for (int i = 0; i < N; i++) asm volatile("" : "+f"(d[i])::"memory");
}
__device__ __forceinline__ void mma16816(float (&c)[4], const uint32_t* a, uint32_t b0, uint32_t b1) {
    asm volatile(
        "mma.sync.aligned.m16n8k16.row.col.f32.bf16.bf16.f32 {%0,%1,%2,%3}, {%4,%5,%6,%7}, {%8,%9}, {%0,%1,%2,%3};"
        : "+f"(c[0]), "+f"(c[1]), "+f"(c[2]), "+f"(c[3])
        : "r"(a[0]), "r"(a[1]), "r"(a[2]), "r"(a[3]), "r"(b0), "r"(b1));
}
__device__ __forceinline__ uint32_t pack_bf16(float lo, float hi) {
    uint32_t r;
    asm("cvt.rn.bf16x2.f32 %0, %1, %2;" : "=r"(r) : "f"(hi), "f"(lo));
    return r;
}
__device__ __forceinline__ float bf_lo(uint32_t v) { return __uint_as_float(v << 16); }
__device__ __forceinline__ float bf_hi(uint32_t v) { return __uint_as_float(v & 0xffff0000u); }
__device__ __forceinline__ float bf16_round(float v) { return __bfloat162float(__float2bfloat16_rn(v)); }
__device__ __forceinline__ float sqrt_fast(float v) {
    float r;
    asm("sqrt.approx.ftz.f32 %0, %1;" : "=f"(r) : "f"(v));
    return r;
}
__device__ __forceinline__ float rcp_fast(float v) {
    float r;
    asm("rcp.approx.ftz.f32 %0, %1;" : "=f"(r) : "f"(v));
    return r;
}
__device__ __forceinline__ float ex2_fast(float v) {
    float r;
    asm("ex2.approx.ftz.f32 %0, %1;" : "=f"(r) : "f"(v));
    return r;
}
__device__ __forceinline__ int fresh_tid() {
    int v;
    asm volatile("mov.u32 %0, %%tid.x;" : "=r"(v));
    return v;
}
__device__ __forceinline__ int fresh_bid() {
    int v;
    asm volatile("mov.u32 %0, %%ctaid.x;" : "=r"(v));
    return v;
}
struct RowScale { float rho, rl, var; };
__device__ __forceinline__ RowScale row_scale(float sd) {
    asm volatile("" : "+f"(sd));
    RowScale r;
    r.rho = rcp_fast(sd);
    r.rl = r.rho * 1.4426950408889634f;
    r.var = sd * sd;
    return r;
}
__device__ __forceinline__ uint4* a2_write_ptr(const uint8_t* smem) {
    const int bid = fresh_bid();
    const unsigned par = *(volatile const unsigned*)(smem + OFF_EPOCH) & 1;
    return g_A2 + (size_t)par * A2_N + (size_t)(((bid >> 3) * 2 + ((bid >> 2) & 1)) * 18) * 4 * 256 + fresh_tid();
}
__device__ __forceinline__ float phi_f(float a, const RowScale& r) {
    return fmaf(fmaxf(a, 0.f), r.rho, ex2_fast(fminf(a, 0.f) * r.rl) + 1e-6f);
}
__device__ __forceinline__ float swiglu_f(float ga, float ua, const RowScale& r) {
    return (ga * ua) * rcp_fast(fmaf(ex2_fast(-ga * r.rl), r.var, r.var));
}
__device__ __forceinline__ uint4 swiglu8(const float* gp, const float* up, const RowScale& r0, const RowScale& r1) {
    uint4 v;
    v.x = pack_bf16(swiglu_f(gp[0], up[0], r0), swiglu_f(gp[1], up[1], r0));
    v.y = pack_bf16(swiglu_f(gp[2], up[2], r1), swiglu_f(gp[3], up[3], r1));
    v.z = pack_bf16(swiglu_f(gp[4], up[4], r0), swiglu_f(gp[5], up[5], r0));
    v.w = pack_bf16(swiglu_f(gp[6], up[6], r1), swiglu_f(gp[7], up[7], r1));
    v.y = v.y ? v.y : 0x8000u;
    v.w = v.w ? v.w : 0x8000u;
    return v;
}
__device__ __forceinline__ bool frag_stale(const uint4 (&f)[12]) {
    unsigned v = min(f[0].y, f[0].w);
#pragma unroll
    for (int i = 1; i < 12; i++) v = min(v, min(f[i].y, f[i].w));
    return __any_sync(0xffffffffu, v == 0u);
}
__device__ __forceinline__ void st_frag(uint4* p, uint4 v) {
    asm volatile("st.relaxed.gpu.global.v4.u32 [%0], {%1,%2,%3,%4};" ::"l"(p), "r"(v.x), "r"(v.y), "r"(v.z), "r"(v.w) : "memory");
}
__device__ __forceinline__ uint4 ld_frag(const uint4* p) {
    uint4 v;
    asm volatile("ld.relaxed.gpu.global.v4.u32 {%0,%1,%2,%3}, [%4];" : "=r"(v.x), "=r"(v.y), "=r"(v.z), "=r"(v.w) : "l"(p) : "memory");
    return v;
}
__device__ __forceinline__ void red_add2(float* p, float a, float b) {
    asm volatile("red.global.add.v2.f32 [%0], {%1, %2};" ::"l"(p), "f"(a), "f"(b) : "memory");
}

__host__ __device__ constexpr int ring_lap(int u) { return (u * 79) >> 10; }
__host__ __device__ constexpr int ring_slot(int u) { return u - NST * ring_lap(u); }

__device__ __forceinline__ void mainloop128(float (&acc)[64], const uint32_t (&xa)[128], int u0, uint32_t sb,
                                            uint32_t desc128, int lane, int wg, bool last = false) {
    bar_sync(7 + wg, 256);
#pragma unroll
    for (int kb = 0; kb < 8; kb++) {
        const int st = ring_slot(u0 + kb);
        mbar_wait(sb + BAR_FULL + 8 * st, ring_lap(u0 + kb) & 1);
        wg_fence();
        const uint32_t d = desc128 + st * (STAGE_BYTES >> 4);
#pragma unroll
        for (int ks = 0; ks < 4; ks++) wgmma_n128_rs(acc, &xa[(kb * 4 + ks) * 4], d + ks * 128, (kb | ks) != 0);
        wg_commit();
        if (kb == 7 && !(last && wg == 1)) bar_arrive(8 - wg, 256);
        if (kb > 0) {
            wg_wait<1>();
            if (lane == 0) mbar_arrive(sb + BAR_EMPTY + 8 * ring_slot(u0 + kb - 1));
        }
    }
    wg_wait<0>();
    acc_fence(acc);
    if (lane == 0) mbar_arrive(sb + BAR_EMPTY + 8 * ring_slot(u0 + 7));
}
__device__ __forceinline__ void mainloop64x2(float (&a0)[32], float (&a1)[32], const uint32_t (&xa)[128], int u0,
                                             uint32_t sb, uint32_t desc128, int lane, int wg) {
    bar_sync(7 + wg, 256);
#pragma unroll
    for (int kb = 0; kb < 8; kb++) {
        const int st = ring_slot(u0 + kb);
        mbar_wait(sb + BAR_FULL + 8 * st, ring_lap(u0 + kb) & 1);
        wg_fence();
        const uint32_t d = desc128 + st * (STAGE_BYTES >> 4);
        const uint32_t d2 = d + (8192 >> 4) - ((4096u >> 4) << 16);
#pragma unroll
        for (int ks = 0; ks < 4; ks++) {
            wgmma_n64_rs<DHI128>(a0, &xa[(kb * 4 + ks) * 4], d + ks * 128, (kb | ks) != 0);
            wgmma_n64_rs<DHI64>(a1, &xa[(kb * 4 + ks) * 4], d2 + ks * 64, (kb | ks) != 0);
        }
        wg_commit();
        if (kb == 7) bar_arrive(8 - wg, 256);
        if (kb > 0) {
            wg_wait<1>();
            if (lane == 0) mbar_arrive(sb + BAR_EMPTY + 8 * ring_slot(u0 + kb - 1));
        }
    }
    wg_wait<0>();
    acc_fence(a0);
    acc_fence(a1);
    if (lane == 0) mbar_arrive(sb + BAR_EMPTY + 8 * ring_slot(u0 + 7));
}

__global__ void __cluster_dims__(2, 1, 1) __launch_bounds__(384, 1)
fused_kernel(const __grid_constant__ CUtensorMap tm_x, const __grid_constant__ CUtensorMap tm_qkv,
             const __grid_constant__ CUtensorMap tm_w1, const __grid_constant__ CUtensorMap tm_w3,
             const __grid_constant__ CUtensorMap tm_w1h, const __grid_constant__ CUtensorMap tm_w3h,
             const __grid_constant__ CUtensorMap tm_w2, const __grid_constant__ CUtensorMap tm_w2h,
             const __grid_constant__ CUtensorMap tm_wo, const __nv_bfloat16* __restrict__ xg,
             __nv_bfloat16* __restrict__ outg) {
    extern __shared__ __align__(1024) uint8_t smem[];
    const uint32_t sb = smem_u32(smem);
    const int tid = threadIdx.x;
    const int warp = tid >> 5, lane = tid & 31;
    const int rank = blockIdx.x & 1;
    const int pair = blockIdx.x >> 1;
    const int m = pair >> 2;
    const int j2 = pair & 3;
    const int c = 2 * j2 + rank;
    const int m2 = m;

    TS(tid >> 7, 0);
    if (tid == 256) {
#pragma unroll
        for (int i = 0; i < 8; i++) mbar_init(sb + BAR_XFULL + 8 * i, 1);
#pragma unroll
        for (int kb = 0; kb < 8; kb++) mbar_expect_tx(sb + BAR_XFULL + 8 * kb, 16384);
        asm volatile("fence.mbarrier_init.release.cluster;" ::: "memory");
        asm volatile("fence.proxy.async.shared::cta;" ::: "memory");
#pragma unroll
        for (int kb = 0; kb < 4; kb++)
            tma_load(sb + (XST0 + kb) * STAGE_BYTES, &tm_x, sb + BAR_XFULL + 8 * kb, kb * 64, m * 128);
        TS(2, 21);
    } else if (tid == 0) {
#pragma unroll
        for (int i = 0; i < NST; i++) mbar_init(sb + BAR_FULL + 8 * i, 1);
        asm volatile("fence.mbarrier_init.release.cluster;" ::: "memory");
    } else if (tid == 32) {
#pragma unroll
        for (int i = 0; i < NST; i++) mbar_init(sb + BAR_EMPTY + 8 * i, 8);
        asm volatile("fence.mbarrier_init.release.cluster;" ::: "memory");
    } else if (tid == 64) {
#pragma unroll
        for (int i = 0; i < 4; i++) mbar_init(sb + BAR_KVREADY + 8 * i, 1);
        mbar_expect_tx(sb + BAR_XCHG, 32768);
        asm volatile("fence.mbarrier_init.release.cluster;" ::: "memory");
    } else if (tid == 288) {
        prefetch_tm(&tm_qkv);
        prefetch_tm(&tm_w1);
        prefetch_tm(&tm_w3);
        prefetch_tm(&tm_w1h);
        prefetch_tm(&tm_w3h);
        prefetch_tm(&tm_w2);
        prefetch_tm(&tm_w2h);
        prefetch_tm(&tm_wo);
    } else if (tid >= 320) {
        ((uint32_t*)(smem + OFF_ONES))[tid - 320] = 0x3F803F80u;
        asm volatile("fence.proxy.async.shared::cta;" ::: "memory");
    }
    __syncthreads();
    TS(tid >> 7, 22);
    asm volatile("barrier.cluster.arrive.relaxed.aligned;\nbarrier.cluster.wait.acquire.aligned;" ::: "memory");

    if (warp >= 8) {
        asm volatile("setmaxnreg.dec.sync.aligned.u32 40;");
        if (warp == 8) {
            if (lane == 0) {
                int st = 0;
                uint32_t lap = 0;
                unsigned par = 0;
#pragma unroll
                for (int i = 2; i < 4; i++) {
                    const int kb = 2 * i + rank;
                    tma_load_mc(sb + (XST0 + kb) * STAGE_BYTES, &tm_x, sb + BAR_XFULL + 8 * kb, kb * 64, m * 128);
                }
                for (int it = 0; it < 40; it++) {
                    const int tile = it >> 3, kb = it & 7;
                    const uint32_t full = sb + BAR_FULL + 8 * st;
                    mbar_wait(sb + BAR_EMPTY + 8 * st, (st >= XST0) ? (lap & 1) : ((lap & 1) ^ 1));
                    mbar_expect_tx(full, STAGE_BYTES);
                    const uint32_t dst = sb + st * STAGE_BYTES;
                    if (tile == 0) {
                        tma_load(dst, &tm_qkv, full, 512 + 64 * c, kb * 64);
                        tma_load(dst + 8192, &tm_qkv, full, 1024 + 64 * c, kb * 64);
                    } else if (tile != 3) {
                        const int col = 224 * c + 64 * (tile == 4 ? 2 : tile - 1);
                        tma_load(dst, &tm_w1, full, col, kb * 64);
                        tma_load(dst + 8192, &tm_w3, full, col, kb * 64);
                    } else {
                        tma_load(dst, &tm_qkv, full, 64 * c, kb * 64);
                        tma_load(dst + 8192, &tm_w1h, full, 224 * c + 192, kb * 64);
                        tma_load(dst + 12288, &tm_w3h, full, 224 * c + 192, kb * 64);
                    }
                    if (++st == NST) { st = 0; lap++; }
                    if (it == 7) {
                        mbar_wait(sb + BAR_EPOCH, 0);
                        par = *(volatile unsigned*)(smem + OFF_EPOCH) & 1;
                        mbar_wait(sb + BAR_EMPTY + 8 * SCR0, 0);
                        mbar_arrive(sb + BAR_FULL + 8 * SCR0);
                        mbar_wait(sb + BAR_EMPTY + 8 * (SCR0 + 1), 0);
                        mbar_arrive(sb + BAR_FULL + 8 * (SCR0 + 1));
                        st += 2;
                    }
                }
                TS(2, 1);
                const char* a2b = (const char*)(g_A2 + (size_t)par * A2_N + (size_t)((m2 * 2 + rank) * 18) * 4 * 256);
#pragma unroll 1
                for (int i = 0; i < 18; i++) {
                    const int b = P2_ID[i];
                    if ((P2_SMASK >> i) & 1) {
                        mbar_wait(sb + BAR_EMPTY + 8 * st, (st >= XST0) ? (lap & 1) : ((lap & 1) ^ 1));
                        mbar_expect_tx(sb + BAR_FULL + 8 * st, STAGE_BYTES);
                        asm volatile("cp.async.bulk.shared::cluster.global.mbarrier::complete_tx::bytes [%0], [%1], 16384, [%2];"
                                     ::"r"(sb + st * STAGE_BYTES), "l"(a2b + b * 16384), "r"(sb + BAR_FULL + 8 * st) : "memory");
                        if (++st == NST) { st = 0; lap++; }
                    }
                    const uint32_t full = sb + BAR_FULL + 8 * st;
                    const uint32_t dst = sb + st * STAGE_BYTES;
                    mbar_wait(sb + BAR_EMPTY + 8 * st, (st >= XST0) ? (lap & 1) : ((lap & 1) ^ 1));
                    mbar_expect_tx(full, STAGE_BYTES);
                    const int cp = 128 * j2 + 64 * (rank ^ 1), co = 128 * j2 + 64 * rank;
                    if (b < 8 || b >= 14) {
                        const int row = (b < 8) ? 224 * (4 * rank + (b & 3)) + 64 * (b >> 2) : 224 * (4 * rank + b - 14) + 128;
                        tma_load(dst, &tm_w2, full, cp, row);
                        tma_load(dst + 8192, &tm_w2, full, co, row);
                    } else if (b < 10) {
                        const int row = 224 * (4 * rank + 2 * (b - 8)) + 192;
                        tma_load(dst, &tm_w2h, full, cp, row);
                        tma_load(dst + 4096, &tm_w2h, full, cp, row + 224);
                        tma_load(dst + 8192, &tm_w2h, full, co, row);
                        tma_load(dst + 12288, &tm_w2h, full, co, row + 224);
                    } else {
                        const int row = 64 * (4 * rank + (b - 10));
                        tma_load(dst, &tm_wo, full, cp, row);
                        tma_load(dst + 8192, &tm_wo, full, co, row);
                    }
                    TS(2, 2 + i);
                    if (++st == NST) { st = 0; lap++; }
                }
#pragma unroll
                for (int k = 0; k < 2; k++)
                    mbar_wait(sb + BAR_EMPTY + 8 * ring_slot(XCH_USE + k),
                              (ring_lap(XCH_USE + k) & 1) ^ (ring_slot(XCH_USE + k) >= XST0 ? 0 : 1));
                mbar_arrive_cta(sb + BAR_XRDY, rank ^ 1);
                TS(2, 20);
            }
        } else if (warp < 11) {
            const int wg = warp - 9;
            bar_sync(3 + wg, 160);
            if (lane == 0) asm volatile("red.release.gpu.global.add.u32 [%0], 1;" ::"l"(&g_kvcnt[c]) : "memory");
            TSW(3, wg);
            mbar_wait(sb + BAR_EPOCH, 0);
            const unsigned par = *(volatile unsigned*)(smem + OFF_EPOCH) & 1;
            uint4* z = g_A2 + (size_t)(par ^ 1) * A2_N + (size_t)((m * 2 + (c >> 2)) * 18) * 4 * 256 + wg * 128 + lane;
            const int cc = c & 3;
#pragma unroll 1
            for (int i = 0; i < 18; i++) {
                const int blk = (i < 8) ? ((i >> 2) * 4 + cc) * 4 + (i & 3)
                              : (i < 10) ? (8 + (cc >> 1)) * 4 + 2 * (cc & 1) + (i - 8)
                              : (i < 14) ? (10 + cc) * 4 + (i - 10) : (14 + cc) * 4 + (i - 14);
#pragma unroll
                for (int k = 0; k < 4; k++) z[blk * 256 + k * 32] = make_uint4(0, 0, 0, 0);
                __nanosleep(300);
            }
        } else {
            const unsigned epoch = read_epoch();
            if (lane == 0) {
                const unsigned tk = atomicInc(&g_ticket, 127u);
                if (tk == 127u) *(volatile unsigned*)&g_epoch = epoch;
            }
            if (lane == 0) *(volatile unsigned*)(smem + OFF_EPOCH) = epoch;
            __syncwarp();
            if (lane == 0) mbar_arrive(sb + BAR_EPOCH);
            if (lane < 17) g_kvacc[(((epoch & 1) ^ 1) * 8 + c) * 272 + 17 * m + lane] = make_float4(0.f, 0.f, 0.f, 0.f);
            {
                unsigned n = 0;
                while ((int)(ld_acquire(&g_kvcnt[c]) - 32u * epoch) < 0) {
                    __nanosleep(200);
                    if (++n > SPIN_LIMIT) asm volatile("trap;");
                }
            }
            TSW(4, 0);
            const int g = lane >> 2, t = lane & 3;
            const float* ks = (const float*)(g_kvacc + ((epoch & 1) * 8 + c) * 272) + 32 * t + g;
            uint32_t* kb = (uint32_t*)(smem + OFF_KVB) + g * 4 + t;
#pragma unroll 2
            for (int hh = 0; hh < 4; hh++) {
                const float* k = ks + hh * 272;
                const float a0 = __ldcg(k), a1 = __ldcg(k + 16), a2 = __ldcg(k + 128), a3 = __ldcg(k + 144);
                const float b0 = __ldcg(k + 8), b1 = __ldcg(k + 24), b2 = __ldcg(k + 136), b3 = __ldcg(k + 152);
                const float2 z0 = __ldcg((const float2*)(k - g - 30 * t + 256)), z1 = __ldcg((const float2*)(k - g - 30 * t + 264));
                uint32_t* o = kb + hh * 192;
                o[0] = pack_bf16(a0, a1);
                o[32] = pack_bf16(a2, a3);
                o[64] = pack_bf16(b0, b1);
                o[96] = pack_bf16(b2, b3);
                o[128] = pack_bf16(z0.x, z0.y);
                o[160] = pack_bf16(z1.x, z1.y);
            }
            asm volatile("fence.proxy.async.shared::cta;" ::: "memory");
            __syncwarp();
            if (lane == 0) mbar_arrive(sb + BAR_KVREADY);
            TSW(4, 4);
        }
    } else {
        asm volatile("setmaxnreg.inc.sync.aligned.u32 232;");
        const int wg = warp >> 2, w = warp & 3;
        const int g = lane >> 2, t = lane & 3;
        float acc[64];
        uint32_t xa[128];
        float sd0, sd1;

        TS(wg, 1);
        {
            const int row = wg * 64 + w * 16 + (lane & 7) + ((lane >> 3) & 1) * 8;
            const uint32_t rbase = sb + XST0 * STAGE_BYTES + row * 128;
            const int hi = lane >> 4, r7 = lane & 7;
            float sm[2][4], c0[2][4], c1[2][4];
#pragma unroll
            for (int i = 0; i < 8; i++) { sm[i >> 2][i & 3] = 0.f; c0[i >> 2][i & 3] = 0.f; c1[i >> 2][i & 3] = 0.f; }
            if (wg == 1) bar_arrive(7, 256);
#pragma unroll
            for (int kb = 0; kb < 8; kb++) {
                mbar_wait(sb + BAR_XFULL + 8 * kb, 0);
#pragma unroll
                for (int ks = 0; ks < 4; ks++) {
                    uint32_t* a = &xa[(kb * 4 + ks) * 4];
                    const uint32_t addr = rbase + kb * STAGE_BYTES + (((2 * ks + hi) ^ r7) << 4);
                    asm volatile("ldmatrix.sync.aligned.m8n8.x4.shared.b16 {%0,%1,%2,%3}, [%4];"
                                 : "=r"(a[0]), "=r"(a[1]), "=r"(a[2]), "=r"(a[3]) : "r"(addr) : "memory");
                    mma16816(sm[ks & 1], a, 0x3F803F80u, 0x3F803F80u);
                    mma16816(c0[ks & 1], a, a[0], a[2]);
                    mma16816(c1[ks & 1], a, a[1], a[3]);
                }
            }
            TS(wg, 2);
            const float mean0 = (sm[0][0] + sm[1][0]) * (1.f / 512.f);
            const float mean1 = (sm[0][2] + sm[1][2]) * (1.f / 512.f);
            __syncwarp();
            if (lane < 8) mbar_arrive(sb + BAR_EMPTY + 8 * (XST0 + lane));
            const __nv_bfloat162 mb0 = __float2bfloat162_rn(mean0), mb1 = __float2bfloat162_rn(mean1);
#pragma unroll
            for (int i = 0; i < 128; i++) {
                __nv_bfloat162 v = *reinterpret_cast<__nv_bfloat162*>(&xa[i]);
                v = __hsub2(v, (i & 1) ? mb1 : mb0);
                xa[i] = *reinterpret_cast<uint32_t*>(&v);
            }
            const float d0 = (g & 1) ? c0[0][1] + c0[1][1] : c0[0][0] + c0[1][0];
            const float d1 = (g & 1) ? c1[0][3] + c1[1][3] : c1[0][2] + c1[1][2];
            const int src = (lane & ~3) | (g >> 1);
            const float var0 = fmaxf(__shfl_sync(0xffffffffu, d0, src) * (1.f / 512.f) - mean0 * mean0, 0.f);
            const float var1 = fmaxf(__shfl_sync(0xffffffffu, d1, src) * (1.f / 512.f) - mean1 * mean1, 0.f);
            sd0 = bf16_round(sqrt_fast(bf16_round(bf16_round(var0) + 1e-5f)));
            sd1 = bf16_round(sqrt_fast(bf16_round(bf16_round(var1) + 1e-5f)));
        }

        TS(wg, 3);
        const uint32_t desc128 = ((sb & 0x3FFFF) >> 4) | ((8192u >> 4) << 16);

        {
            mainloop128(acc, xa, 0, sb, desc128, lane, wg);
            TS(wg, 4);
            {
                TS(wg, 24);
                const RowScale r0 = row_scale(sd0), r1 = row_scale(sd1);
                const float rho0 = r0.rho, rho1 = r1.rho;
                const uint32_t pkb = sb + (SCR0 + wg) * STAGE_BYTES;
                mbar_wait(sb + BAR_FULL + 8 * (SCR0 + wg), 0);
                const uint32_t ra = pkb + (w * 16 + g) * 128 + t * 4;
#pragma unroll
                for (int nb = 0; nb < 8; nb++) {
                    const uint32_t off = (uint32_t)((nb ^ g) << 4);
                    uint32_t p0 = pack_bf16(phi_f(acc[nb * 4], r0), phi_f(acc[nb * 4 + 1], r0));
                    uint32_t p1 = pack_bf16(phi_f(acc[nb * 4 + 2], r1), phi_f(acc[nb * 4 + 3], r1));
                    uint32_t v0 = pack_bf16(acc[32 + nb * 4] * rho0, acc[32 + nb * 4 + 1] * rho0);
                    uint32_t v1 = pack_bf16(acc[32 + nb * 4 + 2] * rho1, acc[32 + nb * 4 + 3] * rho1);
                    asm volatile("st.shared.u32 [%0], %1;" ::"r"(ra + off), "r"(p0) : "memory");
                    asm volatile("st.shared.u32 [%0], %1;" ::"r"(ra + off + 1024), "r"(p1) : "memory");
                    asm volatile("st.shared.u32 [%0], %1;" ::"r"(ra + off + 8192), "r"(v0) : "memory");
                    asm volatile("st.shared.u32 [%0], %1;" ::"r"(ra + off + 8192 + 1024), "r"(v1) : "memory");
                }
                TS(wg, 25);
                asm volatile("fence.proxy.async.shared::cta;" ::: "memory");
                bar_sync(1 + wg, 128);
                TS(wg, 26);
                const uint64_t da = make_desc(pkb, 8192, 1024, 1);
                const uint64_t db = make_desc(pkb + 8192, 8192, 1024, 1);
                const uint64_t d1 = make_desc(sb + OFF_ONES, 128, 128, 0);
                float kva[32], za[4];
                wg_fence();
#pragma unroll
                for (int ks = 0; ks < 4; ks++) {
                    wgmma_n64_ss_tt(kva, da + ks * 128, db + ks * 128, ks != 0);
                    wgmma_n8_ss_tn(za, da + ks * 128, d1, ks != 0);
                }
                wg_commit();
                wg_wait<0>();
                acc_fence(kva);
                acc_fence(za);
                if (lane < 2) mbar_arrive(sb + BAR_EMPTY + 8 * (SCR0 + lane));
                TS(wg, 27);
                float o[8];
#pragma unroll
                for (int i = 0; i < 8; i++)
                    o[i] = (w == 0) ? kva[i] : (w == 1) ? kva[8 + i] : (w == 2) ? kva[16 + i] : kva[24 + i];
                mbar_wait(sb + BAR_EPOCH, 0);
                const unsigned par = *(volatile unsigned*)(smem + OFF_EPOCH) & 1;
                float* dst = (float*)(g_kvacc + (par * 8 + c) * 272) + w * 272 + g * 16 + 2 * t;
                red_add2(dst, o[0], o[1]);
                red_add2(dst + 128, o[2], o[3]);
                red_add2(dst + 8, o[4], o[5]);
                red_add2(dst + 136, o[6], o[7]);
                if (t == 0) {
                    atomicAdd(dst - g * 15 + 256, za[0]);
                    atomicAdd(dst - g * 15 + 264, za[2]);
                }
            }
            bar_arrive(3 + wg, 160);
            TS(wg, 5);
        }
#pragma unroll
        for (int tile = 1; tile < 3; tile++) {
            mainloop128(acc, xa, 2 + 8 * tile, sb, desc128, lane, wg);
            TS(wg, 4 + 2 * tile);
            const RowScale r0 = row_scale(sd0), r1 = row_scale(sd1);
            uint4* dst = a2_write_ptr(smem) + (size_t)((4 * (tile - 1) + (fresh_bid() & 3)) * 4) * 256;
#pragma unroll
            for (int ks = 0; ks < 4; ks++) st_frag(dst + ks * 256, swiglu8(&acc[ks * 8], &acc[32 + ks * 8], r0, r1));
            TS(wg, 5 + 2 * tile);
        }
        {
            float qa[32], gu[32];
            mainloop64x2(qa, gu, xa, 26, sb, desc128, lane, wg);
            TS(wg, 10);
            const RowScale r0 = row_scale(sd0), r1 = row_scale(sd1);
            uint4* const a2w = a2_write_ptr(smem);
            const int cc = fresh_bid() & 3;
            uint4* dst = a2w + (size_t)((8 + (cc >> 1)) * 4 + 2 * (cc & 1)) * 256;
#pragma unroll
            for (int ks = 0; ks < 2; ks++) st_frag(dst + ks * 256, swiglu8(&gu[ks * 8], &gu[16 + ks * 8], r0, r1));
            uint32_t pq[16];
#pragma unroll
            for (int i = 0; i < 16; i++) {
                const RowScale& r = (i & 1) ? r1 : r0;
                pq[i] = pack_bf16(phi_f(qa[2 * i], r), phi_f(qa[2 * i + 1], r));
            }
            TS(wg, 13);
            mbar_wait(sb + BAR_KVREADY, 0);
            TS(wg, 14);
            float nd[4][12];
            const uint64_t dk = make_desc(sb + OFF_KVB, 128, 256, 0);
            wg_fence();
#pragma unroll
            for (int hh = 0; hh < 4; hh++) wgmma_n24_rs(nd[hh], &pq[4 * hh], dk + hh * (768 >> 4));
            wg_commit();
            wg_wait<0>();
            dst = a2w + (size_t)((10 + cc) * 4) * 256;
#pragma unroll
            for (int hh = 0; hh < 4; hh++) {
                acc_fence(nd[hh]);
                const float* n = nd[hh];
                const float i0 = rcp_fast(n[8] + 1e-6f), i1 = rcp_fast(n[10] + 1e-6f);
                uint4 v;
                v.x = pack_bf16(n[0] * i0, n[1] * i0);
                v.y = pack_bf16(n[2] * i1, n[3] * i1);
                v.z = pack_bf16(n[4] * i0, n[5] * i0);
                v.w = pack_bf16(n[6] * i1, n[7] * i1);
                v.y = v.y ? v.y : 0x8000u;
                v.w = v.w ? v.w : 0x8000u;
                st_frag(dst + hh * 256, v);
            }
            TS(wg, 11);
        }
        uint4 af[2][12];
        {
            mainloop128(acc, xa, 34, sb, desc128, lane, wg);
            TS(wg, 12);
            if (!p2_s(0) || !p2_s(1) || !p2_s(2)) {
                const int bid = fresh_bid();
                const uint4* a2r = g_A2 + (size_t)(*(volatile unsigned*)(smem + OFF_EPOCH) & 1) * A2_N +
                                   (size_t)(((bid >> 3) * 2 + (bid & 1)) * 18) * 4 * 256 + fresh_tid();
#pragma unroll
                for (int i = 0; i < 12; i++)
                    if (!p2_s(i >> 2)) af[0][i] = ld_frag(a2r + (p2_id(i >> 2) * 4 + (i & 3)) * 256);
            }
            const RowScale r0 = row_scale(sd0), r1 = row_scale(sd1);
            uint4* dst = a2_write_ptr(smem) + (size_t)((14 + (fresh_bid() & 3)) * 4) * 256;
#pragma unroll
            for (int ks = 0; ks < 4; ks++) st_frag(dst + ks * 256, swiglu8(&acc[ks * 8], &acc[32 + ks * 8], r0, r1));
            TS(wg, 15);
        }

        {
            const int tid = fresh_tid(), bid = fresh_bid();
            const int lane = tid & 31, w = (tid >> 5) & 3, g = lane >> 2, t = lane & 3;
            const int rank = bid & 1, m2 = bid >> 3, j2 = (bid >> 1) & 3;
            const uint4* a2r = g_A2 + (size_t)(*(volatile unsigned*)(smem + OFF_EPOCH) & 1) * A2_N +
                               (size_t)((m2 * 2 + rank) * 18) * 4 * 256 + tid;
            float ao[32], ap[32];
            const uint32_t dso = desc128 + 512, dsp = desc128;
            TS(wg, 16);
#pragma unroll
            for (int gi = 0; gi < 6; gi++) {
                if (gi == 5) TS(wg, 17);
                uint4(&f)[12] = af[gi & 1];
#pragma unroll
                for (int bb = 0; bb < 3; bb++) {
                    const int ub = p2_useB(gi * 3 + bb);
                    if (p2_s(gi * 3 + bb)) {
                        mbar_wait(sb + BAR_FULL + 8 * ring_slot(ub - 1), ring_lap(ub - 1) & 1);
                        const uint4* src = (const uint4*)(smem + ring_slot(ub - 1) * STAGE_BYTES) + tid;
#pragma unroll
                        for (int ks = 0; ks < 4; ks++) f[bb * 4 + ks] = src[ks * 256];
                    }
                    mbar_wait(sb + BAR_FULL + 8 * ring_slot(ub), ring_lap(ub) & 1);
                }
                {
                    unsigned n = 0;
                    while (frag_stale(f)) {
#pragma unroll
                        for (int i = 0; i < 12; i++) f[i] = ld_frag(a2r + (p2_id(gi * 3 + (i >> 2)) * 4 + (i & 3)) * 256);
                        if (++n > SPIN_LIMIT) asm volatile("trap;");
                    }
                }
#pragma unroll
                for (int bb = 0; bb < 3; bb++)
                    if (p2_s(gi * 3 + bb) && p2_recycled(p2_useB(gi * 3 + bb) - 1) && lane == bb)
                        mbar_arrive(sb + BAR_EMPTY + 8 * ring_slot(p2_useB(gi * 3 + bb) - 1));
                bar_sync(7 + wg, 256);
                wg_fence();
#pragma unroll
                for (int i = 0; i < 12; i++) {
                    const uint32_t so = ring_slot(p2_useB(gi * 3 + (i >> 2))) * (STAGE_BYTES >> 4) + (i & 3) * 128;
                    const uint32_t* a = reinterpret_cast<const uint32_t*>(&f[i]);
                    wgmma_n64_rs<DHI128>(ap, a, dsp + so, (gi | i) != 0);
                    if (gi < 5) wgmma_n64_rs<DHI128>(ao, a, dso + so, (gi | i) != 0);
                }
                wg_commit();
                bar_arrive(8 - wg, 256);
                if (gi < 5) {
#pragma unroll
                    for (int i = 0; i < 12; i++)
                        if (!p2_s(gi * 3 + 3 + (i >> 2)))
                            af[(gi + 1) & 1][i] = ld_frag(a2r + (p2_id(gi * 3 + 3 + (i >> 2)) * 4 + (i & 3)) * 256);
                    wg_wait<0>();
#pragma unroll
                    for (int bb = 0; bb < 3; bb++)
                        if (p2_recycled(p2_useB(gi * 3 + bb)) && lane == bb)
                            mbar_arrive(sb + BAR_EMPTY + 8 * ring_slot(p2_useB(gi * 3 + bb)));
                }
            }
            const int row0 = m2 * 128 + wg * 64 + w * 16 + g;
            const int col0 = j2 * 128 + rank * 64 + 2 * t;
            uint32_t xr[16];
#pragma unroll
            for (int nb = 0; nb < 8; nb++) {
                xr[2 * nb] = __ldg((const uint32_t*)(xg + (size_t)row0 * 512 + col0 + nb * 8));
                xr[2 * nb + 1] = __ldg((const uint32_t*)(xg + (size_t)(row0 + 8) * 512 + col0 + nb * 8));
            }
            const int xslot = wg ? ring_slot(XCH_USE + 1) : ring_slot(XCH_USE);
            uint32_t rdst, rbar;
            asm volatile("mapa.shared::cluster.u32 %0, %1, %2;"
                         : "=r"(rdst) : "r"(sb + xslot * STAGE_BYTES + (tid & 127) * 16), "r"(rank ^ 1));
            asm volatile("mapa.shared::cluster.u32 %0, %1, %2;" : "=r"(rbar) : "r"(sb + BAR_XCHG), "r"(rank ^ 1));
            mbar_wait(sb + BAR_XRDY, 0);
            wg_wait<0>();
            acc_fence(ap);
            TS(wg, 18);
#pragma unroll
            for (int i = 0; i < 8; i++)
                asm volatile("st.async.shared::cluster.mbarrier::complete_tx::bytes.v4.f32 [%0], {%1,%2,%3,%4}, [%5];"
                             ::"r"(rdst + i * 2048), "f"(ap[4 * i]), "f"(ap[4 * i + 1]), "f"(ap[4 * i + 2]), "f"(ap[4 * i + 3]),
                             "r"(rbar) : "memory");
            bar_sync(7 + wg, 256);
            wg_fence();
#pragma unroll
            for (int i = 0; i < 12; i++)
                wgmma_n64_rs<DHI128>(ao, reinterpret_cast<const uint32_t*>(&af[1][i]),
                                     dso + ring_slot(p2_useB(15 + (i >> 2))) * (STAGE_BYTES >> 4) + (i & 3) * 128, 1);
            wg_commit();
            if (wg == 0) bar_arrive(8, 256);
            wg_wait<0>();
            acc_fence(ao);
            mbar_wait(sb + BAR_XCHG, 0);
            TS(wg, 19);
            const float4* rx = (const float4*)(smem + xslot * STAGE_BYTES) + (tid & 127);
#pragma unroll
            for (int nb = 0; nb < 8; nb++) {
                const float4 p = rx[nb * 128];
                const uint32_t o0 = pack_bf16(ao[4 * nb] + p.x + bf_lo(xr[2 * nb]), ao[4 * nb + 1] + p.y + bf_hi(xr[2 * nb]));
                const uint32_t o1 = pack_bf16(ao[4 * nb + 2] + p.z + bf_lo(xr[2 * nb + 1]), ao[4 * nb + 3] + p.w + bf_hi(xr[2 * nb + 1]));
                *(uint32_t*)(outg + (size_t)row0 * 512 + col0 + nb * 8) = o0;
                *(uint32_t*)(outg + (size_t)(row0 + 8) * 512 + col0 + nb * 8) = o1;
            }
        }
        TS(wg, 20);
    }
}

typedef CUresult (*EncodeFn)(CUtensorMap*, CUtensorMapDataType, cuuint32_t, void*, const cuuint64_t*, const cuuint64_t*,
                             const cuuint32_t*, const cuuint32_t*, CUtensorMapInterleave, CUtensorMapSwizzle,
                             CUtensorMapL2promotion, CUtensorMapFloatOOBfill);

void make_map(EncodeFn enc, CUtensorMap* tm, const void* ptr, int rows, int cols, int box_rows, int box_cols,
              CUtensorMapSwizzle swz) {
    cuuint64_t dims[2] = {(cuuint64_t)cols, (cuuint64_t)rows};
    cuuint64_t strides[1] = {(cuuint64_t)cols * 2};
    cuuint32_t box[2] = {(cuuint32_t)box_cols, (cuuint32_t)box_rows};
    cuuint32_t es[2] = {1, 1};
    enc(tm, CU_TENSOR_MAP_DATA_TYPE_BFLOAT16, 2, const_cast<void*>(ptr), dims, strides, box, es,
        CU_TENSOR_MAP_INTERLEAVE_NONE, swz, CU_TENSOR_MAP_L2_PROMOTION_L2_256B, CU_TENSOR_MAP_FLOAT_OOB_FILL_NONE);
}

}

extern "C" void kernel_launch(void* const* d_in, const int* in_sizes, int n_in, void* d_out, int out_size) {
    (void)in_sizes; (void)n_in; (void)out_size;
    static EncodeFn enc = nullptr;
    if (!enc) {
        void* fn = nullptr;
        cudaDriverEntryPointQueryResult qr;
        cudaGetDriverEntryPoint("cuTensorMapEncodeTiled", &fn, cudaEnableDefault, &qr);
        enc = (EncodeFn)fn;
        cudaFuncSetAttribute(fused_kernel, cudaFuncAttributeMaxDynamicSharedMemorySize, SMEM_BYTES);
    }
    const void* x = d_in[0];
    const void* wqkv = d_in[1];
    const void* wo = d_in[2];
    const void* w1 = d_in[4];
    const void* w3 = d_in[5];
    const void* w2 = d_in[6];
    CUtensorMap tx, tqkv, t1, t3, t1h, t3h, t2, t2h, two;
    make_map(enc, &tx, x, 2048, 512, 128, 64, CU_TENSOR_MAP_SWIZZLE_128B);
    make_map(enc, &tqkv, wqkv, 512, 1536, 64, 64, CU_TENSOR_MAP_SWIZZLE_128B);
    make_map(enc, &t1, w1, 512, 1792, 64, 64, CU_TENSOR_MAP_SWIZZLE_128B);
    make_map(enc, &t3, w3, 512, 1792, 64, 64, CU_TENSOR_MAP_SWIZZLE_128B);
    make_map(enc, &t1h, w1, 512, 1792, 64, 32, CU_TENSOR_MAP_SWIZZLE_64B);
    make_map(enc, &t3h, w3, 512, 1792, 64, 32, CU_TENSOR_MAP_SWIZZLE_64B);
    make_map(enc, &t2, w2, 1792, 512, 64, 64, CU_TENSOR_MAP_SWIZZLE_128B);
    make_map(enc, &t2h, w2, 1792, 512, 32, 64, CU_TENSOR_MAP_SWIZZLE_128B);
    make_map(enc, &two, wo, 512, 512, 64, 64, CU_TENSOR_MAP_SWIZZLE_128B);
    fused_kernel<<<128, 384, SMEM_BYTES>>>(tx, tqkv, t1, t3, t1h, t3h, t2, t2h, two, (const __nv_bfloat16*)x,
                                           (__nv_bfloat16*)d_out);
}
```

```cpp
#include <cuda_runtime.h>
#include <cuda_bf16.h>
#include <cuda.h>
#include <stdint.h>

namespace {

constexpr int NST = 13;
constexpr int STAGE_BYTES = 16384;
constexpr int XST0 = 5;
constexpr int SCR0 = 8;
#define P2_ORDER {16, 0, 1, 2, 3, 8, 4, 5, 9, 6, 7, 10, 11, 12, 13, 17, 14, 15}
#define P2_SMASK 0x16DEu
__host__ __device__ constexpr int p2_id(int i) {
    constexpr int t[18] = P2_ORDER;
    return t[i];
}
__device__ __forceinline__ int p2_rid(int i, int j2) { return p2_id(i) >= 14 ? 14 + ((j2 + p2_id(i)) & 3) : p2_id(i); }
__host__ __device__ constexpr bool p2_s(int i) { return (P2_SMASK >> i) & 1; }
__host__ __device__ constexpr int popc18(unsigned v) {
    v = v - ((v >> 1) & 0x55555555u);
    v = (v & 0x33333333u) + ((v >> 2) & 0x33333333u);
    return (int)((((v + (v >> 4)) & 0x0F0F0F0Fu) * 0x01010101u) >> 24);
}
__host__ __device__ constexpr int p2_useB(int i) { return 42 + i + popc18(P2_SMASK & ((2u << i) - 1)); }
constexpr int XCH_USE = p2_useB(17) + 1;
__host__ __device__ constexpr bool p2_recycled(int u) { return u + NST <= XCH_USE + 1; }
constexpr int OFF_MISC = NST * STAGE_BYTES;
constexpr int OFF_KVB = OFF_MISC;
constexpr int OFF_ONES = OFF_MISC + 3072;
constexpr int OFF_BARS = OFF_MISC + 3328;
constexpr int BAR_FULL = OFF_BARS;
constexpr int BAR_EMPTY = BAR_FULL + 8 * NST;
constexpr int BAR_XFULL = BAR_EMPTY + 8 * NST;
constexpr int BAR_KVREADY = BAR_XFULL + 64;
constexpr int BAR_XCHG = BAR_KVREADY + 8;
constexpr int BAR_EPOCH = BAR_XCHG + 8;
constexpr int BAR_XRDY = BAR_EPOCH + 8;
constexpr int OFF_EPOCH = BAR_XRDY + 8;
constexpr int SMEM_BYTES = OFF_MISC + 4096;

constexpr unsigned SPIN_LIMIT = 1u << 24;

constexpr int A2_N = 16 * 2 * 18 * 4 * 256;
__device__ uint4 g_A2[2 * A2_N];
__device__ float4 g_kvacc[2 * 8 * 272];
__device__ unsigned g_kvcnt[8];
__constant__ unsigned char P2_ID[18] = P2_ORDER;
__device__ unsigned g_epoch;
__device__ unsigned g_ticket;

#define TS(role, i)
#define TSW(role, i)

__device__ __forceinline__ uint32_t smem_u32(const void* p) { return (uint32_t)__cvta_generic_to_shared(p); }
__device__ __forceinline__ void mbar_init(uint32_t bar, uint32_t cnt) {
    asm volatile("mbarrier.init.shared::cta.b64 [%0], %1;" ::"r"(bar), "r"(cnt) : "memory");
}
__device__ __forceinline__ void mbar_expect_tx(uint32_t bar, uint32_t bytes) {
    asm volatile("mbarrier.arrive.expect_tx.shared::cta.b64 _, [%0], %1;" ::"r"(bar), "r"(bytes) : "memory");
}
__device__ __forceinline__ void mbar_arrive(uint32_t bar) {
    asm volatile("mbarrier.arrive.shared::cta.b64 _, [%0];" ::"r"(bar) : "memory");
}
__device__ __forceinline__ void mbar_arrive_cta(uint32_t bar, uint32_t cta) {
    asm volatile(
        "{\n.reg .b32 ra;\nmapa.shared::cluster.u32 ra, %0, %1;\n"
        "mbarrier.arrive.shared::cluster.b64 _, [ra];\n}" ::"r"(bar), "r"(cta) : "memory");
}
__device__ __forceinline__ void mbar_wait(uint32_t bar, uint32_t parity) {
    asm volatile(
        "{\n.reg .pred p, q;\n.reg .u32 n;\nmov.u32 n, 0;\n"
        "WAIT_%=:\n"
        "mbarrier.try_wait.parity.shared::cta.b64 p, [%0], %1;\n"
        "@p bra.uni DONE_%=;\n"
        "add.u32 n, n, 1;\n"
        "setp.gt.u32 q, n, %2;\n"
        "@q trap;\n"
        "bra.uni WAIT_%=;\n"
        "DONE_%=:\n}"
        ::"r"(bar), "r"(parity), "n"(SPIN_LIMIT) : "memory");
}
__device__ __forceinline__ unsigned ld_acquire(const unsigned* p) {
    unsigned v;
    asm volatile("ld.acquire.gpu.global.u32 %0, [%1];" : "=r"(v) : "l"(p) : "memory");
    return v;
}
__device__ __forceinline__ unsigned read_epoch() {
    return __shfl_sync(0xffffffffu, *(volatile unsigned*)&g_epoch, 0) + 1;
}
__device__ __forceinline__ void tma_load(uint32_t dst, const CUtensorMap* tm, uint32_t bar, int x, int y) {
    asm volatile(
        "cp.async.bulk.tensor.2d.shared::cluster.global.mbarrier::complete_tx::bytes [%0], [%1, {%3, %4}], [%2];"
        ::"r"(dst), "l"(tm), "r"(bar), "r"(x), "r"(y) : "memory");
}
__device__ __forceinline__ void tma_load_mc(uint32_t dst, const CUtensorMap* tm, uint32_t bar, int x, int y) {
    asm volatile(
        "cp.async.bulk.tensor.2d.shared::cluster.global.mbarrier::complete_tx::bytes.multicast::cluster "
        "[%0], [%1, {%3, %4}], [%2], %5;"
        ::"r"(dst), "l"(tm), "r"(bar), "r"(x), "r"(y), "h"((uint16_t)3) : "memory");
}
__device__ __forceinline__ void prefetch_tm(const CUtensorMap* tm) {
    asm volatile("prefetch.tensormap [%0];" ::"l"(tm) : "memory");
}
__device__ __forceinline__ void bar_sync(int id, int n) { asm volatile("bar.sync %0, %1;" ::"r"(id), "r"(n) : "memory"); }
__device__ __forceinline__ void bar_arrive(int id, int n) { asm volatile("bar.arrive %0, %1;" ::"r"(id), "r"(n) : "memory"); }
__device__ __forceinline__ void wg_fence() { asm volatile("wgmma.fence.sync.aligned;" ::: "memory"); }
__device__ __forceinline__ void wg_commit() { asm volatile("wgmma.commit_group.sync.aligned;" ::: "memory"); }
template <int N>
__device__ __forceinline__ void wg_wait() { asm volatile("wgmma.wait_group.sync.aligned %0;" ::"n"(N) : "memory"); }

__device__ __forceinline__ uint64_t make_desc(uint32_t addr, uint32_t lbo, uint32_t sbo, uint64_t swz) {
    return (uint64_t)((addr & 0x3FFFF) >> 4) | ((uint64_t)(lbo >> 4) << 16) | ((uint64_t)(sbo >> 4) << 32) | (swz << 62);
}

#define ACC8(a, o) "+f"(a[o]), "+f"(a[o + 1]), "+f"(a[o + 2]), "+f"(a[o + 3]), "+f"(a[o + 4]), "+f"(a[o + 5]), "+f"(a[o + 6]), "+f"(a[o + 7])
constexpr uint32_t DHI128 = (1024u >> 4) | (1u << 30);
constexpr uint32_t DHI64 = (512u >> 4) | (2u << 30);
__device__ __forceinline__ void wgmma_n128_rs(float (&d)[64], const uint32_t* a, uint32_t db, int scale_d) {
    asm volatile(
        "{\n.reg .pred p;\n.reg .b64 dd;\nsetp.ne.b32 p, %69, 0;\nmov.b64 dd, {%68, %70};\n"
        "wgmma.mma_async.sync.aligned.m64n128k16.f32.bf16.bf16 "
        "{%0,%1,%2,%3,%4,%5,%6,%7,%8,%9,%10,%11,%12,%13,%14,%15,%16,%17,%18,%19,%20,%21,%22,%23,%24,%25,%26,%27,%28,%29,%30,%31,"
        "%32,%33,%34,%35,%36,%37,%38,%39,%40,%41,%42,%43,%44,%45,%46,%47,%48,%49,%50,%51,%52,%53,%54,%55,%56,%57,%58,%59,%60,%61,%62,%63},"
        "{%64,%65,%66,%67}, dd, p, 1, 1, 1;\n}"
        : ACC8(d, 0), ACC8(d, 8), ACC8(d, 16), ACC8(d, 24), ACC8(d, 32), ACC8(d, 40), ACC8(d, 48), ACC8(d, 56)
        : "r"(a[0]), "r"(a[1]), "r"(a[2]), "r"(a[3]), "r"(db), "r"(scale_d), "n"(DHI128));
}
template <uint32_t HI>
__device__ __forceinline__ void wgmma_n64_rs(float (&d)[32], const uint32_t* a, uint32_t db, int scale_d) {
    asm volatile(
        "{\n.reg .pred p;\n.reg .b64 dd;\nsetp.ne.b32 p, %37, 0;\nmov.b64 dd, {%36, %38};\n"
        "wgmma.mma_async.sync.aligned.m64n64k16.f32.bf16.bf16 "
        "{%0,%1,%2,%3,%4,%5,%6,%7,%8,%9,%10,%11,%12,%13,%14,%15,%16,%17,%18,%19,%20,%21,%22,%23,%24,%25,%26,%27,%28,%29,%30,%31},"
        "{%32,%33,%34,%35}, dd, p, 1, 1, 1;\n}"
        : ACC8(d, 0), ACC8(d, 8), ACC8(d, 16), ACC8(d, 24)
        : "r"(a[0]), "r"(a[1]), "r"(a[2]), "r"(a[3]), "r"(db), "r"(scale_d), "n"(HI));
}
__device__ __forceinline__ void wgmma_n64_ss_tt(float (&d)[32], uint64_t da, uint64_t db, int scale_d) {
    asm volatile(
        "{\n.reg .pred p;\nsetp.ne.b32 p, %34, 0;\n"
        "wgmma.mma_async.sync.aligned.m64n64k16.f32.bf16.bf16 "
        "{%0,%1,%2,%3,%4,%5,%6,%7,%8,%9,%10,%11,%12,%13,%14,%15,%16,%17,%18,%19,%20,%21,%22,%23,%24,%25,%26,%27,%28,%29,%30,%31},"
        "%32, %33, p, 1, 1, 1, 1;\n}"
        : ACC8(d, 0), ACC8(d, 8), ACC8(d, 16), ACC8(d, 24)
        : "l"(da), "l"(db), "r"(scale_d));
}
__device__ __forceinline__ void wgmma_n8_ss_tn(float (&d)[4], uint64_t da, uint64_t db, int scale_d) {
    asm volatile(
        "{\n.reg .pred p;\nsetp.ne.b32 p, %6, 0;\n"
        "wgmma.mma_async.sync.aligned.m64n8k16.f32.bf16.bf16 {%0,%1,%2,%3}, %4, %5, p, 1, 1, 1, 0;\n}"
        : "+f"(d[0]), "+f"(d[1]), "+f"(d[2]), "+f"(d[3])
        : "l"(da), "l"(db), "r"(scale_d));
}
__device__ __forceinline__ void wgmma_n24_rs(float (&d)[12], const uint32_t* a, uint64_t db) {
    asm volatile(
        "wgmma.mma_async.sync.aligned.m64n24k16.f32.bf16.bf16 {%0,%1,%2,%3,%4,%5,%6,%7,%8,%9,%10,%11}, "
        "{%12,%13,%14,%15}, %16, 0, 1, 1, 0;"
        : ACC8(d, 0), "+f"(d[8]), "+f"(d[9]), "+f"(d[10]), "+f"(d[11])
        : "r"(a[0]), "r"(a[1]), "r"(a[2]), "r"(a[3]), "l"(db));
}
template <int N>
__device__ __forceinline__ void acc_fence(float (&d)[N]) {
#pragma unroll
    for (int i = 0; i < N; i++) asm volatile("" : "+f"(d[i])::"memory");
}
__device__ __forceinline__ void mma16816(float (&c)[4], const uint32_t* a, uint32_t b0, uint32_t b1) {
    asm volatile(
        "mma.sync.aligned.m16n8k16.row.col.f32.bf16.bf16.f32 {%0,%1,%2,%3}, {%4,%5,%6,%7}, {%8,%9}, {%0,%1,%2,%3};"
        : "+f"(c[0]), "+f"(c[1]), "+f"(c[2]), "+f"(c[3])
        : "r"(a[0]), "r"(a[1]), "r"(a[2]), "r"(a[3]), "r"(b0), "r"(b1));
}
__device__ __forceinline__ uint32_t pack_bf16(float lo, float hi) {
    uint32_t r;
    asm("cvt.rn.bf16x2.f32 %0, %1, %2;" : "=r"(r) : "f"(hi), "f"(lo));
    return r;
}
__device__ __forceinline__ float bf_lo(uint32_t v) { return __uint_as_float(v << 16); }
__device__ __forceinline__ float bf_hi(uint32_t v) { return __uint_as_float(v & 0xffff0000u); }
__device__ __forceinline__ float bf16_round(float v) { return __bfloat162float(__float2bfloat16_rn(v)); }
__device__ __forceinline__ float sqrt_fast(float v) {
    float r;
    asm("sqrt.approx.ftz.f32 %0, %1;" : "=f"(r) : "f"(v));
    return r;
}
__device__ __forceinline__ float rcp_fast(float v) {
    float r;
    asm("rcp.approx.ftz.f32 %0, %1;" : "=f"(r) : "f"(v));
    return r;
}
__device__ __forceinline__ float ex2_fast(float v) {
    float r;
    asm("ex2.approx.ftz.f32 %0, %1;" : "=f"(r) : "f"(v));
    return r;
}
__device__ __forceinline__ int fresh_tid() {
    int v;
    asm volatile("mov.u32 %0, %%tid.x;" : "=r"(v));
    return v;
}
__device__ __forceinline__ int fresh_bid() {
    int v;
    asm volatile("mov.u32 %0, %%ctaid.x;" : "=r"(v));
    return v;
}
struct RowScale { float rho, rl, var; };
__device__ __forceinline__ RowScale row_scale(float sd) {
    asm volatile("" : "+f"(sd));
    RowScale r;
    r.rho = rcp_fast(sd);
    r.rl = r.rho * 1.4426950408889634f;
    r.var = sd * sd;
    return r;
}
__device__ __forceinline__ uint4* a2_write_ptr(const uint8_t* smem) {
    const int bid = fresh_bid();
    const unsigned par = *(volatile const unsigned*)(smem + OFF_EPOCH) & 1;
    return g_A2 + (size_t)par * A2_N + (size_t)(((bid >> 3) * 2 + (bid & 1)) * 18) * 4 * 256 + fresh_tid();
}
__device__ __forceinline__ float phi_f(float a, const RowScale& r) {
    return fmaf(fmaxf(a, 0.f), r.rho, ex2_fast(fminf(a, 0.f) * r.rl) + 1e-6f);
}
__device__ __forceinline__ float swiglu_f(float ga, float ua, const RowScale& r) {
    return (ga * ua) * rcp_fast(fmaf(ex2_fast(-ga * r.rl), r.var, r.var));
}
__device__ __forceinline__ uint4 swiglu8(const float* gp, const float* up, const RowScale& r0, const RowScale& r1) {
    uint4 v;
    v.x = pack_bf16(swiglu_f(gp[0], up[0], r0), swiglu_f(gp[1], up[1], r0));
    v.y = pack_bf16(swiglu_f(gp[2], up[2], r1), swiglu_f(gp[3], up[3], r1));
    v.z = pack_bf16(swiglu_f(gp[4], up[4], r0), swiglu_f(gp[5], up[5], r0));
    v.w = pack_bf16(swiglu_f(gp[6], up[6], r1), swiglu_f(gp[7], up[7], r1));
    v.y = v.y ? v.y : 0x8000u;
    v.w = v.w ? v.w : 0x8000u;
    return v;
}
__device__ __forceinline__ bool frag_stale(const uint4 (&f)[12]) {
    unsigned v = min(f[0].y, f[0].w);
#pragma unroll
    for (int i = 1; i < 12; i++) v = min(v, min(f[i].y, f[i].w));
    return __any_sync(0xffffffffu, v == 0u);
}
__device__ __forceinline__ void st_frag(uint4* p, uint4 v) {
    asm volatile("st.relaxed.gpu.global.v4.u32 [%0], {%1,%2,%3,%4};" ::"l"(p), "r"(v.x), "r"(v.y), "r"(v.z), "r"(v.w) : "memory");
}
__device__ __forceinline__ uint4 ld_frag(const uint4* p) {
    uint4 v;
    asm volatile("ld.relaxed.gpu.global.v4.u32 {%0,%1,%2,%3}, [%4];" : "=r"(v.x), "=r"(v.y), "=r"(v.z), "=r"(v.w) : "l"(p) : "memory");
    return v;
}
__device__ __forceinline__ void red_add2(float* p, float a, float b) {
    asm volatile("red.global.add.v2.f32 [%0], {%1, %2};" ::"l"(p), "f"(a), "f"(b) : "memory");
}

__host__ __device__ constexpr int ring_lap(int u) { return (u * 79) >> 10; }
__host__ __device__ constexpr int ring_slot(int u) { return u - NST * ring_lap(u); }

__device__ __forceinline__ void mainloop128(float (&acc)[64], const uint32_t (&xa)[128], int u0, uint32_t sb,
                                            uint32_t desc128, int lane, int wg, bool last = false) {
    bar_sync(7 + wg, 256);
#pragma unroll
    for (int kb = 0; kb < 8; kb++) {
        const int st = ring_slot(u0 + kb);
        mbar_wait(sb + BAR_FULL + 8 * st, ring_lap(u0 + kb) & 1);
        wg_fence();
        const uint32_t d = desc128 + st * (STAGE_BYTES >> 4);
#pragma unroll
        for (int ks = 0; ks < 4; ks++) wgmma_n128_rs(acc, &xa[(kb * 4 + ks) * 4], d + ks * 128, (kb | ks) != 0);
        wg_commit();
        if (kb == 7 && !(last && wg == 1)) bar_arrive(8 - wg, 256);
        if (kb > 0) {
            wg_wait<1>();
            if (lane == 0) mbar_arrive(sb + BAR_EMPTY + 8 * ring_slot(u0 + kb - 1));
        }
    }
    wg_wait<0>();
    acc_fence(acc);
    if (lane == 0) mbar_arrive(sb + BAR_EMPTY + 8 * ring_slot(u0 + 7));
}
__device__ __forceinline__ void mainloop64x2(float (&a0)[32], float (&a1)[32], const uint32_t (&xa)[128], int u0,
                                             uint32_t sb, uint32_t desc128, int lane, int wg) {
    bar_sync(7 + wg, 256);
#pragma unroll
    for (int kb = 0; kb < 8; kb++) {
        const int st = ring_slot(u0 + kb);
        mbar_wait(sb + BAR_FULL + 8 * st, ring_lap(u0 + kb) & 1);
        wg_fence();
        const uint32_t d = desc128 + st * (STAGE_BYTES >> 4);
        const uint32_t d2 = d + (8192 >> 4) - ((4096u >> 4) << 16);
#pragma unroll
        for (int ks = 0; ks < 4; ks++) {
            wgmma_n64_rs<DHI128>(a0, &xa[(kb * 4 + ks) * 4], d + ks * 128, (kb | ks) != 0);
            wgmma_n64_rs<DHI64>(a1, &xa[(kb * 4 + ks) * 4], d2 + ks * 64, (kb | ks) != 0);
        }
        wg_commit();
        if (kb == 7) bar_arrive(8 - wg, 256);
        if (kb > 0) {
            wg_wait<1>();
            if (lane == 0) mbar_arrive(sb + BAR_EMPTY + 8 * ring_slot(u0 + kb - 1));
        }
    }
    wg_wait<0>();
    acc_fence(a0);
    acc_fence(a1);
    if (lane == 0) mbar_arrive(sb + BAR_EMPTY + 8 * ring_slot(u0 + 7));
}

__global__ void __cluster_dims__(2, 1, 1) __launch_bounds__(384, 1)
fused_kernel(const __grid_constant__ CUtensorMap tm_x, const __grid_constant__ CUtensorMap tm_qkv,
             const __grid_constant__ CUtensorMap tm_w1, const __grid_constant__ CUtensorMap tm_w3,
             const __grid_constant__ CUtensorMap tm_w1h, const __grid_constant__ CUtensorMap tm_w3h,
             const __grid_constant__ CUtensorMap tm_w2, const __grid_constant__ CUtensorMap tm_w2h,
             const __grid_constant__ CUtensorMap tm_wo, const __nv_bfloat16* __restrict__ xg,
             __nv_bfloat16* __restrict__ outg) {
    extern __shared__ __align__(1024) uint8_t smem[];
    const uint32_t sb = smem_u32(smem);
    const int tid = threadIdx.x;
    const int warp = tid >> 5, lane = tid & 31;
    const int rank = blockIdx.x & 1;
    const int pair = blockIdx.x >> 1;
    const int m = pair >> 2;
    const int j2 = pair & 3;
    const int c = 4 * rank + j2;
    const int m2 = m;

    TS(tid >> 7, 0);
    if (tid == 256) {
#pragma unroll
        for (int i = 0; i < 8; i++) mbar_init(sb + BAR_XFULL + 8 * i, 1);
#pragma unroll
        for (int kb = 0; kb < 8; kb++) mbar_expect_tx(sb + BAR_XFULL + 8 * kb, 16384);
        asm volatile("fence.mbarrier_init.release.cluster;" ::: "memory");
        asm volatile("fence.proxy.async.shared::cta;" ::: "memory");
#pragma unroll
        for (int kb = 0; kb < 4; kb++)
            tma_load(sb + (XST0 + kb) * STAGE_BYTES, &tm_x, sb + BAR_XFULL + 8 * kb, kb * 64, m * 128);
        TS(2, 21);
    } else if (tid == 0) {
#pragma unroll
        for (int i = 0; i < NST; i++) mbar_init(sb + BAR_FULL + 8 * i, 1);
        asm volatile("fence.mbarrier_init.release.cluster;" ::: "memory");
    } else if (tid == 32) {
#pragma unroll
        for (int i = 0; i < NST; i++) mbar_init(sb + BAR_EMPTY + 8 * i, 8);
        asm volatile("fence.mbarrier_init.release.cluster;" ::: "memory");
    } else if (tid == 64) {
#pragma unroll
        for (int i = 0; i < 4; i++) mbar_init(sb + BAR_KVREADY + 8 * i, 1);
        mbar_expect_tx(sb + BAR_XCHG, 32768);
        asm volatile("fence.mbarrier_init.release.cluster;" ::: "memory");
    } else if (tid == 288) {
        prefetch_tm(&tm_qkv);
        prefetch_tm(&tm_w1);
        prefetch_tm(&tm_w3);
        prefetch_tm(&tm_w1h);
        prefetch_tm(&tm_w3h);
        prefetch_tm(&tm_w2);
        prefetch_tm(&tm_w2h);
        prefetch_tm(&tm_wo);
    } else if (tid >= 320) {
        ((uint32_t*)(smem + OFF_ONES))[tid - 320] = 0x3F803F80u;
        asm volatile("fence.proxy.async.shared::cta;" ::: "memory");
    }
    __syncthreads();
    TS(tid >> 7, 22);
    asm volatile("barrier.cluster.arrive.relaxed.aligned;\nbarrier.cluster.wait.acquire.aligned;" ::: "memory");

    if (warp >= 8) {
        asm volatile("setmaxnreg.dec.sync.aligned.u32 40;");
        if (warp == 8) {
            if (lane == 0) {
                int st = 0;
                uint32_t lap = 0;
                unsigned par = 0;
#pragma unroll
                for (int i = 2; i < 4; i++) {
                    const int kb = 2 * i + rank;
                    tma_load_mc(sb + (XST0 + kb) * STAGE_BYTES, &tm_x, sb + BAR_XFULL + 8 * kb, kb * 64, m * 128);
                }
                for (int it = 0; it < 40; it++) {
                    const int tile = it >> 3, kb = it & 7;
                    const uint32_t full = sb + BAR_FULL + 8 * st;
                    mbar_wait(sb + BAR_EMPTY + 8 * st, (st >= XST0) ? (lap & 1) : ((lap & 1) ^ 1));
                    mbar_expect_tx(full, STAGE_BYTES);
                    const uint32_t dst = sb + st * STAGE_BYTES;
                    if (tile == 0) {
                        tma_load(dst, &tm_qkv, full, 512 + 64 * c, kb * 64);
                        tma_load(dst + 8192, &tm_qkv, full, 1024 + 64 * c, kb * 64);
                    } else if (tile != 3) {
                        const int col = 224 * c + 64 * (tile == 4 ? 2 : tile - 1);
                        tma_load(dst, &tm_w1, full, col, kb * 64);
                        tma_load(dst + 8192, &tm_w3, full, col, kb * 64);
                    } else {
                        tma_load(dst, &tm_qkv, full, 64 * c, kb * 64);
                        tma_load(dst + 8192, &tm_w1h, full, 224 * c + 192, kb * 64);
                        tma_load(dst + 12288, &tm_w3h, full, 224 * c + 192, kb * 64);
                    }
                    if (++st == NST) { st = 0; lap++; }
                    if (it == 7) {
                        mbar_wait(sb + BAR_EPOCH, 0);
                        par = *(volatile unsigned*)(smem + OFF_EPOCH) & 1;
                        mbar_wait(sb + BAR_EMPTY + 8 * SCR0, 0);
                        mbar_arrive(sb + BAR_FULL + 8 * SCR0);
                        mbar_wait(sb + BAR_EMPTY + 8 * (SCR0 + 1), 0);
                        mbar_arrive(sb + BAR_FULL + 8 * (SCR0 + 1));
                        st += 2;
                    }
                }
                TS(2, 1);
                const char* a2b = (const char*)(g_A2 + (size_t)par * A2_N + (size_t)((m2 * 2 + rank) * 18) * 4 * 256);
#pragma unroll 1
                for (int i = 0; i < 18; i++) {
                    int b = P2_ID[i];
                    if (b >= 14) b = 14 + ((j2 + b) & 3);
                    if ((P2_SMASK >> i) & 1) {
                        mbar_wait(sb + BAR_EMPTY + 8 * st, (st >= XST0) ? (lap & 1) : ((lap & 1) ^ 1));
                        mbar_expect_tx(sb + BAR_FULL + 8 * st, STAGE_BYTES);
                        asm volatile("cp.async.bulk.shared::cluster.global.mbarrier::complete_tx::bytes [%0], [%1], 16384, [%2];"
                                     ::"r"(sb + st * STAGE_BYTES), "l"(a2b + b * 16384), "r"(sb + BAR_FULL + 8 * st) : "memory");
                        if (++st == NST) { st = 0; lap++; }
                    }
                    const uint32_t full = sb + BAR_FULL + 8 * st;
                    const uint32_t dst = sb + st * STAGE_BYTES;
                    mbar_wait(sb + BAR_EMPTY + 8 * st, (st >= XST0) ? (lap & 1) : ((lap & 1) ^ 1));
                    mbar_expect_tx(full, STAGE_BYTES);
                    const int cp = 128 * j2 + 64 * (rank ^ 1), co = 128 * j2 + 64 * rank;
                    if (b < 8 || b >= 14) {
                        const int row = (b < 8) ? 224 * (4 * rank + (b & 3)) + 64 * (b >> 2) : 224 * (4 * rank + b - 14) + 128;
                        tma_load(dst, &tm_w2, full, cp, row);
                        tma_load(dst + 8192, &tm_w2, full, co, row);
                    } else if (b < 10) {
                        const int row = 224 * (4 * rank + 2 * (b - 8)) + 192;
                        tma_load(dst, &tm_w2h, full, cp, row);
                        tma_load(dst + 4096, &tm_w2h, full, cp, row + 224);
                        tma_load(dst + 8192, &tm_w2h, full, co, row);
                        tma_load(dst + 12288, &tm_w2h, full, co, row + 224);
                    } else {
                        const int row = 64 * (4 * rank + (b - 10));
                        tma_load(dst, &tm_wo, full, cp, row);
                        tma_load(dst + 8192, &tm_wo, full, co, row);
                    }
                    TS(2, 2 + i);
                    if (++st == NST) { st = 0; lap++; }
                }
#pragma unroll
                for (int k = 0; k < 2; k++)
                    mbar_wait(sb + BAR_EMPTY + 8 * ring_slot(XCH_USE + k),
                              (ring_lap(XCH_USE + k) & 1) ^ (ring_slot(XCH_USE + k) >= XST0 ? 0 : 1));
                mbar_arrive_cta(sb + BAR_XRDY, rank ^ 1);
                TS(2, 20);
            }
        } else if (warp < 11) {
            const int wg = warp - 9;
            bar_sync(3 + wg, 160);
            if (lane == 0) asm volatile("red.release.gpu.global.add.u32 [%0], 1;" ::"l"(&g_kvcnt[c]) : "memory");
            TSW(3, wg);
            mbar_wait(sb + BAR_EPOCH, 0);
            const unsigned par = *(volatile unsigned*)(smem + OFF_EPOCH) & 1;
            uint4* z = g_A2 + (size_t)(par ^ 1) * A2_N + (size_t)((m * 2 + (c >> 2)) * 18) * 4 * 256 + wg * 128 + lane;
            const int cc = c & 3;
#pragma unroll 1
            for (int i = 0; i < 18; i++) {
                const int blk = (i < 8) ? ((i >> 2) * 4 + cc) * 4 + (i & 3)
                              : (i < 10) ? (8 + (cc >> 1)) * 4 + 2 * (cc & 1) + (i - 8)
                              : (i < 14) ? (10 + cc) * 4 + (i - 10) : (14 + cc) * 4 + (i - 14);
#pragma unroll
                for (int k = 0; k < 4; k++) z[blk * 256 + k * 32] = make_uint4(0, 0, 0, 0);
                __nanosleep(300);
            }
        } else {
            const unsigned epoch = read_epoch();
            if (lane == 0) {
                const unsigned tk = atomicInc(&g_ticket, 127u);
                if (tk == 127u) *(volatile unsigned*)&g_epoch = epoch;
            }
            if (lane == 0) *(volatile unsigned*)(smem + OFF_EPOCH) = epoch;
            __syncwarp();
            if (lane == 0) mbar_arrive(sb + BAR_EPOCH);
            if (lane < 17) g_kvacc[(((epoch & 1) ^ 1) * 8 + c) * 272 + 17 * m + lane] = make_float4(0.f, 0.f, 0.f, 0.f);
            {
                unsigned n = 0;
                while ((int)(ld_acquire(&g_kvcnt[c]) - 32u * epoch) < 0) {
                    __nanosleep(200);
                    if (++n > SPIN_LIMIT) asm volatile("trap;");
                }
            }
            TSW(4, 0);
            const int g = lane >> 2, t = lane & 3;
            const float* ks = (const float*)(g_kvacc + ((epoch & 1) * 8 + c) * 272) + 32 * t + g;
            uint32_t* kb = (uint32_t*)(smem + OFF_KVB) + g * 4 + t;
#pragma unroll 2
            for (int hh = 0; hh < 4; hh++) {
                const float* k = ks + hh * 272;
                const float a0 = __ldcg(k), a1 = __ldcg(k + 16), a2 = __ldcg(k + 128), a3 = __ldcg(k + 144);
                const float b0 = __ldcg(k + 8), b1 = __ldcg(k + 24), b2 = __ldcg(k + 136), b3 = __ldcg(k + 152);
                const float2 z0 = __ldcg((const float2*)(k - g - 30 * t + 256)), z1 = __ldcg((const float2*)(k - g - 30 * t + 264));
                uint32_t* o = kb + hh * 192;
                o[0] = pack_bf16(a0, a1);
                o[32] = pack_bf16(a2, a3);
                o[64] = pack_bf16(b0, b1);
                o[96] = pack_bf16(b2, b3);
                o[128] = pack_bf16(z0.x, z0.y);
                o[160] = pack_bf16(z1.x, z1.y);
            }
            asm volatile("fence.proxy.async.shared::cta;" ::: "memory");
            __syncwarp();
            if (lane == 0) mbar_arrive(sb + BAR_KVREADY);
            TSW(4, 4);
        }
    } else {
        asm volatile("setmaxnreg.inc.sync.aligned.u32 232;");
        const int wg = warp >> 2, w = warp & 3;
        const int g = lane >> 2, t = lane & 3;
        float acc[64];
        uint32_t xa[128];
        float sd0, sd1;

        TS(wg, 1);
        {
            const int row = wg * 64 + w * 16 + (lane & 7) + ((lane >> 3) & 1) * 8;
            const uint32_t rbase = sb + XST0 * STAGE_BYTES + row * 128;
            const int hi = lane >> 4, r7 = lane & 7;
            float sm[2][4], c0[2][4], c1[2][4];
#pragma unroll
            for (int i = 0; i < 8; i++) { sm[i >> 2][i & 3] = 0.f; c0[i >> 2][i & 3] = 0.f; c1[i >> 2][i & 3] = 0.f; }
            if (wg == 1) bar_arrive(7, 256);
#pragma unroll
            for (int kb = 0; kb < 8; kb++) {
                mbar_wait(sb + BAR_XFULL + 8 * kb, 0);
#pragma unroll
                for (int ks = 0; ks < 4; ks++) {
                    uint32_t* a = &xa[(kb * 4 + ks) * 4];
                    const uint32_t addr = rbase + kb * STAGE_BYTES + (((2 * ks + hi) ^ r7) << 4);
                    asm volatile("ldmatrix.sync.aligned.m8n8.x4.shared.b16 {%0,%1,%2,%3}, [%4];"
                                 : "=r"(a[0]), "=r"(a[1]), "=r"(a[2]), "=r"(a[3]) : "r"(addr) : "memory");
                    mma16816(sm[ks & 1], a, 0x3F803F80u, 0x3F803F80u);
                    mma16816(c0[ks & 1], a, a[0], a[2]);
                    mma16816(c1[ks & 1], a, a[1], a[3]);
                }
            }
            TS(wg, 2);
            const float mean0 = (sm[0][0] + sm[1][0]) * (1.f / 512.f);
            const float mean1 = (sm[0][2] + sm[1][2]) * (1.f / 512.f);
            __syncwarp();
            if (lane < 8) mbar_arrive(sb + BAR_EMPTY + 8 * (XST0 + lane));
            const __nv_bfloat162 mb0 = __float2bfloat162_rn(mean0), mb1 = __float2bfloat162_rn(mean1);
#pragma unroll
            for (int i = 0; i < 128; i++) {
                __nv_bfloat162 v = *reinterpret_cast<__nv_bfloat162*>(&xa[i]);
                v = __hsub2(v, (i & 1) ? mb1 : mb0);
                xa[i] = *reinterpret_cast<uint32_t*>(&v);
            }
            const float d0 = (g & 1) ? c0[0][1] + c0[1][1] : c0[0][0] + c0[1][0];
            const float d1 = (g & 1) ? c1[0][3] + c1[1][3] : c1[0][2] + c1[1][2];
            const int src = (lane & ~3) | (g >> 1);
            const float var0 = fmaxf(__shfl_sync(0xffffffffu, d0, src) * (1.f / 512.f) - mean0 * mean0, 0.f);
            const float var1 = fmaxf(__shfl_sync(0xffffffffu, d1, src) * (1.f / 512.f) - mean1 * mean1, 0.f);
            sd0 = bf16_round(sqrt_fast(bf16_round(bf16_round(var0) + 1e-5f)));
            sd1 = bf16_round(sqrt_fast(bf16_round(bf16_round(var1) + 1e-5f)));
        }

        TS(wg, 3);
        const uint32_t desc128 = ((sb & 0x3FFFF) >> 4) | ((8192u >> 4) << 16);

        {
            mainloop128(acc, xa, 0, sb, desc128, lane, wg);
            TS(wg, 4);
            {
                TS(wg, 24);
                const RowScale r0 = row_scale(sd0), r1 = row_scale(sd1);
                const float rho0 = r0.rho, rho1 = r1.rho;
                const uint32_t pkb = sb + (SCR0 + wg) * STAGE_BYTES;
                mbar_wait(sb + BAR_FULL + 8 * (SCR0 + wg), 0);
                const uint32_t ra = pkb + (w * 16 + g) * 128 + t * 4;
#pragma unroll
                for (int nb = 0; nb < 8; nb++) {
                    const uint32_t off = (uint32_t)((nb ^ g) << 4);
                    uint32_t p0 = pack_bf16(phi_f(acc[nb * 4], r0), phi_f(acc[nb * 4 + 1], r0));
                    uint32_t p1 = pack_bf16(phi_f(acc[nb * 4 + 2], r1), phi_f(acc[nb * 4 + 3], r1));
                    uint32_t v0 = pack_bf16(acc[32 + nb * 4] * rho0, acc[32 + nb * 4 + 1] * rho0);
                    uint32_t v1 = pack_bf16(acc[32 + nb * 4 + 2] * rho1, acc[32 + nb * 4 + 3] * rho1);
                    asm volatile("st.shared.u32 [%0], %1;" ::"r"(ra + off), "r"(p0) : "memory");
                    asm volatile("st.shared.u32 [%0], %1;" ::"r"(ra + off + 1024), "r"(p1) : "memory");
                    asm volatile("st.shared.u32 [%0], %1;" ::"r"(ra + off + 8192), "r"(v0) : "memory");
                    asm volatile("st.shared.u32 [%0], %1;" ::"r"(ra + off + 8192 + 1024), "r"(v1) : "memory");
                }
                TS(wg, 25);
                asm volatile("fence.proxy.async.shared::cta;" ::: "memory");
                bar_sync(1 + wg, 128);
                TS(wg, 26);
                const uint64_t da = make_desc(pkb, 8192, 1024, 1);
                const uint64_t db = make_desc(pkb + 8192, 8192, 1024, 1);
                const uint64_t d1 = make_desc(sb + OFF_ONES, 128, 128, 0);
                float kva[32], za[4];
                wg_fence();
#pragma unroll
                for (int ks = 0; ks < 4; ks++) {
                    wgmma_n64_ss_tt(kva, da + ks * 128, db + ks * 128, ks != 0);
                    wgmma_n8_ss_tn(za, da + ks * 128, d1, ks != 0);
                }
                wg_commit();
                wg_wait<0>();
                acc_fence(kva);
                acc_fence(za);
                if (lane < 2) mbar_arrive(sb + BAR_EMPTY + 8 * (SCR0 + lane));
                TS(wg, 27);
                float o[8];
#pragma unroll
                for (int i = 0; i < 8; i++)
                    o[i] = (w == 0) ? kva[i] : (w == 1) ? kva[8 + i] : (w == 2) ? kva[16 + i] : kva[24 + i];
                mbar_wait(sb + BAR_EPOCH, 0);
                const unsigned par = *(volatile unsigned*)(smem + OFF_EPOCH) & 1;
                float* dst = (float*)(g_kvacc + (par * 8 + c) * 272) + w * 272 + g * 16 + 2 * t;
                red_add2(dst, o[0], o[1]);
                red_add2(dst + 128, o[2], o[3]);
                red_add2(dst + 8, o[4], o[5]);
                red_add2(dst + 136, o[6], o[7]);
                if (t == 0) {
                    atomicAdd(dst - g * 15 + 256, za[0]);
                    atomicAdd(dst - g * 15 + 264, za[2]);
                }
            }
            bar_arrive(3 + wg, 160);
            TS(wg, 5);
        }
#pragma unroll
        for (int tile = 1; tile < 3; tile++) {
            mainloop128(acc, xa, 2 + 8 * tile, sb, desc128, lane, wg);
            TS(wg, 4 + 2 * tile);
            const RowScale r0 = row_scale(sd0), r1 = row_scale(sd1);
            uint4* dst = a2_write_ptr(smem) + (size_t)((4 * (tile - 1) + ((fresh_bid() >> 1) & 3)) * 4) * 256;
#pragma unroll
            for (int ks = 0; ks < 4; ks++) st_frag(dst + ks * 256, swiglu8(&acc[ks * 8], &acc[32 + ks * 8], r0, r1));
            TS(wg, 5 + 2 * tile);
        }
        {
            float qa[32], gu[32];
            mainloop64x2(qa, gu, xa, 26, sb, desc128, lane, wg);
            TS(wg, 10);
            const RowScale r0 = row_scale(sd0), r1 = row_scale(sd1);
            uint4* const a2w = a2_write_ptr(smem);
            const int cc = (fresh_bid() >> 1) & 3;
            uint4* dst = a2w + (size_t)((8 + (cc >> 1)) * 4 + 2 * (cc & 1)) * 256;
#pragma unroll
            for (int ks = 0; ks < 2; ks++) st_frag(dst + ks * 256, swiglu8(&gu[ks * 8], &gu[16 + ks * 8], r0, r1));
            uint32_t pq[16];
#pragma unroll
            for (int i = 0; i < 16; i++) {
                const RowScale& r = (i & 1) ? r1 : r0;
                pq[i] = pack_bf16(phi_f(qa[2 * i], r), phi_f(qa[2 * i + 1], r));
            }
            TS(wg, 13);
            mbar_wait(sb + BAR_KVREADY, 0);
            TS(wg, 14);
            float nd[4][12];
            const uint64_t dk = make_desc(sb + OFF_KVB, 128, 256, 0);
            wg_fence();
#pragma unroll
            for (int hh = 0; hh < 4; hh++) wgmma_n24_rs(nd[hh], &pq[4 * hh], dk + hh * (768 >> 4));
            wg_commit();
            wg_wait<0>();
            dst = a2w + (size_t)((10 + cc) * 4) * 256;
#pragma unroll
            for (int hh = 0; hh < 4; hh++) {
                acc_fence(nd[hh]);
                const float* n = nd[hh];
                const float i0 = rcp_fast(n[8] + 1e-6f), i1 = rcp_fast(n[10] + 1e-6f);
                uint4 v;
                v.x = pack_bf16(n[0] * i0, n[1] * i0);
                v.y = pack_bf16(n[2] * i1, n[3] * i1);
                v.z = pack_bf16(n[4] * i0, n[5] * i0);
                v.w = pack_bf16(n[6] * i1, n[7] * i1);
                v.y = v.y ? v.y : 0x8000u;
                v.w = v.w ? v.w : 0x8000u;
                st_frag(dst + hh * 256, v);
            }
            TS(wg, 11);
        }
        uint4 af[2][12];
        {
            mainloop128(acc, xa, 34, sb, desc128, lane, wg);
            TS(wg, 12);
            const RowScale r0 = row_scale(sd0), r1 = row_scale(sd1);
            uint4* dst = a2_write_ptr(smem) + (size_t)((14 + ((fresh_bid() >> 1) & 3)) * 4) * 256;
#pragma unroll
            for (int ks = 0; ks < 4; ks++) {
                af[0][ks] = swiglu8(&acc[ks * 8], &acc[32 + ks * 8], r0, r1);
                st_frag(dst + ks * 256, af[0][ks]);
            }
            TS(wg, 15);
        }

        {
            const int tid = fresh_tid(), bid = fresh_bid();
            const int lane = tid & 31, w = (tid >> 5) & 3, g = lane >> 2, t = lane & 3;
            const int rank = bid & 1, m2 = bid >> 3, j2 = (bid >> 1) & 3;
            const uint4* a2r = g_A2 + (size_t)(*(volatile unsigned*)(smem + OFF_EPOCH) & 1) * A2_N +
                               (size_t)((m2 * 2 + rank) * 18) * 4 * 256 + tid;
            float ao[32], ap[32];
            const uint32_t dso = desc128 + 512, dsp = desc128;
            TS(wg, 16);
#pragma unroll
            for (int gi = 0; gi < 6; gi++) {
                if (gi == 5) TS(wg, 17);
                uint4(&f)[12] = af[gi & 1];
#pragma unroll
                for (int bb = 0; bb < 3; bb++) {
                    const int ub = p2_useB(gi * 3 + bb);
                    if (p2_s(gi * 3 + bb)) {
                        mbar_wait(sb + BAR_FULL + 8 * ring_slot(ub - 1), ring_lap(ub - 1) & 1);
                        const uint4* src = (const uint4*)(smem + ring_slot(ub - 1) * STAGE_BYTES) + tid;
#pragma unroll
                        for (int ks = 0; ks < 4; ks++) f[bb * 4 + ks] = src[ks * 256];
                    }
                    mbar_wait(sb + BAR_FULL + 8 * ring_slot(ub), ring_lap(ub) & 1);
                }
                {
                    unsigned n = 0;
                    while (frag_stale(f)) {
#pragma unroll
                        for (int i = 0; i < 12; i++) f[i] = ld_frag(a2r + (p2_rid(gi * 3 + (i >> 2), j2) * 4 + (i & 3)) * 256);
                        if (++n > SPIN_LIMIT) asm volatile("trap;");
                    }
                }
#pragma unroll
                for (int bb = 0; bb < 3; bb++)
                    if (p2_s(gi * 3 + bb) && p2_recycled(p2_useB(gi * 3 + bb) - 1) && lane == bb)
                        mbar_arrive(sb + BAR_EMPTY + 8 * ring_slot(p2_useB(gi * 3 + bb) - 1));
                bar_sync(7 + wg, 256);
                wg_fence();
#pragma unroll
                for (int i = 0; i < 12; i++) {
                    const uint32_t so = ring_slot(p2_useB(gi * 3 + (i >> 2))) * (STAGE_BYTES >> 4) + (i & 3) * 128;
                    const uint32_t* a = reinterpret_cast<const uint32_t*>(&f[i]);
                    wgmma_n64_rs<DHI128>(ap, a, dsp + so, (gi | i) != 0);
                    if (gi < 5) wgmma_n64_rs<DHI128>(ao, a, dso + so, (gi | i) != 0);
                }
                wg_commit();
                bar_arrive(8 - wg, 256);
                if (gi < 5) {
#pragma unroll
                    for (int i = 0; i < 12; i++)
                        if (!p2_s(gi * 3 + 3 + (i >> 2)))
                            af[(gi + 1) & 1][i] = ld_frag(a2r + (p2_rid(gi * 3 + 3 + (i >> 2), j2) * 4 + (i & 3)) * 256);
                    wg_wait<0>();
#pragma unroll
                    for (int bb = 0; bb < 3; bb++)
                        if (p2_recycled(p2_useB(gi * 3 + bb)) && lane == bb)
                            mbar_arrive(sb + BAR_EMPTY + 8 * ring_slot(p2_useB(gi * 3 + bb)));
                }
            }
            const int row0 = m2 * 128 + wg * 64 + w * 16 + g;
            const int col0 = j2 * 128 + rank * 64 + 2 * t;
            uint32_t xr[16];
#pragma unroll
            for (int nb = 0; nb < 8; nb++) {
                xr[2 * nb] = __ldg((const uint32_t*)(xg + (size_t)row0 * 512 + col0 + nb * 8));
                xr[2 * nb + 1] = __ldg((const uint32_t*)(xg + (size_t)(row0 + 8) * 512 + col0 + nb * 8));
            }
            const int xslot = wg ? ring_slot(XCH_USE + 1) : ring_slot(XCH_USE);
            uint32_t rdst, rbar;
            asm volatile("mapa.shared::cluster.u32 %0, %1, %2;"
                         : "=r"(rdst) : "r"(sb + xslot * STAGE_BYTES + (tid & 127) * 16), "r"(rank ^ 1));
            asm volatile("mapa.shared::cluster.u32 %0, %1, %2;" : "=r"(rbar) : "r"(sb + BAR_XCHG), "r"(rank ^ 1));
            mbar_wait(sb + BAR_XRDY, 0);
            wg_wait<0>();
            acc_fence(ap);
            TS(wg, 18);
#pragma unroll
            for (int i = 0; i < 8; i++)
                asm volatile("st.async.shared::cluster.mbarrier::complete_tx::bytes.v4.f32 [%0], {%1,%2,%3,%4}, [%5];"
                             ::"r"(rdst + i * 2048), "f"(ap[4 * i]), "f"(ap[4 * i + 1]), "f"(ap[4 * i + 2]), "f"(ap[4 * i + 3]),
                             "r"(rbar) : "memory");
            bar_sync(7 + wg, 256);
            wg_fence();
#pragma unroll
            for (int i = 0; i < 12; i++)
                wgmma_n64_rs<DHI128>(ao, reinterpret_cast<const uint32_t*>(&af[1][i]),
                                     dso + ring_slot(p2_useB(15 + (i >> 2))) * (STAGE_BYTES >> 4) + (i & 3) * 128, 1);
            wg_commit();
            if (wg == 0) bar_arrive(8, 256);
            wg_wait<0>();
            acc_fence(ao);
            mbar_wait(sb + BAR_XCHG, 0);
            TS(wg, 19);
            const float4* rx = (const float4*)(smem + xslot * STAGE_BYTES) + (tid & 127);
#pragma unroll
            for (int nb = 0; nb < 8; nb++) {
                const float4 p = rx[nb * 128];
                const uint32_t o0 = pack_bf16(ao[4 * nb] + p.x + bf_lo(xr[2 * nb]), ao[4 * nb + 1] + p.y + bf_hi(xr[2 * nb]));
                const uint32_t o1 = pack_bf16(ao[4 * nb + 2] + p.z + bf_lo(xr[2 * nb + 1]), ao[4 * nb + 3] + p.w + bf_hi(xr[2 * nb + 1]));
                *(uint32_t*)(outg + (size_t)row0 * 512 + col0 + nb * 8) = o0;
                *(uint32_t*)(outg + (size_t)(row0 + 8) * 512 + col0 + nb * 8) = o1;
            }
        }
        TS(wg, 20);
    }
}

typedef CUresult (*EncodeFn)(CUtensorMap*, CUtensorMapDataType, cuuint32_t, void*, const cuuint64_t*, const cuuint64_t*,
                             const cuuint32_t*, const cuuint32_t*, CUtensorMapInterleave, CUtensorMapSwizzle,
                             CUtensorMapL2promotion, CUtensorMapFloatOOBfill);

void make_map(EncodeFn enc, CUtensorMap* tm, const void* ptr, int rows, int cols, int box_rows, int box_cols,
              CUtensorMapSwizzle swz) {
    cuuint64_t dims[2] = {(cuuint64_t)cols, (cuuint64_t)rows};
    cuuint64_t strides[1] = {(cuuint64_t)cols * 2};
    cuuint32_t box[2] = {(cuuint32_t)box_cols, (cuuint32_t)box_rows};
    cuuint32_t es[2] = {1, 1};
    enc(tm, CU_TENSOR_MAP_DATA_TYPE_BFLOAT16, 2, const_cast<void*>(ptr), dims, strides, box, es,
        CU_TENSOR_MAP_INTERLEAVE_NONE, swz, CU_TENSOR_MAP_L2_PROMOTION_L2_256B, CU_TENSOR_MAP_FLOAT_OOB_FILL_NONE);
}

}

extern "C" void kernel_launch(void* const* d_in, const int* in_sizes, int n_in, void* d_out, int out_size) {
    (void)in_sizes; (void)n_in; (void)out_size;
    static EncodeFn enc = nullptr;
    if (!enc) {
        void* fn = nullptr;
        cudaDriverEntryPointQueryResult qr;
        cudaGetDriverEntryPoint("cuTensorMapEncodeTiled", &fn, cudaEnableDefault, &qr);
        enc = (EncodeFn)fn;
        cudaFuncSetAttribute(fused_kernel, cudaFuncAttributeMaxDynamicSharedMemorySize, SMEM_BYTES);
    }
    const void* x = d_in[0];
    const void* wqkv = d_in[1];
    const void* wo = d_in[2];
    const void* w1 = d_in[4];
    const void* w3 = d_in[5];
    const void* w2 = d_in[6];
    CUtensorMap tx, tqkv, t1, t3, t1h, t3h, t2, t2h, two;
    make_map(enc, &tx, x, 2048, 512, 128, 64, CU_TENSOR_MAP_SWIZZLE_128B);
    make_map(enc, &tqkv, wqkv, 512, 1536, 64, 64, CU_TENSOR_MAP_SWIZZLE_128B);
    make_map(enc, &t1, w1, 512, 1792, 64, 64, CU_TENSOR_MAP_SWIZZLE_128B);
    make_map(enc, &t3, w3, 512, 1792, 64, 64, CU_TENSOR_MAP_SWIZZLE_128B);
    make_map(enc, &t1h, w1, 512, 1792, 64, 32, CU_TENSOR_MAP_SWIZZLE_64B);
    make_map(enc, &t3h, w3, 512, 1792, 64, 32, CU_TENSOR_MAP_SWIZZLE_64B);
    make_map(enc, &t2, w2, 1792, 512, 64, 64, CU_TENSOR_MAP_SWIZZLE_128B);
    make_map(enc, &t2h, w2, 1792, 512, 32, 64, CU_TENSOR_MAP_SWIZZLE_128B);
    make_map(enc, &two, wo, 512, 512, 64, 64, CU_TENSOR_MAP_SWIZZLE_128B);
    fused_kernel<<<128, 384, SMEM_BYTES>>>(tx, tqkv, t1, t3, t1h, t3h, t2, t2h, two, (const __nv_bfloat16*)x,
                                           (__nv_bfloat16*)d_out);
}
```
